```python
import torch

def _softmax(x, axis=-1):
    return torch.softmax(x, dim=axis)
def _gelu(x):
    return torch.nn.functional.gelu(x, approximate="tanh")
def _silu(x):
    return torch.nn.functional.silu(x)
def _sigmoid(x):
    return torch.sigmoid(x)
def _layernorm(x, axis=-1, eps=1e-5):
    m = x.mean(dim=axis, keepdim=True)
    v = x.var(dim=axis, keepdim=True, unbiased=False)
    return (x - m) / torch.sqrt(v + eps)
def _scatter_add(tgt, idx, src, axis=0):
    return tgt.clone().index_add_(axis, idx, src)
def _segment_sum(src, seg, n):
    out = torch.zeros((n,) + src.shape[1:], dtype=src.dtype)
    return out.index_add_(0, seg, src)
def _pad(x, pw):
    flat = tuple(v for pair in reversed(pw) for v in pair)
    return torch.nn.functional.pad(x, flat)

kernel_name = 'sequential_preLN__linear_kernel_hedgehog__mixer_token_mlp__prompt'

def setup_inputs():

    _w = (lambda a: (lambda t: t.to(torch.bfloat16) if t.is_floating_point() else t)(torch.as_tensor(a)))
    def _A_setup():
        B, S, D, H = 1, 2048, 576, 32
        Dh = D // H
        return {
            "x": _w((lambda *s: torch.randn(*s, dtype=torch.bfloat16) * 0.05)(B, S, D)),
            "wqkv": _w((lambda *s: torch.randn(*s, dtype=torch.bfloat16) * 0.2)(D, 3 * D)),
            "w_phi": _w((lambda *s: torch.randn(*s, dtype=torch.bfloat16) * 0.2)(H, Dh, Dh) * (Dh ** -0.5)),
            "wo": _w((lambda *s: torch.randn(*s, dtype=torch.bfloat16) * 0.05)(D, D)),
        }
    _A_in = _A_setup()

    def _B_setup():
        B, S, D, F = 1, 2048, 576, 4608
        return {
            "x": _w((lambda *s: torch.randn(*s, dtype=torch.bfloat16) * 0.05)(B, S, D)),
            "w1": _w((lambda *s: torch.randn(*s, dtype=torch.bfloat16) * 0.4)(S, F) * (S ** -0.5)),
            "b1": _w((lambda *s: torch.randn(*s, dtype=torch.bfloat16) * 12.8)(F) * 0.02),
            "w2": _w((lambda *s: torch.randn(*s, dtype=torch.bfloat16) * 0.4)(F, S) * (F ** -0.5)),
            "b2": _w((lambda *s: torch.randn(*s, dtype=torch.bfloat16) * 6.4)(S) * 0.02),
        }
    _B_in = _B_setup()

    return {
        "A_x": _A_in["x"],
        "A_wqkv": _A_in["wqkv"],
        "A_w_phi": _A_in["w_phi"],
        "A_wo": _A_in["wo"],
        "B_x": _B_in["x"],
        "B_w1": _B_in["w1"],
        "B_b1": _B_in["b1"],
        "B_w2": _B_in["w2"],
        "B_b2": _B_in["b2"],
    }

def reference(A_x, A_wqkv, A_w_phi, A_wo, B_x, B_w1, B_b1, B_w2, B_b2):
    def _A_ref(x, wqkv, w_phi, wo):
        B, S, D = x.shape
        H = 32; Dh = D // H
        qkv = (lambda x, *d: x.permute(*d))((x @ wqkv).reshape(B, S, 3, H, Dh), 2, 0, 3, 1, 4)
        q, k, v = qkv[0], qkv[1], qkv[2]
        pq = torch.einsum("bhsd,hdf->bhsf", q, w_phi)
        pk = torch.einsum("bhsd,hdf->bhsf", k, w_phi)
        phi_q = torch.concatenate([_softmax(pq, axis=-1), _softmax(-pq, axis=-1)], axis=-1)
        phi_k = torch.concatenate([_softmax(pk, axis=-1), _softmax(-pk, axis=-1)], axis=-1)
        kv = torch.einsum("bhsf,bhsd->bhfd", phi_k, v)
        z  = torch.einsum("bhsf->bhf", phi_k)
        num = torch.einsum("bhqf,bhfd->bhqd", phi_q, kv)
        den = torch.einsum("bhqf,bhf->bhq", phi_q, z)[..., None] + 1e-6
        o = num / den
        return (lambda x, *d: x.permute(*d))(o, 0, 2, 1, 3).reshape(B, S, D) @ wo

    def _B_ref(x, w1, b1, w2, b2):
        B, S, D = x.shape
        h = _layernorm(x, axis=-1)
        u = torch.einsum("bsd,sf->bdf", h, w1) + b1
        u = _gelu(u)
        y = torch.einsum("bdf,fs->bds", u, w2) + b2
        return (lambda x, *d: x.permute(*d))(y, 0, 2, 1)

    x = A_x
    h = x + _A_ref(_layernorm(x, axis=-1), A_wqkv, A_w_phi, A_wo)
    h2 = h + _B_ref(_layernorm(h, axis=-1), B_w1, B_b1, B_w2, B_b2)
    return h2
```

```cpp
#include <cuda_runtime.h>
#include <cuda.h>
#include <cuda_bf16.h>
#include <stdint.h>
#include <stdlib.h>

typedef __nv_bfloat16 bf16;
#define DEVI __device__ __forceinline__

constexpr int S_ = 2048, D_ = 576, F_ = 4608;
constexpr float LN_EPS = 1e-5f;
constexpr float LOG2E = 1.4426950408889634f;

__device__ __align__(1024) bf16 g_o[S_ * D_];
__device__ __align__(16) float g_cs[8 * 18 * 216];
__device__ __align__(16) float2 g_ln[S_];
__device__ __align__(1024) bf16 g_wqkv[8 * 27 * 72 * 64];
__device__ __align__(1024) bf16 g_wo[8 * 72 * 72 * 8];
constexpr int KV_H = 960;
constexpr int PQ_UNIT = 1168;
__device__ __align__(1024) float g_kv[32 * KV_H];
__device__ __align__(1024) unsigned char g_phiq[32 * 8 * 16 * PQ_UNIT];
__device__ __align__(1024) unsigned long long g_stats[S_ * 8];
__device__ __align__(1024) uint32_t g_h[32 * 8 * 18 * 128];
__device__ __align__(1024) bf16 g_hnT[D_ * S_];
__device__ __align__(1024) bf16 g_u[D_ * F_];
__device__ __align__(16) unsigned int g_flag[256];
#define TL(k, i)
#define CK0()
#define CK1(k)

DEVI uint32_t smem_u32(const void* p) { return (uint32_t)__cvta_generic_to_shared(p); }
DEVI void mbar_init(uint32_t bar, int cnt) { asm volatile("mbarrier.init.shared::cta.b64 [%0], %1;" :: "r"(bar), "r"(cnt) : "memory"); }
DEVI void mbar_expect(uint32_t bar, uint32_t bytes) { asm volatile("mbarrier.arrive.expect_tx.shared::cta.b64 _, [%0], %1;" :: "r"(bar), "r"(bytes) : "memory"); }
DEVI void mbar_wait(uint32_t bar, uint32_t parity) {
    asm volatile("{\n.reg .pred p;\n.reg .u32 it;\n"
                 "mbarrier.try_wait.parity.shared::cta.b64 p, [%0], %1;\n@p bra MW_DONE;\n"
                 "mov.u32 it, 0;\n"
                 "MW_LOOP:\nmbarrier.try_wait.parity.shared::cta.b64 p, [%0], %1;\n@p bra MW_DONE;\n"
                 "add.u32 it, it, 1;\nsetp.lt.u32 p, it, 4194304;\n@p bra MW_LOOP;\ntrap;\n"
                 "MW_DONE:\n}" :: "r"(bar), "r"(parity) : "memory");
}
DEVI void mbar_arrive(uint32_t bar) { asm volatile("mbarrier.arrive.shared::cta.b64 _, [%0];" :: "r"(bar) : "memory"); }
DEVI uint32_t mapa(uint32_t addr, uint32_t cta) { uint32_t r; asm volatile("mapa.shared::cluster.u32 %0, %1, %2;" : "=r"(r) : "r"(addr), "r"(cta)); return r; }
DEVI void mbar_arrive_remote(uint32_t raddr) { asm volatile("mbarrier.arrive.shared::cluster.b64 _, [%0];" :: "r"(raddr) : "memory"); }
DEVI void fence_mbar_init() { asm volatile("fence.mbarrier_init.release.cluster;" ::: "memory"); }
DEVI void fence_async_smem() { asm volatile("fence.proxy.async.shared::cta;" ::: "memory"); }
DEVI void cluster_arrive() { asm volatile("barrier.cluster.arrive.aligned;" ::: "memory"); }
DEVI void cluster_arrive_relaxed() { asm volatile("barrier.cluster.arrive.relaxed.aligned;" ::: "memory"); }
DEVI void cluster_wait() { asm volatile("barrier.cluster.wait.aligned;" ::: "memory"); }
DEVI void bar_sync(int id, int n) { asm volatile("bar.sync %0, %1;" :: "r"(id), "r"(n) : "memory"); }
DEVI void bar_arrive(int id, int n) { asm volatile("bar.arrive %0, %1;" :: "r"(id), "r"(n) : "memory"); }
DEVI void pdl_wait() { asm volatile("griddepcontrol.wait;" ::: "memory"); }
DEVI void pdl_trigger() { asm volatile("griddepcontrol.launch_dependents;" ::: "memory"); }
DEVI void bulk_g2s(uint32_t dst, const void* src, uint32_t bytes, uint32_t bar) {
    asm volatile("cp.async.bulk.shared::cluster.global.mbarrier::complete_tx::bytes [%0], [%1], %2, [%3];" :: "r"(dst), "l"(src), "r"(bytes), "r"(bar) : "memory");
}
DEVI void bulk_g2s_mc(uint32_t dst, const void* src, uint32_t bytes, uint32_t bar, uint16_t mask) {
    asm volatile("cp.async.bulk.shared::cluster.global.mbarrier::complete_tx::bytes.multicast::cluster [%0], [%1], %2, [%3], %4;" :: "r"(dst), "l"(src), "r"(bytes), "r"(bar), "h"(mask) : "memory");
}
DEVI void bulk_s2s(uint32_t rdst, uint32_t src, uint32_t bytes, uint32_t rbar) {
    asm volatile("cp.async.bulk.shared::cluster.shared::cta.mbarrier::complete_tx::bytes [%0], [%1], %2, [%3];" :: "r"(rdst), "r"(src), "r"(bytes), "r"(rbar) : "memory");
}
DEVI void bulk_s2g(void* dst, uint32_t src, uint32_t bytes) {
    asm volatile("cp.async.bulk.global.shared::cta.bulk_group [%0], [%1], %2;" :: "l"(dst), "r"(src), "r"(bytes) : "memory");
}
DEVI void l2_prefetch(const void* p, uint32_t bytes) { asm volatile("cp.async.bulk.prefetch.L2.global [%0], %1;" :: "l"(p), "r"(bytes) : "memory"); }
DEVI void bulk_commit() { asm volatile("cp.async.bulk.commit_group;" ::: "memory"); }
DEVI void bulk_wait_read() { asm volatile("cp.async.bulk.wait_group.read 0;" ::: "memory"); }
DEVI void tma2d(uint32_t dst, const CUtensorMap* tm, uint32_t bar, int c0, int c1) {
    asm volatile("cp.async.bulk.tensor.2d.shared::cluster.global.mbarrier::complete_tx::bytes [%0], [%1, {%3, %4}], [%2];" :: "r"(dst), "l"(tm), "r"(bar), "r"(c0), "r"(c1) : "memory");
}
DEVI void tma3d(uint32_t dst, const CUtensorMap* tm, uint32_t bar, int c0, int c1, int c2) {
    asm volatile("cp.async.bulk.tensor.3d.shared::cluster.global.mbarrier::complete_tx::bytes [%0], [%1, {%3, %4, %5}], [%2];" :: "r"(dst), "l"(tm), "r"(bar), "r"(c0), "r"(c1), "r"(c2) : "memory");
}
DEVI void tma3d_mc(uint32_t dst, const CUtensorMap* tm, uint32_t bar, int c0, int c1, int c2, uint16_t mask) {
    asm volatile("cp.async.bulk.tensor.3d.shared::cluster.global.mbarrier::complete_tx::bytes.multicast::cluster [%0], [%1, {%3, %4, %5}], [%2], %6;" :: "r"(dst), "l"(tm), "r"(bar), "r"(c0), "r"(c1), "r"(c2), "h"(mask) : "memory");
}
DEVI void tma2d_store(const CUtensorMap* tm, uint32_t src, int c0, int c1) {
    asm volatile("cp.async.bulk.tensor.2d.global.shared::cta.bulk_group [%0, {%2, %3}], [%1];" :: "l"(tm), "r"(src), "r"(c0), "r"(c1) : "memory");
}
DEVI void prefetch_tm(const CUtensorMap* tm) { asm volatile("prefetch.tensormap [%0];" :: "l"(tm) : "memory"); }
DEVI uint64_t mkdesc(uint32_t addr, uint32_t lbo, uint32_t sbo, uint64_t swz) {
    return (uint64_t)((addr & 0x3FFFF) >> 4) | ((uint64_t)(lbo >> 4) << 16) | ((uint64_t)(sbo >> 4) << 32) | (swz << 62);
}
DEVI uint64_t dadv(uint64_t d, uint32_t bytes) { return (d & 0xffffffff00000000ull) | (uint64_t)((uint32_t)d + (bytes >> 4)); }
DEVI void wg_fence() { asm volatile("wgmma.fence.sync.aligned;" ::: "memory"); }
DEVI void wg_commit() { asm volatile("wgmma.commit_group.sync.aligned;" ::: "memory"); }
template<int N> DEVI void wg_wait() { asm volatile("wgmma.wait_group.sync.aligned %0;" :: "n"(N) : "memory"); }
template<int N> DEVI void reg_fence(float* d) {
    #pragma unroll
    for (int i = 0; i < N; i++) asm volatile("" : "+f"(d[i]) :: "memory");
}
DEVI uint32_t pack2(float lo, float hi) { uint32_t r; asm("cvt.rn.bf16x2.f32 %0, %1, %2;" : "=r"(r) : "f"(hi), "f"(lo)); return r; }
DEVI float bf_lo(uint32_t v) { return __uint_as_float(v << 16); }
DEVI float bf_hi(uint32_t v) { return __uint_as_float(v & 0xffff0000u); }
DEVI float ex2(float x) { float r; asm("ex2.approx.ftz.f32 %0, %1;" : "=f"(r) : "f"(x)); return r; }
DEVI float rcp(float x) { float r; asm("rcp.approx.ftz.f32 %0, %1;" : "=f"(r) : "f"(x)); return r; }
DEVI float tanh_fast(float x) { float r; asm("tanh.approx.f32 %0, %1;" : "=f"(r) : "f"(x)); return r; }
DEVI void mma16816(float* c, uint32_t a0, uint32_t a1, uint32_t a2, uint32_t a3, uint32_t b0, uint32_t b1) {
    asm volatile("mma.sync.aligned.m16n8k16.row.col.f32.bf16.bf16.f32 {%0,%1,%2,%3}, {%4,%5,%6,%7}, {%8,%9}, {%0,%1,%2,%3};"
        : "+f"(c[0]), "+f"(c[1]), "+f"(c[2]), "+f"(c[3]) : "r"(a0), "r"(a1), "r"(a2), "r"(a3), "r"(b0), "r"(b1));
}
DEVI void mma1688(float* c, uint32_t a0, uint32_t a1, uint32_t b0) {
    asm volatile("mma.sync.aligned.m16n8k8.row.col.f32.bf16.bf16.f32 {%0,%1,%2,%3}, {%4,%5}, {%6}, {%0,%1,%2,%3};"
        : "+f"(c[0]), "+f"(c[1]), "+f"(c[2]), "+f"(c[3]) : "r"(a0), "r"(a1), "r"(b0));
}
DEVI void ldsm4t(uint32_t addr, uint32_t& r0, uint32_t& r1, uint32_t& r2, uint32_t& r3) {
    asm volatile("ldmatrix.sync.aligned.m8n8.x4.trans.shared.b16 {%0,%1,%2,%3}, [%4];" : "=r"(r0), "=r"(r1), "=r"(r2), "=r"(r3) : "r"(addr) : "memory");
}
DEVI void stsm4t(uint32_t addr, uint32_t r0, uint32_t r1, uint32_t r2, uint32_t r3) {
    asm volatile("stmatrix.sync.aligned.m8n8.x4.trans.shared.b16 [%0], {%1,%2,%3,%4};" :: "r"(addr), "r"(r0), "r"(r1), "r"(r2), "r"(r3) : "memory");
}
DEVI void stsm2t(uint32_t addr, uint32_t r0, uint32_t r1) {
    asm volatile("stmatrix.sync.aligned.m8n8.x2.trans.shared.b16 [%0], {%1,%2};" :: "r"(addr), "r"(r0), "r"(r1) : "memory");
}
DEVI void stsm4(uint32_t addr, uint32_t r0, uint32_t r1, uint32_t r2, uint32_t r3) {
    asm volatile("stmatrix.sync.aligned.m8n8.x4.shared.b16 [%0], {%1,%2,%3,%4};" :: "r"(addr), "r"(r0), "r"(r1), "r"(r2), "r"(r3) : "memory");
}
DEVI void stsm2(uint32_t addr, uint32_t r0, uint32_t r1) {
    asm volatile("stmatrix.sync.aligned.m8n8.x2.shared.b16 [%0], {%1,%2};" :: "r"(addr), "r"(r0), "r"(r1) : "memory");
}
DEVI void sts128(uint32_t addr, uint32_t r0, uint32_t r1, uint32_t r2, uint32_t r3) {
    asm volatile("st.shared.v4.b32 [%0], {%1,%2,%3,%4};" :: "r"(addr), "r"(r0), "r"(r1), "r"(r2), "r"(r3) : "memory");
}
DEVI uint32_t lds32(uint32_t addr) { uint32_t r; asm volatile("ld.shared.b32 %0, [%1];" : "=r"(r) : "r"(addr) : "memory"); return r; }
DEVI void sts32(uint32_t addr, uint32_t r0) { asm volatile("st.shared.b32 [%0], %1;" :: "r"(addr), "r"(r0) : "memory"); }
template<int TA, int TB> DEVI void wgmma_n48(float* d, uint64_t da, uint64_t db, int sd) {
  asm volatile("{\n.reg .pred p;\nsetp.ne.b32 p, %26, 0;\n"
    "wgmma.mma_async.sync.aligned.m64n48k16.f32.bf16.bf16 {%0, %1, %2, %3, %4, %5, %6, %7, %8, %9, %10, %11, %12, %13, %14, %15, %16, %17, %18, %19, %20, %21, %22, %23}, %24, %25, p, 1, 1, %27, %28;\n}\n"
    : "+f"(d[0]), "+f"(d[1]), "+f"(d[2]), "+f"(d[3]), "+f"(d[4]), "+f"(d[5]), "+f"(d[6]), "+f"(d[7]), "+f"(d[8]), "+f"(d[9]), "+f"(d[10]), "+f"(d[11]), "+f"(d[12]), "+f"(d[13]), "+f"(d[14]), "+f"(d[15]), "+f"(d[16]), "+f"(d[17]), "+f"(d[18]), "+f"(d[19]), "+f"(d[20]), "+f"(d[21]), "+f"(d[22]), "+f"(d[23]) : "l"(da), "l"(db), "r"(sd), "n"(TA), "n"(TB));
}
template<int TA, int TB> DEVI void wgmma_n72(float* d, uint64_t da, uint64_t db, int sd) {
  asm volatile("{\n.reg .pred p;\nsetp.ne.b32 p, %38, 0;\n"
    "wgmma.mma_async.sync.aligned.m64n72k16.f32.bf16.bf16 {%0, %1, %2, %3, %4, %5, %6, %7, %8, %9, %10, %11, %12, %13, %14, %15, %16, %17, %18, %19, %20, %21, %22, %23, %24, %25, %26, %27, %28, %29, %30, %31, %32, %33, %34, %35}, %36, %37, p, 1, 1, %39, %40;\n}\n"
    : "+f"(d[0]), "+f"(d[1]), "+f"(d[2]), "+f"(d[3]), "+f"(d[4]), "+f"(d[5]), "+f"(d[6]), "+f"(d[7]), "+f"(d[8]), "+f"(d[9]), "+f"(d[10]), "+f"(d[11]), "+f"(d[12]), "+f"(d[13]), "+f"(d[14]), "+f"(d[15]), "+f"(d[16]), "+f"(d[17]), "+f"(d[18]), "+f"(d[19]), "+f"(d[20]), "+f"(d[21]), "+f"(d[22]), "+f"(d[23]), "+f"(d[24]), "+f"(d[25]), "+f"(d[26]), "+f"(d[27]), "+f"(d[28]), "+f"(d[29]), "+f"(d[30]), "+f"(d[31]), "+f"(d[32]), "+f"(d[33]), "+f"(d[34]), "+f"(d[35]) : "l"(da), "l"(db), "r"(sd), "n"(TA), "n"(TB));
}
template<int TA, int TB> DEVI void wgmma_n96(float* d, uint64_t da, uint64_t db, int sd) {
  asm volatile("{\n.reg .pred p;\nsetp.ne.b32 p, %50, 0;\n"
    "wgmma.mma_async.sync.aligned.m64n96k16.f32.bf16.bf16 {%0, %1, %2, %3, %4, %5, %6, %7, %8, %9, %10, %11, %12, %13, %14, %15, %16, %17, %18, %19, %20, %21, %22, %23, %24, %25, %26, %27, %28, %29, %30, %31, %32, %33, %34, %35, %36, %37, %38, %39, %40, %41, %42, %43, %44, %45, %46, %47}, %48, %49, p, 1, 1, %51, %52;\n}\n"
    : "+f"(d[0]), "+f"(d[1]), "+f"(d[2]), "+f"(d[3]), "+f"(d[4]), "+f"(d[5]), "+f"(d[6]), "+f"(d[7]), "+f"(d[8]), "+f"(d[9]), "+f"(d[10]), "+f"(d[11]), "+f"(d[12]), "+f"(d[13]), "+f"(d[14]), "+f"(d[15]), "+f"(d[16]), "+f"(d[17]), "+f"(d[18]), "+f"(d[19]), "+f"(d[20]), "+f"(d[21]), "+f"(d[22]), "+f"(d[23]), "+f"(d[24]), "+f"(d[25]), "+f"(d[26]), "+f"(d[27]), "+f"(d[28]), "+f"(d[29]), "+f"(d[30]), "+f"(d[31]), "+f"(d[32]), "+f"(d[33]), "+f"(d[34]), "+f"(d[35]), "+f"(d[36]), "+f"(d[37]), "+f"(d[38]), "+f"(d[39]), "+f"(d[40]), "+f"(d[41]), "+f"(d[42]), "+f"(d[43]), "+f"(d[44]), "+f"(d[45]), "+f"(d[46]), "+f"(d[47]) : "l"(da), "l"(db), "r"(sd), "n"(TA), "n"(TB));
}
template<int TA, int TB> DEVI void wgmma_n144(float* d, uint64_t da, uint64_t db, int sd) {
  asm volatile("{\n.reg .pred p;\nsetp.ne.b32 p, %74, 0;\n"
    "wgmma.mma_async.sync.aligned.m64n144k16.f32.bf16.bf16 {%0, %1, %2, %3, %4, %5, %6, %7, %8, %9, %10, %11, %12, %13, %14, %15, %16, %17, %18, %19, %20, %21, %22, %23, %24, %25, %26, %27, %28, %29, %30, %31, %32, %33, %34, %35, %36, %37, %38, %39, %40, %41, %42, %43, %44, %45, %46, %47, %48, %49, %50, %51, %52, %53, %54, %55, %56, %57, %58, %59, %60, %61, %62, %63, %64, %65, %66, %67, %68, %69, %70, %71}, %72, %73, p, 1, 1, %75, %76;\n}\n"
    : "+f"(d[0]), "+f"(d[1]), "+f"(d[2]), "+f"(d[3]), "+f"(d[4]), "+f"(d[5]), "+f"(d[6]), "+f"(d[7]), "+f"(d[8]), "+f"(d[9]), "+f"(d[10]), "+f"(d[11]), "+f"(d[12]), "+f"(d[13]), "+f"(d[14]), "+f"(d[15]), "+f"(d[16]), "+f"(d[17]), "+f"(d[18]), "+f"(d[19]), "+f"(d[20]), "+f"(d[21]), "+f"(d[22]), "+f"(d[23]), "+f"(d[24]), "+f"(d[25]), "+f"(d[26]), "+f"(d[27]), "+f"(d[28]), "+f"(d[29]), "+f"(d[30]), "+f"(d[31]), "+f"(d[32]), "+f"(d[33]), "+f"(d[34]), "+f"(d[35]), "+f"(d[36]), "+f"(d[37]), "+f"(d[38]), "+f"(d[39]), "+f"(d[40]), "+f"(d[41]), "+f"(d[42]), "+f"(d[43]), "+f"(d[44]), "+f"(d[45]), "+f"(d[46]), "+f"(d[47]), "+f"(d[48]), "+f"(d[49]), "+f"(d[50]), "+f"(d[51]), "+f"(d[52]), "+f"(d[53]), "+f"(d[54]), "+f"(d[55]), "+f"(d[56]), "+f"(d[57]), "+f"(d[58]), "+f"(d[59]), "+f"(d[60]), "+f"(d[61]), "+f"(d[62]), "+f"(d[63]), "+f"(d[64]), "+f"(d[65]), "+f"(d[66]), "+f"(d[67]), "+f"(d[68]), "+f"(d[69]), "+f"(d[70]), "+f"(d[71]) : "l"(da), "l"(db), "r"(sd), "n"(TA), "n"(TB));
}
template<int TA, int TB> DEVI void wgmma_n160(float* d, uint64_t da, uint64_t db, int sd) {
  asm volatile("{\n.reg .pred p;\nsetp.ne.b32 p, %82, 0;\n"
    "wgmma.mma_async.sync.aligned.m64n160k16.f32.bf16.bf16 {%0, %1, %2, %3, %4, %5, %6, %7, %8, %9, %10, %11, %12, %13, %14, %15, %16, %17, %18, %19, %20, %21, %22, %23, %24, %25, %26, %27, %28, %29, %30, %31, %32, %33, %34, %35, %36, %37, %38, %39, %40, %41, %42, %43, %44, %45, %46, %47, %48, %49, %50, %51, %52, %53, %54, %55, %56, %57, %58, %59, %60, %61, %62, %63, %64, %65, %66, %67, %68, %69, %70, %71, %72, %73, %74, %75, %76, %77, %78, %79}, %80, %81, p, 1, 1, %83, %84;\n}\n"
    : "+f"(d[0]), "+f"(d[1]), "+f"(d[2]), "+f"(d[3]), "+f"(d[4]), "+f"(d[5]), "+f"(d[6]), "+f"(d[7]), "+f"(d[8]), "+f"(d[9]), "+f"(d[10]), "+f"(d[11]), "+f"(d[12]), "+f"(d[13]), "+f"(d[14]), "+f"(d[15]), "+f"(d[16]), "+f"(d[17]), "+f"(d[18]), "+f"(d[19]), "+f"(d[20]), "+f"(d[21]), "+f"(d[22]), "+f"(d[23]), "+f"(d[24]), "+f"(d[25]), "+f"(d[26]), "+f"(d[27]), "+f"(d[28]), "+f"(d[29]), "+f"(d[30]), "+f"(d[31]), "+f"(d[32]), "+f"(d[33]), "+f"(d[34]), "+f"(d[35]), "+f"(d[36]), "+f"(d[37]), "+f"(d[38]), "+f"(d[39]), "+f"(d[40]), "+f"(d[41]), "+f"(d[42]), "+f"(d[43]), "+f"(d[44]), "+f"(d[45]), "+f"(d[46]), "+f"(d[47]), "+f"(d[48]), "+f"(d[49]), "+f"(d[50]), "+f"(d[51]), "+f"(d[52]), "+f"(d[53]), "+f"(d[54]), "+f"(d[55]), "+f"(d[56]), "+f"(d[57]), "+f"(d[58]), "+f"(d[59]), "+f"(d[60]), "+f"(d[61]), "+f"(d[62]), "+f"(d[63]), "+f"(d[64]), "+f"(d[65]), "+f"(d[66]), "+f"(d[67]), "+f"(d[68]), "+f"(d[69]), "+f"(d[70]), "+f"(d[71]), "+f"(d[72]), "+f"(d[73]), "+f"(d[74]), "+f"(d[75]), "+f"(d[76]), "+f"(d[77]), "+f"(d[78]), "+f"(d[79]) : "l"(da), "l"(db), "r"(sd), "n"(TA), "n"(TB));
}

__global__ void __launch_bounds__(256, 3) k0_prep(const bf16* __restrict__ x, const bf16* __restrict__ wqkv,
                                                  const bf16* __restrict__ wphi, const bf16* __restrict__ wo) {
    __shared__ __align__(16) uint32_t s_in[64 * 36];
    __shared__ __align__(16) unsigned short s_phi[4 * 324 + 160];
    __shared__ __align__(128) bf16 s_out[72 * 64 + 64];
    if (threadIdx.x == 0) TL(0, 0);
    const int tid = threadIdx.x, lane = tid & 31, warp = __shfl_sync(~0u, tid >> 5, 0);
    const int c = blockIdx.x, g = blockIdx.y, p = blockIdx.z;
    const int b = (p * 8 + g) * 9 + c;
    uint4 xv[3];
    {
        const int ld = (p < 3) ? 1728 : 576;
        const bf16* src = ((p < 3) ? wqkv + p * 576 : wo) + (c * 64 * ld + g * 72);
        const uint32_t si = smem_u32(s_in);
        #pragma unroll
        for (int j = 0; j < 3; j++) {
            const int i = tid + j * 256, r = (i * 7282) >> 16;
            if (j < 2 || tid < 64) asm volatile("cp.async.cg.shared.global [%0], [%1], 16;" :: "r"(si + i * 16), "l"(src + (r * (ld - 72) + i * 8)) : "memory");
        }
        if (p < 2 && tid < 162) asm volatile("cp.async.cg.shared.global [%0], [%1], 16;" :: "r"(smem_u32(s_phi) + tid * 16), "l"(wphi + g * 1296 + tid * 8) : "memory");
        pdl_trigger();
        if (threadIdx.x == 0) TL(0, 4);
        const int t = warp & 3, half = warp >> 2, g8 = lane >> 2, c4 = lane & 3;
        uint32_t sa[3];
        {
            const int kc = half * 4 + (lane >> 3);
            #pragma unroll
            for (int fb = 0; fb < 3; fb++) {
                const int f = 8 * fb + (lane & 7), n = 8 * (f >> 1) + 2 * t + (f & 1);
                const uint32_t o = (p < 3) ? n * 128 + ((kc ^ (n & 7)) << 4) : (kc * 72 + 18 * t + f) * 16;
                sa[fb] = smem_u32(s_out) + (f < 18 ? o : 9216);
            }
        }
        asm volatile("cp.async.wait_all;" ::: "memory");
        if (threadIdx.x == 0) TL(0, 1);
        __syncthreads();
        {
            const uint4* xr = reinterpret_cast<const uint4*>(x + min(b * 8 + warp, S_ - 1) * D_);
            xv[0] = xr[lane]; xv[1] = xr[lane + 32]; xv[2] = xr[64 + (lane & 7)];
        }
        if (threadIdx.x == 0) TL(0, 5);
        uint32_t af[3][3];
        if (p < 2) {
            const unsigned short* ph = s_phi + t * 324 + c4 * 36 + g8;
            #pragma unroll
            for (int fb = 0; fb < 3; fb++)
                #pragma unroll
                for (int db = 0; db < 3; db++) {
                    uint32_t v = (uint32_t)ph[db * 144 + fb * 8] | ((uint32_t)ph[db * 144 + 18 + fb * 8] << 16);
                    if (db == 2 && c4 != 0) v = 0;
                    af[fb][db] = v;
                }
        } else {
            const uint32_t v = (g8 == 2 * c4 ? 0x3f80u : 0u) | (g8 == 2 * c4 + 1 ? 0x3f800000u : 0u);
            #pragma unroll
            for (int fb = 0; fb < 3; fb++)
                #pragma unroll
                for (int db = 0; db < 3; db++) af[fb][db] = fb == db ? v : 0u;
        }
        uint32_t ov[3][4];
        const uint32_t* wr = &s_in[(half * 32 + g8) * 36 + t * 9 + c4];
        #pragma unroll
        for (int j = 0; j < 4; j++) {
            const uint32_t b0 = wr[j * 288], b1 = wr[j * 288 + 4], b2 = c4 == 0 ? wr[j * 288 + 8] : 0u;
            float c0[4] = {0.f, 0.f, 0.f, 0.f}, c1[4] = {0.f, 0.f, 0.f, 0.f};
            mma16816(c0, af[0][0], af[1][0], af[0][1], af[1][1], b0, b1);
            mma1688(c0, af[0][2], af[1][2], b2);
            mma16816(c1, af[2][0], 0u, af[2][1], 0u, b0, b1);
            mma1688(c1, af[2][2], 0u, b2);
            ov[0][j] = pack2(c0[0], c0[1]); ov[1][j] = pack2(c0[2], c0[3]); ov[2][j] = pack2(c1[0], c1[1]);
        }
        #pragma unroll
        for (int fb = 0; fb < 3; fb++) stsm4(sa[fb], ov[fb][0], ov[fb][1], ov[fb][2], ov[fb][3]);
        fence_async_smem();
        if (threadIdx.x == 0) TL(0, 2);
        __syncthreads();
        if (tid == 0) {
            bulk_s2g((p < 3 ? g_wqkv + (g * 3 + p) * (9 * 4608) : g_wo + g * (9 * 4608)) + c * 4608, smem_u32(s_out), 9216);
            bulk_commit();
        }
        if (p < 3) {
            float cs0[4] = {0.f, 0.f, 0.f, 0.f}, cs1[4] = {0.f, 0.f, 0.f, 0.f};
            mma16816(cs0, ov[0][0], ov[1][0], ov[0][1], ov[1][1], 0x3f803f80u, 0x3f803f80u);
            mma16816(cs0, ov[0][2], ov[1][2], ov[0][3], ov[1][3], 0x3f803f80u, 0x3f803f80u);
            mma16816(cs1, ov[2][0], 0u, ov[2][1], 0u, 0x3f803f80u, 0x3f803f80u);
            mma16816(cs1, ov[2][2], 0u, ov[2][3], 0u, 0x3f803f80u, 0x3f803f80u);
            const int f = g8 + 8 * c4;
            if (f < 18) g_cs[(g * 18 + c * 2 + half) * 216 + p * 72 + 8 * (f >> 1) + 2 * t + (f & 1)] = c4 == 0 ? cs0[0] : c4 == 1 ? cs0[2] : cs1[0];
        }
    }
    if (threadIdx.x == 0) TL(0, 6);
    if (b < 256) {
        const int row = b * 8 + warp;
        if (lane < 8) g_stats[row * 8 + lane] = ~0ull;
        if (b < 30) reinterpret_cast<float4*>(g_kv)[b * 256 + tid] = make_float4(0.f, 0.f, 0.f, 0.f);
        if (b == 32) g_flag[tid] = 0u;
        const uint32_t w[12] = {xv[0].x, xv[0].y, xv[0].z, xv[0].w, xv[1].x, xv[1].y, xv[1].z, xv[1].w, xv[2].x, xv[2].y, xv[2].z, xv[2].w};
        float s = 0.f, s2 = 0.f;
        #pragma unroll
        for (int i = 0; i < 12; i++) { if (i < 8) s += bf_lo(w[i]) + bf_hi(w[i]); else s2 += bf_lo(w[i]) + bf_hi(w[i]); }
        if (lane < 8) s += s2;
        #pragma unroll
        for (int o = 16; o; o >>= 1) s += __shfl_xor_sync(~0u, s, o);
        const float mean = s * (1.f / D_);
        float q = 0.f, q2 = 0.f;
        #pragma unroll
        for (int i = 0; i < 12; i++) {
            const float e0 = bf_lo(w[i]) - mean, e1 = bf_hi(w[i]) - mean;
            if (i < 8) q += e0 * e0 + e1 * e1; else q2 += e0 * e0 + e1 * e1;
        }
        if (lane < 8) q += q2;
        #pragma unroll
        for (int o = 16; o; o >>= 1) q += __shfl_xor_sync(~0u, q, o);
        if (lane == 0) g_ln[row] = make_float2(mean, rsqrtf(q * (1.f / D_) + LN_EPS));
    }
    if (tid == 0) bulk_wait_read();
    if (threadIdx.x == 0) TL(0, 3);
}

DEVI void dual_softmax(const float* a, float scale, uint32_t* o) {
    float mx = a[0], mn = a[0];
    #pragma unroll
    for (int j = 1; j < 18; j++) { mx = fmaxf(mx, a[j]); mn = fminf(mn, a[j]); }
    const float mxs = -mx * scale, mns = mn * scale;
    float ep[18], en[18], sp = 0.f, sn = 0.f;
    #pragma unroll
    for (int j = 0; j < 18; j++) {
        ep[j] = ex2(fmaf(a[j], scale, mxs)); sp += ep[j];
        en[j] = ex2(fmaf(a[j], -scale, mns)); sn += en[j];
    }
    const float rp = rcp(sp), rn = rcp(sn);
    #pragma unroll
    for (int j = 0; j < 9; j++) {
        o[j] = pack2(ep[2 * j] * rp, ep[2 * j + 1] * rp);
        o[9 + j] = pack2(en[2 * j] * rn, en[2 * j + 1] * rn);
    }
}

constexpr int K1_A = 0, K1_B = 147456, K1_BAR = K1_B + 9 * 9216, K1_CS = K1_BAR + 256, K1_SMEM = K1_CS + 864;
static_assert(K1_SMEM <= 232448, "smem");
__global__ void __cluster_dims__(2, 1, 1) __launch_bounds__(512, 1) k1_qkv(const __grid_constant__ CUtensorMap tmXA) {
    extern __shared__ __align__(1024) char smem[];
    const uint32_t sm = smem_u32(smem);
    const uint32_t bFull = sm + K1_BAR, bEmpty = bFull + 9 * 8, bCs = bEmpty + 9 * 8;
    const int tid = threadIdx.x, lane = tid & 31, warp = __shfl_sync(~0u, tid >> 5, 0);
    const int rank = blockIdx.x & 1, g = (blockIdx.x >> 1) & 7, mt = (blockIdx.x >> 4) * 2 + rank;
    if (tid == 384) {
        TL(1, 0);
        #pragma unroll
        for (int c = 0; c < 9; c++) { mbar_init(bFull + c * 8, 1); mbar_init(bEmpty + c * 8, 8); }
        mbar_init(bCs, 96);
        fence_mbar_init();
        #pragma unroll
        for (int c = 0; c < 9; c++) {
            mbar_expect(bFull + c * 8, 16384 + 9216);
            tma3d(sm + K1_A + c * 16384, &tmXA, bFull + c * 8, 0, mt * 128, c);
        }
    }
    __syncthreads();
    cluster_arrive_relaxed();
    if (warp >= 12) {
        asm volatile("setmaxnreg.dec.sync.aligned.u32 32;");
        cluster_wait();
        pdl_wait();
        pdl_trigger();
        if (warp == 12) {
            if (lane == 0) {
                TL(1, 1);
                const bf16* wsrc = g_wqkv + (size_t)g * 27 * 4608 + rank * 2304;
                const uint32_t sb = sm + K1_B + rank * 4608;
                #pragma unroll
                for (int c = 0; c < 9; c++) bulk_g2s_mc(sb + c * 9216, wsrc + c * 4608, 4608, bFull + c * 8, 3);
                #pragma unroll 1
                for (int p = 1; p < 3; p++) {
                    #pragma unroll
                    for (int c = 0; c < 9; c++) {
                        mbar_wait(bEmpty + c * 8, p - 1);
                        mbar_expect(bFull + c * 8, 9216);
                        bulk_g2s_mc(sb + c * 9216, wsrc + (p * 9 + c) * 4608, 4608, bFull + c * 8, 3);
                    }
                }
            }
        } else {
            for (int n = tid - 416; n < 216; n += 96) {
                float cs = 0.f;
                #pragma unroll
                for (int c = 0; c < 18; c++) cs += __ldcg(g_cs + (g * 18 + c) * 216 + n);
                reinterpret_cast<float*>(smem + K1_CS)[n] = cs;
            }
            mbar_arrive(bCs);
        }
    } else {
        asm volatile("setmaxnreg.inc.sync.aligned.u32 160;");
        const int wg = warp >> 2, w4 = warp & 3, gq = lane >> 2, t = lane & 3;
        const uint32_t eaddr = mapa(bEmpty, lane & 1);
        const bool rel = wg < 2 && lane < 2;
        cluster_wait();
        pdl_wait();
        float2 ln[4];
        #pragma unroll
        for (int r = 0; r < 4; r++) ln[r] = __ldcg(g_ln + mt * 128 + (r >> 1) * 64 + w4 * 16 + gq + (r & 1) * 8);
        float acc[2][36];
        const uint64_t d0 = mkdesc(sm, 16, 1024, 1);
        if (wg > 0) bar_sync(wg, 256);
        #pragma unroll
        for (int c = 0; c < 9; c++) {
            mbar_wait(bFull + c * 8, wg & 1);
            wg_fence();
            #pragma unroll
            for (int kk = 0; kk < 4; kk++) {
                wgmma_n72<0, 0>(acc[0], dadv(d0, K1_A + c * 16384 + kk * 32), dadv(d0, K1_B + c * 9216 + kk * 32), (c | kk) != 0);
                wgmma_n72<0, 0>(acc[1], dadv(d0, K1_A + c * 16384 + 8192 + kk * 32), dadv(d0, K1_B + c * 9216 + kk * 32), (c | kk) != 0);
            }
            wg_commit();
            if (c == 8 && wg < 2) bar_arrive(wg + 1, 256);
            if (c > 0) {
                wg_wait<1>();
                if (rel) mbar_arrive_remote(eaddr + (c - 1) * 8);
            }
            if (wg == 2) {
                if (c == 2) bar_arrive(3, 256);
                if (c == 3) bar_arrive(7, 256);
                if (c == 4) bar_arrive(9, 256);
                if (c == 5) bar_arrive(8, 256);
            }
        }
        wg_wait<0>();
        reg_fence<36>(acc[0]); reg_fence<36>(acc[1]);
        if (rel) mbar_arrive_remote(eaddr + 8 * 8);
        if ((tid & 127) == 0) TL(1, 2 + wg);
        mbar_wait(bCs, 0);
        {
            const float2* cs = reinterpret_cast<const float2*>(smem + K1_CS) + wg * 36 + t;
            #pragma unroll
            for (int j = 0; j < 9; j++) {
                const float2 c2 = cs[4 * j];
                #pragma unroll
                for (int r = 0; r < 4; r++) {
                    float* q = &acc[r >> 1][4 * j + 2 * (r & 1)];
                    q[0] = fmaf(-ln[r].x, c2.x, q[0]); q[1] = fmaf(-ln[r].x, c2.y, q[1]);
                }
            }
        }
        if (wg < 2) {
            uint32_t ph[2][2][18];
            #pragma unroll
            for (int m = 0; m < 2; m++) {
                #pragma unroll
                for (int r = 0; r < 2; r++) {
                    float a[18];
                    #pragma unroll
                    for (int j = 0; j < 9; j++) { a[2 * j] = acc[m][4 * j + 2 * r]; a[2 * j + 1] = acc[m][4 * j + 2 * r + 1]; }
                    dual_softmax(a, ln[2 * m + r].y * LOG2E, ph[m][r]);
                }
                #pragma unroll
                for (int j = 0; j < 18; j++) asm volatile("" : "+r"(ph[m][0][j]), "+r"(ph[m][1][j]));
                if (wg == 1) {
                    bar_sync(m ? 9 : 3, 256);
                    #pragma unroll
                    for (int r = 0; r < 2; r++) {
                        const int tok = w4 * 16 + gq + 8 * r;
                        const uint32_t base = sm + K1_A + m * 32768 + t * 8192 + tok * 128;
                        const int sw = (tok + 2 * t) & 7;
                        #pragma unroll
                        for (int j = 0; j < 4; j++) sts128(base + ((j ^ sw) << 4), ph[m][r][4 * j], ph[m][r][4 * j + 1], ph[m][r][4 * j + 2], ph[m][r][4 * j + 3]);
                        sts128(base + ((4 ^ sw) << 4), ph[m][r][16], ph[m][r][17], 0u, 0u);
                    }
                }
            }
            if (wg == 0) {
                #pragma unroll
                for (int m = 0; m < 2; m++) {
                    bar_sync(7 + m, 256);
                    const uint32_t st = sm + K1_B + m * (16 * PQ_UNIT);
                    const uint32_t ub = st + (w4 * 4 + t) * PQ_UNIT;
                    #pragma unroll
                    for (int r = 0; r < 2; r++)
                        #pragma unroll
                        for (int j = 0; j < 4; j++) sts128(ub + r * 512 + (gq * 4 + j) * 16, ph[m][r][j], ph[m][r][4 + j], ph[m][r][8 + j], ph[m][r][12 + j]);
                    sts128(ub + 1024 + gq * 16, ph[m][0][16], ph[m][1][16], ph[m][0][17], ph[m][1][17]);
                    fence_async_smem();
                    bar_sync(4, 128);
                    if (tid == 0) { bulk_s2g(g_phiq + (size_t)((mt * 2 + m) * 8 + g) * (16 * PQ_UNIT), st, 16 * PQ_UNIT); bulk_commit(); }
                }
            }
        } else {
            bar_sync(6, 128);
            #pragma unroll
            for (int r = 0; r < 4; r++) {
                const int tok = w4 * 16 + gq + 8 * (r & 1);
                const uint32_t base = sm + K1_A + (r >> 1) * 32768 + t * 8192 + tok * 128;
                const int sw = (tok + 2 * t) & 7;
                uint32_t pv[9];
                #pragma unroll
                for (int j = 0; j < 9; j++) pv[j] = pack2(acc[r >> 1][4 * j + 2 * (r & 1)] * ln[r].y, acc[r >> 1][4 * j + 2 * (r & 1) + 1] * ln[r].y);
                sts128(base + ((5 ^ sw) << 4), pv[0], pv[1], pv[2], pv[3]);
                sts128(base + ((6 ^ sw) << 4), pv[4], pv[5], pv[6], pv[7]);
                sts128(base + ((7 ^ sw) << 4), pv[8], 0x00003f80u, 0u, 0u);
            }
        }
        if (tid == 128) TL(1, 5);
        bar_sync(5, 384);
        float ck[2][2][4];
        #pragma unroll
        for (int m = 0; m < 2; m++)
            #pragma unroll
            for (int n = 0; n < 2; n++)
                #pragma unroll
                for (int i = 0; i < 4; i++) ck[m][n][i] = 0.f;
        {
            const int tok0 = (lane & 7) + ((lane >> 3) & 1) * 8;
            const int sw = (tok0 + 2 * w4) & 7, hi = lane >> 4;
            const uint32_t hb = sm + K1_A + w4 * 8192 + tok0 * 128;
            const uint32_t o0 = ((2 * wg + hi) ^ sw) << 4, o1 = ((4 + hi) ^ sw) << 4, o2 = ((6 + hi) ^ sw) << 4;
            #pragma unroll
            for (int ks = 0; ks < 8; ks++) {
                const uint32_t rb = hb + (ks >> 2) * 32768 + (ks & 3) * 2048;
                uint32_t f[6][2];
                ldsm4t(rb + o0, f[0][0], f[0][1], f[1][0], f[1][1]);
                ldsm4t(rb + o1, f[2][0], f[2][1], f[3][0], f[3][1]);
                ldsm4t(rb + o2, f[4][0], f[4][1], f[5][0], f[5][1]);
                #pragma unroll
                for (int n = 0; n < 2; n++) {
                    mma16816(ck[0][n], f[3][0], f[4][0], f[3][1], f[4][1], f[n][0], f[n][1]);
                    mma16816(ck[1][n], f[5][0], 0u, f[5][1], 0u, f[n][0], f[n][1]);
                }
            }
        }
        if (tid == 0) TL(1, 6);
        float* kvh = g_kv + (size_t)(g * 4 + w4) * KV_H + wg * 128;
        #pragma unroll
        for (int nt = 0; nt < 3; nt++) {
            const int m = nt >> 1, e = (nt & 1) * 2;
            if (nt < 2 || gq < 3) {
                float* p = kvh + nt * 320;
                if (wg < 2) asm volatile("red.global.add.v4.f32 [%0], {%1, %2, %3, %4};" :: "l"(p + lane * 4), "f"(ck[m][0][e]), "f"(ck[m][0][e + 1]), "f"(ck[m][1][e]), "f"(ck[m][1][e + 1]) : "memory");
                else if (t < 2) asm volatile("red.global.add.v2.f32 [%0], {%1, %2};" :: "l"(p + lane * 2), "f"(ck[m][0][e]), "f"(ck[m][0][e + 1]) : "memory");
            }
        }
        if (tid == 0) bulk_wait_read();
        if (tid == 0) TL(1, 7);
    }
}

DEVI uint4 ldg128(const void* p) { uint4 v; asm volatile("ld.global.cg.v4.u32 {%0,%1,%2,%3}, [%4];" : "=r"(v.x), "=r"(v.y), "=r"(v.z), "=r"(v.w) : "l"(p)); return v; }
DEVI uint2 ldg64(const void* p) { uint2 v; asm volatile("ld.global.cg.v2.u32 {%0,%1}, [%2];" : "=r"(v.x), "=r"(v.y) : "l"(p)); return v; }
DEVI uint32_t packu(uint32_t lo, uint32_t hi) { return pack2(__uint_as_float(lo), __uint_as_float(hi)); }
__global__ void __maxnreg__(72) k1b_o() {
    __shared__ __align__(128) unsigned char s_o[18432];
    const uint32_t sm = smem_u32(s_o);
    const int tid = threadIdx.x, lane = tid & 31, warp = __shfl_sync(~0u, tid >> 5, 0), gq = lane >> 2, t = lane & 3;
    const int oct = blockIdx.x & 3, mt = blockIdx.x >> 2;
    const int hl = warp & 7, mh = warp >> 3, h = oct * 8 + hl;
    const float* kp = g_kv + (size_t)h * KV_H;
    const unsigned char* pp = g_phiq + (size_t)(((mt * 8 + (h >> 2)) * 4 + mh * 2) * 4 + (h & 3)) * PQ_UNIT;
    if (tid == 0) TL(5, 0);
    pdl_trigger();
    pdl_wait();
    if (tid == 0) TL(5, 1);
    uint4 u0[3], u1[3]; uint2 u2[3];
    uint4 a0[2], a1[2]; uint2 at[2];
    #pragma unroll
    for (int n = 0; n < 3; n++) {
        u0[n] = ldg128(kp + n * 320 + lane * 4); u1[n] = ldg128(kp + n * 320 + 128 + lane * 4); u2[n] = ldg64(kp + n * 320 + 256 + lane * 2);
    }
    #pragma unroll
    for (int m = 0; m < 2; m++) {
        a0[m] = ldg128(pp + m * 4 * PQ_UNIT + lane * 16); a1[m] = ldg128(pp + m * 4 * PQ_UNIT + 512 + lane * 16);
        at[m] = ldg64(pp + m * 4 * PQ_UNIT + 1024 + gq * 16 + (t & 1) * 8);
    }
    uint32_t bq[3][5];
    #pragma unroll
    for (int n = 0; n < 3; n++) {
        bq[n][0] = packu(u0[n].x, u0[n].y); bq[n][1] = packu(u0[n].z, u0[n].w);
        bq[n][2] = packu(u1[n].x, u1[n].y); bq[n][3] = packu(u1[n].z, u1[n].w);
        bq[n][4] = packu(u2[n].x, u2[n].y);
    }
    #pragma unroll
    for (int m = 0; m < 2; m++) {
        float c[3][4];
        #pragma unroll
        for (int n = 0; n < 3; n++) {
            c[n][0] = c[n][1] = c[n][2] = c[n][3] = 0.f;
            mma16816(c[n], a0[m].x, a1[m].x, a0[m].y, a1[m].y, bq[n][0], bq[n][1]);
            mma16816(c[n], a0[m].z, a1[m].z, a0[m].w, a1[m].w, bq[n][2], bq[n][3]);
            mma1688(c[n], at[m].x, at[m].y, bq[n][4]);
        }
        const float d0 = __shfl_sync(~0u, c[2][0], (lane & 28) | 1), d1 = __shfl_sync(~0u, c[2][2], (lane & 28) | 1);
        const float r0 = __fdividef(1.f, d0 + 1e-6f), r1 = __fdividef(1.f, d1 + 1e-6f);
        #pragma unroll
        for (int n = 0; n < 3; n++) {
            if (n < 2 || t == 0) {
                const int k = hl * 18 + n * 8 + 2 * t;
                const uint32_t ad = sm + (k >> 3) * 1024 + ((mh * 2 + m) * 16 + gq) * 16 + (k & 7) * 2;
                sts32(ad, pack2(c[n][0] * r0, c[n][1] * r0));
                sts32(ad + 128, pack2(c[n][2] * r1, c[n][3] * r1));
            }
        }
    }
    if (tid == 0) TL(5, 2);
    fence_async_smem();
    __syncthreads();
    if (tid == 0) {
        bulk_s2g(g_o + (size_t)mt * (64 * D_) + oct * 9216, sm, 18432);
        bulk_commit();
        bulk_wait_read();
        TL(5, 7);
    }
}

constexpr int K2_B = 73728, K2_PIECE = 27648, K2_BAR = K2_B + 5 * K2_PIECE, K2_SMEM = K2_BAR + 128;
__global__ void __cluster_dims__(2, 1, 1) __maxnreg__(104) k2_attn(const __grid_constant__ CUtensorMap tmX, const bf16* __restrict__ w1) {
    extern __shared__ __align__(1024) char smem[];
    const uint32_t sm = smem_u32(smem);
    const uint32_t bFull = sm + K2_BAR, bX = bFull + 6 * 8;
    const int tid = threadIdx.x, lane = tid & 31, warp = __shfl_sync(~0u, tid >> 5, 0);
    const int rank = blockIdx.x & 1, ns = (blockIdx.x >> 1) & 3, mt = (blockIdx.x >> 3) * 2 + rank;
    const int wg = warp >> 2, w4 = warp & 3, gq = lane >> 2, t = lane & 3;
    const bf16* wsrc = g_wo + (size_t)ns * (2 * 72 * 576);
    if (tid == 0) {
        TL(2, 0);
        prefetch_tm(&tmX);
        #pragma unroll
        for (int i = 0; i < 7; i++) mbar_init(bFull + i * 8, 1);
        fence_mbar_init();
        #pragma unroll
        for (int i = 0; i < 6; i++) mbar_expect(bFull + i * 8, K2_PIECE + 12288);
        mbar_expect(bX, 18432);
    }
    if (tid == 128) l2_prefetch(w1 + blockIdx.x * 13824, 27648);
    __syncthreads();
    cluster_arrive_relaxed();
    cluster_wait();
    if (tid == 0) {
        #pragma unroll
        for (int i = 0; i < 5; i++) bulk_g2s_mc(sm + K2_B + i * K2_PIECE + rank * (K2_PIECE / 2), wsrc + rank * (72 * 576) + i * (K2_PIECE / 4), K2_PIECE / 2, bFull + i * 8, 3);
        pdl_wait();
        pdl_trigger();
        TL(2, 1);
        const bf16* osrc = g_o + (size_t)mt * (64 * D_);
        #pragma unroll
        for (int i = 0; i < 6; i++) bulk_g2s(sm + i * 12288, osrc + i * 6144, 12288, bFull + i * 8);
    }
    __syncwarp();
    {
        float acc[36];
        const uint64_t da0 = mkdesc(sm, 1024, 128, 0), db0 = mkdesc(sm + K2_B + wg * (K2_PIECE / 2), 1152, 128, 0);
        #pragma unroll
        for (int i = 0; i < 6; i++) {
            mbar_wait(bFull + i * 8, 0);
            if (i == 0 && tid == 0) TL(2, 3);
            wg_fence();
            #pragma unroll
            for (int kk = 0; kk < 6; kk++)
                wgmma_n72<0, 0>(acc, dadv(da0, i * 12288 + kk * 2048), dadv(db0, (i % 5) * K2_PIECE + kk * 2304), (i | kk) != 0);
            wg_commit();
            if (i == 1) {
                wg_wait<1>();
                if (warp == 7) { bar_sync(3, 256); if (lane < 2) bulk_g2s(sm + K2_B + lane * (K2_PIECE / 2), wsrc + lane * (72 * 576) + 5 * (K2_PIECE / 4), K2_PIECE / 2, bFull + 5 * 8); __syncwarp(); }
                else bar_arrive(3, 256);
            }
            if (i == 2) {
                wg_wait<1>();
                if (warp == 3) {
                    bar_sync(4, 256);
                    if (lane == 0) { tma2d(sm + K2_B + K2_PIECE, &tmX, bX, ns * 144, mt * 64); tma2d(sm + K2_B + K2_PIECE + 9216, &tmX, bX, ns * 144 + 72, mt * 64); }
                    __syncwarp();
                } else bar_arrive(4, 256);
            }
        }
        uint32_t xr[18];
        const uint32_t xs = sm + K2_B + K2_PIECE + wg * 9216;
        mbar_wait(bX, 0);
        #pragma unroll
        for (int j = 0; j < 9; j++) {
            xr[2 * j] = lds32(xs + (w4 * 16 + gq) * 144 + j * 16 + t * 4);
            xr[2 * j + 1] = lds32(xs + (w4 * 16 + gq + 8) * 144 + j * 16 + t * 4);
        }
        wg_wait<0>();
        reg_fence<36>(acc);
        if (tid == 0) TL(2, 4);
        uint32_t hp[18];
        float s0 = 0.f, s1 = 0.f;
        #pragma unroll
        for (int j = 0; j < 9; j++) {
            hp[2 * j] = pack2(bf_lo(xr[2 * j]) + acc[4 * j], bf_hi(xr[2 * j]) + acc[4 * j + 1]);
            hp[2 * j + 1] = pack2(bf_lo(xr[2 * j + 1]) + acc[4 * j + 2], bf_hi(xr[2 * j + 1]) + acc[4 * j + 3]);
            acc[4 * j] = bf_lo(hp[2 * j]); acc[4 * j + 1] = bf_hi(hp[2 * j]);
            acc[4 * j + 2] = bf_lo(hp[2 * j + 1]); acc[4 * j + 3] = bf_hi(hp[2 * j + 1]);
            s0 += acc[4 * j] + acc[4 * j + 1]; s1 += acc[4 * j + 2] + acc[4 * j + 3];
        }
        s0 += __shfl_xor_sync(~0u, s0, 1); s1 += __shfl_xor_sync(~0u, s1, 1);
        s0 += __shfl_xor_sync(~0u, s0, 2); s1 += __shfl_xor_sync(~0u, s1, 2);
        const float m0 = s0 * (1.f / 72), m1 = s1 * (1.f / 72);
        float q0 = 0.f, q1 = 0.f;
        #pragma unroll
        for (int j = 0; j < 9; j++) {
            float e;
            e = acc[4 * j] - m0; q0 += e * e; e = acc[4 * j + 1] - m0; q0 += e * e;
            e = acc[4 * j + 2] - m1; q1 += e * e; e = acc[4 * j + 3] - m1; q1 += e * e;
        }
        q0 += __shfl_xor_sync(~0u, q0, 1); q1 += __shfl_xor_sync(~0u, q1, 1);
        q0 += __shfl_xor_sync(~0u, q0, 2); q1 += __shfl_xor_sync(~0u, q1, 2);
        const int row0 = mt * 64 + w4 * 16 + gq, p = ns * 2 + wg;
        if (t < 2) {
            uint32_t mb = __float_as_uint(t ? m1 : m0), qb = __float_as_uint(t ? q1 : q0);
            if (qb == 0xffffffffu) qb = 0x7fffffffu;
            unsigned long long rec = ((unsigned long long)qb << 32) | mb;
            asm volatile("st.relaxed.gpu.global.u64 [%0], %1;" :: "l"(g_stats + (row0 + 8 * t) * 8 + p), "l"(rec) : "memory");
        }
        {
            uint32_t* hd = g_h + (size_t)(mt * 8 + p) * (18 * 128);
            const int tw = tid & 127;
            #pragma unroll
            for (int j = 0; j < 4; j++) reinterpret_cast<uint4*>(hd)[j * 128 + tw] = make_uint4(hp[4 * j], hp[4 * j + 1], hp[4 * j + 2], hp[4 * j + 3]);
            reinterpret_cast<uint2*>(hd + 16 * 128)[tw] = make_uint2(hp[16], hp[17]);
        }
        bar_sync(1 + wg, 128);
        if (tid == 0) TL(2, 5);
        unsigned long long ra, rb, rc, rd;
        {
            const unsigned long long* sp = g_stats + row0 * 8 + 2 * t;
            int it = 0;
            while (true) {
                asm volatile("ld.relaxed.gpu.global.v2.u64 {%0, %1}, [%2];" : "=l"(ra), "=l"(rb) : "l"(sp) : "memory");
                asm volatile("ld.relaxed.gpu.global.v2.u64 {%0, %1}, [%2];" : "=l"(rc), "=l"(rd) : "l"(sp + 64) : "memory");
                bool ok = (uint32_t)(ra >> 32) != 0xffffffffu && (uint32_t)(rb >> 32) != 0xffffffffu &&
                          (uint32_t)(rc >> 32) != 0xffffffffu && (uint32_t)(rd >> 32) != 0xffffffffu;
                if (__all_sync(~0u, ok)) break;
                if (++it > (1 << 22)) __trap();
            }
        }
        if (tid == 0) TL(2, 6);
        float sc[2], mu[2];
        #pragma unroll
        for (int r = 0; r < 2; r++) {
            const unsigned long long u = r ? rc : ra, v = r ? rd : rb;
            const float ma = __uint_as_float((uint32_t)u), mb = __uint_as_float((uint32_t)v);
            float ms = ma + mb;
            ms += __shfl_xor_sync(~0u, ms, 1); ms += __shfl_xor_sync(~0u, ms, 2);
            const float mean = ms * 0.125f;
            float M2 = __uint_as_float((uint32_t)(u >> 32)) + __uint_as_float((uint32_t)(v >> 32)) + 72.f * ((ma - mean) * (ma - mean) + (mb - mean) * (mb - mean));
            M2 += __shfl_xor_sync(~0u, M2, 1); M2 += __shfl_xor_sync(~0u, M2, 2);
            const float var = M2 * (1.f / D_);
            const float r1 = rsqrtf(var + LN_EPS);
            const float var2 = var * r1 * r1;
            const float r2 = rsqrtf(var2 + LN_EPS);
            sc[r] = 0.5f * (r1 * r2); mu[r] = mean;
        }
        {
            uint32_t o[18];
            #pragma unroll
            for (int j = 0; j < 9; j++) {
                o[2 * j] = pack2((acc[4 * j] - mu[0]) * sc[0], (acc[4 * j + 1] - mu[0]) * sc[0]);
                o[2 * j + 1] = pack2((acc[4 * j + 2] - mu[1]) * sc[1], (acc[4 * j + 3] - mu[1]) * sc[1]);
            }
            const int ch = 2 * w4 + ((lane >> 3) & 1);
            const uint32_t ad = xs + ((lane >> 4) * 8 + (lane & 7)) * 128 + ((ch ^ (lane & 7)) << 4);
            #pragma unroll
            for (int j = 0; j < 4; j++) stsm4t(ad + j * 2048, o[4 * j], o[4 * j + 1], o[4 * j + 2], o[4 * j + 3]);
            stsm2t(xs + (64 + (lane & 7)) * 128 + ((ch ^ (lane & 7)) << 4), o[16], o[17]);
        }
        fence_async_smem();
        bar_sync(1 + wg, 128);
        if ((tid & 127) == 0) {
            bulk_s2g(g_hnT + ((size_t)mt * D_ + ns * 144 + wg * 72) * 64, xs, 9216);
            bulk_commit();
            bulk_wait_read();
        }
        if (tid == 0) TL(2, 7);
    }
}

constexpr int K3_STAGES = 6, K3_STAGE = 36864, K3_STAG = 4, K3_PRE = 2, K3_BAR = K3_STAGES * K3_STAGE, K3_SMEM = K3_BAR + 256;
DEVI uint32_t gelu2(float a0, float a1) {
    const float z0 = a0 * fmaf(a0 * a0, 0.2854192650904f, 1.5957691216057f), z1 = a1 * fmaf(a1 * a1, 0.2854192650904f, 1.5957691216057f);
    return pack2(fmaf(a0, tanh_fast(z0), a0), fmaf(a1, tanh_fast(z1), a1));
}
template<int ROWS, int OFF> DEVI void k3_store(const float* q, uint32_t st, uint32_t lo, bf16* dst, int wg, int tw) {
    #pragma unroll
    for (int jj = 0; jj < ROWS / 16; jj++)
        stsm4t(st + lo + jj * 2048, gelu2(q[OFF + jj * 8], q[OFF + jj * 8 + 1]), gelu2(q[OFF + jj * 8 + 2], q[OFF + jj * 8 + 3]),
               gelu2(q[OFF + jj * 8 + 4], q[OFF + jj * 8 + 5]), gelu2(q[OFF + jj * 8 + 6], q[OFF + jj * 8 + 7]));
    fence_async_smem();
    bar_sync(1 + wg, 128);
    if (tw == 0) { bulk_s2g(dst, st, ROWS * 128); bulk_commit(); }
}
DEVI void k3_typeb(uint32_t sm_, int fc_, uint32_t lo, float bias0, float bias1, const bf16* __restrict__ b1) {
    const uint32_t sm = __shfl_sync(~0u, sm_, 0);
    const int fc = __shfl_sync(~0u, fc_, 0);
    const uint32_t bFull = sm + K3_BAR, bEmpty = bFull + K3_STAGES * 8;
    const int tid = threadIdx.x, lane = tid & 31, warp = __shfl_sync(~0u, tid >> 5, 0);
    const int wg = warp >> 2, w4 = warp & 3, gq = lane >> 2, tw = tid & 127;
    bf16* dst = g_u + ((size_t)(fc + wg) * D_ + 480) * 64;
    const uint32_t st = sm + wg * 8192;
    const uint64_t da0 = mkdesc(st, 8192, 1024, 1);
    int s = 0, ps = 0; uint32_t ph = 0;
    {
            const int f2 = (fc + 2) * 64 + w4 * 16 + gq;
            const float bias2 = 0.5f * __bfloat162float(b1[f2]), bias3 = 0.5f * __bfloat162float(b1[f2 + 8]);
            float acc[48], acc2[24];
            const uint64_t da2 = mkdesc(sm + 16384, 8192, 1024, 1), db0 = mkdesc(sm + 24576, 16, 1024, 1), db2 = mkdesc(sm + 24576 + wg * 6144, 16, 1024, 1);
            #pragma unroll 1
            for (int i = 0; i < 32; i++) {
                mbar_wait(bFull + s * 8, ph);
                const uint32_t so = s * K3_STAGE;
                wg_fence();
                #pragma unroll
                for (int kk = 0; kk < 4; kk++) {
                    wgmma_n96<1, 0>(acc, dadv(da0, so + kk * 2048), dadv(db0, so + kk * 32), (i | kk) != 0);
                    wgmma_n48<1, 0>(acc2, dadv(da2, so + kk * 2048), dadv(db2, so + kk * 32), (i | kk) != 0);
                }
                wg_commit();
                wg_wait<1>();
                if (i > 0 && lane == 0) mbar_arrive(bEmpty + ps * 8);
                ps = s;
                if (++s == K3_STAGES) { s = 0; ph ^= 1; }
            }
            wg_wait<0>();
            reg_fence<48>(acc); reg_fence<24>(acc2);
            #pragma unroll
            for (int j = 0; j < 48; j++) acc[j] += (j & 2) ? bias1 : bias0;
            #pragma unroll
            for (int j = 0; j < 24; j++) acc2[j] += (j & 2) ? bias3 : bias2;
            if (tw == 0) TL(7, 4 + wg);
            bar_sync(1 + wg, 128);
            k3_store<64, 0>(acc, st, lo, dst, wg, tw);
            k3_store<32, 32>(acc, st + K3_STAGE, lo, dst + 4096, wg, tw);
            k3_store<48, 0>(acc2, st + 2 * K3_STAGE, lo, g_u + ((size_t)(fc + 2) * D_ + 480 + wg * 48) * 64, wg, tw);
    }
}
__global__ void __cluster_dims__(2, 1, 1) __launch_bounds__(288, 1) k3_mix1(const __grid_constant__ CUtensorMap tmW1a, const __grid_constant__ CUtensorMap tmW1b,
                                                                             const bf16* __restrict__ b1, const bf16* __restrict__ w2) {
    extern __shared__ __align__(1024) char smem[];
    const uint32_t sm = smem_u32(smem);
    const uint32_t bFull = sm + K3_BAR, bEmpty = bFull + K3_STAGES * 8;
    const int tid = threadIdx.x, lane = tid & 31, warp = __shfl_sync(~0u, tid >> 5, 0);
    const int cl = blockIdx.x >> 1, rank = blockIdx.x & 1;
    bool tb = false; int fc, d0;
    if (cl < 36) { fc = 2 * cl; d0 = 160 * rank; }
    else if (cl < 60) { const int q = (cl - 36) >> 1, e = (cl - 36) & 1; tb = rank; fc = rank ? 6 * q + 3 * e : 6 * q + 4 * e; d0 = rank ? 480 : 320; }
    else { fc = 6 * (2 * (cl - 60) + rank) + 2; d0 = 320; }
    const CUtensorMap* tm = tb ? &tmW1b : &tmW1a;
    const uint32_t abytes = tb ? 24576 : 16384;
    if (tid == 256) {
        TL(3, 0);
        #pragma unroll
        for (int i = 0; i < K3_STAGES; i++) { mbar_init(bFull + i * 8, 1); mbar_init(bEmpty + i * 8, 8); }
        fence_mbar_init();
        #pragma unroll
        for (int i = 0; i < K3_STAGES; i++) mbar_expect(bFull + i * 8, K3_STAGE);
        #pragma unroll
        for (int i = 0; i < K3_PRE; i++) tma3d(sm + i * K3_STAGE, tm, bFull + i * 8, 0, i * 64, fc);
    }
    __syncthreads();
    if (warp >= 8) {
        if (tid == 256) {
            pdl_wait();
            pdl_trigger();
            TL(3, 1);
            const bf16* hs = g_hnT + d0 * 64;
            #pragma unroll
            for (int i = 0; i < K3_STAGES; i++) {
                bulk_g2s(sm + i * K3_STAGE + abytes, hs + i * (D_ * 64), K3_STAGE - abytes, bFull + i * 8);
                if (i >= K3_PRE) tma3d(sm + i * K3_STAGE, tm, bFull + i * 8, 0, i * 64, fc);
            }
            int s = 0; uint32_t ph = 0;
            #pragma unroll 1
            for (int i = K3_STAGES; i < 32; i++) {
                mbar_wait(bEmpty + s * 8, ph);
                mbar_expect(bFull + s * 8, K3_STAGE);
                tma3d(sm + s * K3_STAGE, tm, bFull + s * 8, 0, i * 64, fc);
                bulk_g2s(sm + s * K3_STAGE + abytes, hs + i * (D_ * 64), K3_STAGE - abytes, bFull + s * 8);
                if (++s == K3_STAGES) { s = 0; ph ^= 1; }
            }
            if (blockIdx.x < 96) l2_prefetch(w2 + (size_t)(blockIdx.x & 1) * (2304 * S_) + (blockIdx.x >> 1) * 16384, 32768);
        }
    } else {
        const int wg = warp >> 2, w4 = warp & 3, gq = lane >> 2, tw = tid & 127;
        const int f0 = (fc + wg) * 64 + w4 * 16 + gq;
        const float bias0 = 0.5f * __bfloat162float(b1[f0]), bias1 = 0.5f * __bfloat162float(b1[f0 + 8]);
        const int ch = 2 * w4 + ((lane >> 3) & 1);
        const uint32_t lo = ((lane >> 4) * 8 + (lane & 7)) * 128 + ((ch ^ (lane & 7)) << 4);
        bf16* dst = g_u + ((size_t)(fc + wg) * D_ + d0) * 64;
        const uint32_t st = sm + wg * 8192;
        const uint64_t da0 = mkdesc(st, 8192, 1024, 1);
        int s = 0, ps = 0; uint32_t ph = 0;
        if (!tb) {
            float acc[80];
            #pragma unroll
            for (int j = 0; j < 80; j++) acc[j] = (j & 2) ? bias1 : bias0;
            reg_fence<80>(acc);
            const uint64_t db0 = mkdesc(sm + 16384, 16, 1024, 1);
            CK0();
            #pragma unroll 1
            for (int i = 0; i < 32 - K3_STAG; i++) {
                mbar_wait(bFull + s * 8, ph);
                const uint64_t da = dadv(da0, s * K3_STAGE), db = dadv(db0, s * K3_STAGE);
                wg_fence();
                #pragma unroll
                for (int kk = 0; kk < 4; kk++)
                    wgmma_n160<1, 0>(acc, dadv(da, kk * 2048), dadv(db, kk * 32), 1);
                wg_commit();
                wg_wait<1>();
                if (i > 0 && lane == 0) mbar_arrive(bEmpty + ps * 8);
                ps = s;
                if (++s == K3_STAGES) { s = 0; ph ^= 1; }
            }
            if (tid == 0) CK1(3);
            static_assert(K3_STAG < K3_STAGES, "all stages needed by the producer are released in the main loop");
            if (wg == 1) {
                #pragma unroll
                for (int i = 32 - K3_STAG; i < 32; i++) mbar_wait(bFull + (i % K3_STAGES) * 8, (i / K3_STAGES) & 1);
                bar_sync(3, 256);
            }
            #pragma unroll
            for (int i = 32 - K3_STAG; i < 32; i++) {
                if (wg == 0) mbar_wait(bFull + (i % K3_STAGES) * 8, (i / K3_STAGES) & 1);
                wg_fence();
                #pragma unroll
                for (int kk = 0; kk < 4; kk++)
                    wgmma_n160<1, 0>(acc, dadv(da0, (i % K3_STAGES) * K3_STAGE + kk * 2048), dadv(db0, (i % K3_STAGES) * K3_STAGE + kk * 32), 1);
                wg_commit();
            }
            if (wg == 0) bar_arrive(3, 256);
            wg_wait<0>();
            reg_fence<80>(acc);
            if (tw == 0) TL(3, 4 + wg);
            bar_sync(1 + wg, 128);
            k3_store<64, 0>(acc, st, lo, dst, wg, tw);
            k3_store<64, 32>(acc, st + K3_STAGE, lo, dst + 4096, wg, tw);
            k3_store<32, 64>(acc, st + 2 * K3_STAGE, lo, dst + 8192, wg, tw);
        } else {
            k3_typeb(sm, fc, lo, bias0, bias1, b1);
        }
        if (tw == 0) { bulk_wait_read(); TL(3, 6 + wg); }
    }
}

constexpr int K4_STAGES = 5, K4_STAGE = 8192 + 36864, K4_STAG = 4, K4_BAR = K4_STAGES * K4_STAGE, K4_SMEM = K4_BAR + 256;
constexpr int K4_XS = (36 - K4_STAG - 1) % K4_STAGES;
__global__ void __cluster_dims__(2, 1, 1) __launch_bounds__(288, 1) k4_mix2(const __grid_constant__ CUtensorMap tmW2, const __grid_constant__ CUtensorMap tmOut,
                                                                             const bf16* __restrict__ b2) {
    extern __shared__ __align__(1024) char smem[];
    const uint32_t sm = smem_u32(smem);
    const uint32_t bFull = sm + K4_BAR, bEmpty = bFull + K4_STAGES * 8, bP = bEmpty + K4_STAGES * 8, bRdy = bP + 8;
    const int tid = threadIdx.x, lane = tid & 31, warp = __shfl_sync(~0u, tid >> 5, 0);
    const int ks = blockIdx.x & 1, tm = (blockIdx.x >> 1) & 31, tn = blockIdx.x >> 6;
    const int k0 = ks * 36;
    if (tid == 256) {
        TL(4, 0);
        #pragma unroll
        for (int i = 0; i < K4_STAGES; i++) { mbar_init(bFull + i * 8, 1); mbar_init(bEmpty + i * 8, 8); }
        mbar_init(bP, 1); mbar_init(bRdy, 8);
        fence_mbar_init();
        mbar_expect(bP, 36864);
        #pragma unroll
        for (int i = 0; i < K4_STAGES; i++) {
            mbar_expect(bFull + i * 8, K4_STAGE);
            tma3d(sm + i * K4_STAGE, &tmW2, bFull + i * 8, 0, (k0 + i) * 64, tm);
        }
        prefetch_tm(&tmOut);
    }
    __syncthreads();
    cluster_arrive_relaxed();
    if (warp == 8) {
        if (lane == 0) {
            pdl_wait();
            TL(4, 1);
            const bf16* us = g_u + ((size_t)k0 * D_ + tn * 288) * 64;
            #pragma unroll
            for (int i = 0; i < K4_STAGES; i++) bulk_g2s(sm + i * K4_STAGE + 8192, us + (size_t)i * (D_ * 64), 36864, bFull + i * 8);
            int s = 0; uint32_t ph = 0;
            #pragma unroll 1
            for (int i = K4_STAGES; i < 36; i++) {
                mbar_wait(bEmpty + s * 8, ph);
                mbar_expect(bFull + s * 8, K4_STAGE);
                tma3d(sm + s * K4_STAGE, &tmW2, bFull + s * 8, 0, (k0 + i) * 64, tm);
                bulk_g2s(sm + s * K4_STAGE + 8192, us + (size_t)i * (D_ * 64), 36864, bFull + s * 8);
                if (++s == K4_STAGES) { s = 0; ph ^= 1; }
            }
        }
        __syncwarp();
        cluster_wait();
    } else {
        const int wg = warp >> 2, w4 = warp & 3, gq = lane >> 2, tw = tid & 127;
        const bool keep = wg == ks;
        float acc[72];
        const uint64_t da0 = mkdesc(sm, 8192, 1024, 1), db0 = mkdesc(sm + 8192 + wg * 18432, 16, 1024, 1);
        const uint32_t rdy = mapa(bRdy, ks ^ 1);
        cluster_wait();
        CK0();
        int s = 0, ps = 0; uint32_t ph = 0;
        #pragma unroll 1
        for (int i = 0; i < 36 - K4_STAG; i++) {
            mbar_wait(bFull + s * 8, ph);
            const uint64_t da = dadv(da0, s * K4_STAGE), db = dadv(db0, s * K4_STAGE);
            wg_fence();
            #pragma unroll
            for (int kk = 0; kk < 4; kk++)
                wgmma_n144<1, 0>(acc, dadv(da, kk * 2048), dadv(db, kk * 32), (i | kk) != 0);
            wg_commit();
            wg_wait<1>();
            if (i > 0 && lane == 0) mbar_arrive(bEmpty + ps * 8);
            ps = s;
            if (++s == K4_STAGES) { s = 0; ph ^= 1; }
        }
        if (tid == 0) CK1(4);
        const uint32_t xa = sm + K4_XS * K4_STAGE + tw * 16;
        if (!keep) {
            #pragma unroll
            for (int i = 36 - K4_STAG; i < 36; i++) {
                mbar_wait(bFull + (i % K4_STAGES) * 8, (i / K4_STAGES) & 1);
                wg_fence();
                #pragma unroll
                for (int kk = 0; kk < 4; kk++)
                    wgmma_n144<1, 0>(acc, dadv(da0, (i % K4_STAGES) * K4_STAGE + kk * 2048), dadv(db0, (i % K4_STAGES) * K4_STAGE + kk * 32), 1);
                wg_commit();
                if (i == 36 - K4_STAG) { wg_wait<1>(); if (lane == 0) mbar_arrive_remote(rdy); }
            }
            bar_arrive(3, 256);
            mbar_wait(bRdy, 0);
            wg_wait<0>();
            reg_fence<72>(acc);
            if (tw == 0) TL(4, 2);
            const uint32_t rd = mapa(xa, ks ^ 1), rb = mapa(bP, ks ^ 1);
            #pragma unroll
            for (int j = 0; j < 18; j++)
                asm volatile("st.async.shared::cluster.mbarrier::complete_tx::bytes.v4.f32 [%0], {%1,%2,%3,%4}, [%5];"
                             :: "r"(rd + j * 2048), "f"(acc[4 * j]), "f"(acc[4 * j + 1]), "f"(acc[4 * j + 2]), "f"(acc[4 * j + 3]), "r"(rb) : "memory");
            if (tw == 0) TL(4, 3);
        } else {
            const int r0 = tm * 64 + w4 * 16 + gq;
            const float bias0 = __bfloat162float(b2[r0]), bias1 = __bfloat162float(b2[r0 + 8]);
            uint32_t hp[36];
            #pragma unroll
            for (int hh = 0; hh < 2; hh++) {
                const uint32_t* hs = g_h + (size_t)(tm * 8 + tn * 4 + ks * 2 + hh) * (18 * 128);
                #pragma unroll
                for (int j = 0; j < 4; j++) { uint4 v = ldg128(reinterpret_cast<const uint4*>(hs) + j * 128 + tw); hp[hh * 18 + 4 * j] = v.x; hp[hh * 18 + 4 * j + 1] = v.y; hp[hh * 18 + 4 * j + 2] = v.z; hp[hh * 18 + 4 * j + 3] = v.w; }
                uint2 v = ldg64(reinterpret_cast<const uint2*>(hs + 16 * 128) + tw); hp[hh * 18 + 16] = v.x; hp[hh * 18 + 17] = v.y;
            }
            wg_wait<0>();
            reg_fence<72>(acc);
            if (lane == 0) mbar_arrive_remote(rdy);
            #pragma unroll
            for (int j = 0; j < 18; j++) {
                acc[4 * j] += bias0 + bf_lo(hp[2 * j]); acc[4 * j + 1] += bias0 + bf_hi(hp[2 * j]);
                acc[4 * j + 2] += bias1 + bf_lo(hp[2 * j + 1]); acc[4 * j + 3] += bias1 + bf_hi(hp[2 * j + 1]);
            }
            reg_fence<72>(acc);
            #pragma unroll
            for (int i = 36 - K4_STAG; i < 36; i++) mbar_wait(bFull + (i % K4_STAGES) * 8, (i / K4_STAGES) & 1);
            bar_sync(3, 256);
            wg_fence();
            #pragma unroll
            for (int i = 36 - K4_STAG; i < 36; i++)
                #pragma unroll
                for (int kk = 0; kk < 4; kk++)
                    wgmma_n144<1, 0>(acc, dadv(da0, (i % K4_STAGES) * K4_STAGE + kk * 2048), dadv(db0, (i % K4_STAGES) * K4_STAGE + kk * 32), 1);
            wg_commit();
            wg_wait<0>();
            reg_fence<72>(acc);
            if (tw == 0) TL(4, 4);
            bar_sync(1, 128);
            mbar_wait(bP, 0);
            if (tw == 0) TL(4, 5);
            const uint32_t st = sm + ((K4_XS + 1) % K4_STAGES) * K4_STAGE + 8192 + wg * 18432;
            const uint32_t ad = st + (w4 * 16 + ((lane >> 3) & 1) * 8 + (lane & 7)) * 144;
            #pragma unroll
            for (int hh = 0; hh < 2; hh++) {
                uint32_t o[18];
                #pragma unroll
                for (int j = 0; j < 9; j++) {
                    float p0, p1, p2, p3;
                    asm volatile("ld.shared.v4.f32 {%0,%1,%2,%3}, [%4];" : "=f"(p0), "=f"(p1), "=f"(p2), "=f"(p3) : "r"(xa + (hh * 9 + j) * 2048) : "memory");
                    const float* q = acc + hh * 36 + 4 * j;
                    o[2 * j] = pack2(q[0] + p0, q[1] + p1); o[2 * j + 1] = pack2(q[2] + p2, q[3] + p3);
                }
                #pragma unroll
                for (int j = 0; j < 4; j++) stsm4(ad + hh * 9216 + (lane >> 4) * 16 + j * 32, o[4 * j], o[4 * j + 1], o[4 * j + 2], o[4 * j + 3]);
                stsm2(ad + hh * 9216 + 128, o[16], o[17]);
                fence_async_smem();
                bar_sync(1, 128);
                if (tw == 0) { tma2d_store(&tmOut, st + hh * 9216, tn * 288 + ks * 144 + hh * 72, tm * 64); bulk_commit(); }
            }
            if (tw == 0) { bulk_wait_read(); TL(4, 7); }
        }
    }
}

typedef CUresult (*EncFn)(CUtensorMap*, CUtensorMapDataType, cuuint32_t, void*, const cuuint64_t*, const cuuint64_t*, const cuuint32_t*,
                          const cuuint32_t*, CUtensorMapInterleave, CUtensorMapSwizzle, CUtensorMapL2promotion, CUtensorMapFloatOOBfill);

template <typename... KArgs, typename... Args>
static void launch(void (*kern)(KArgs...), dim3 grid, int block, int smem, bool pdl, Args... args) {
    cudaLaunchConfig_t cfg = {};
    cfg.gridDim = grid; cfg.blockDim = dim3(block); cfg.dynamicSmemBytes = smem; cfg.stream = cudaStreamPerThread;
    cudaLaunchAttribute at[1];
    at[0].id = cudaLaunchAttributeProgrammaticStreamSerialization; at[0].val.programmaticStreamSerializationAllowed = 1;
    cfg.attrs = at; cfg.numAttrs = pdl ? 1 : 0;
    cudaLaunchKernelEx(&cfg, kern, args...);
}

extern "C" void kernel_launch(void* const* d_in, const int* in_sizes, int n_in, void* d_out, int out_size) {
    const bf16* x = (const bf16*)d_in[0];
    const bf16* wqkv = (const bf16*)d_in[1];
    const bf16* wphi = (const bf16*)d_in[2];
    const bf16* wo = (const bf16*)d_in[3];
    const bf16* w1 = (const bf16*)d_in[5];
    const bf16* b1 = (const bf16*)d_in[6];
    const bf16* w2 = (const bf16*)d_in[7];
    const bf16* b2 = (const bf16*)d_in[8];
    static EncFn enc = nullptr;
    if (!enc) {
        void* fn = nullptr; cudaDriverEntryPointQueryResult qr;
        cudaGetDriverEntryPoint("cuTensorMapEncodeTiled", &fn, cudaEnableDefault, &qr);
        enc = (EncFn)fn;
        cudaFuncSetAttribute(k1_qkv, cudaFuncAttributeMaxDynamicSharedMemorySize, K1_SMEM);
        cudaFuncSetAttribute(k2_attn, cudaFuncAttributeMaxDynamicSharedMemorySize, K2_SMEM);
        cudaFuncSetAttribute(k3_mix1, cudaFuncAttributeMaxDynamicSharedMemorySize, K3_SMEM);
        cudaFuncSetAttribute(k4_mix2, cudaFuncAttributeMaxDynamicSharedMemorySize, K4_SMEM);
    }
    CUtensorMap tmW1, tmW1b, tmW2, tmOut, tmX, tmXA;
    const cuuint32_t es[3] = {1, 1, 1};
    {
        cuuint64_t dims[3] = {64, (cuuint64_t)S_, (cuuint64_t)(F_ / 64)}; cuuint64_t st[2] = {(cuuint64_t)F_ * 2, 128}; cuuint32_t box[3] = {64, 64, 2};
        enc(&tmW1, CU_TENSOR_MAP_DATA_TYPE_BFLOAT16, 3, (void*)w1, dims, st, box, es, CU_TENSOR_MAP_INTERLEAVE_NONE, CU_TENSOR_MAP_SWIZZLE_128B, CU_TENSOR_MAP_L2_PROMOTION_L2_128B, CU_TENSOR_MAP_FLOAT_OOB_FILL_NONE);
        box[2] = 3;
        enc(&tmW1b, CU_TENSOR_MAP_DATA_TYPE_BFLOAT16, 3, (void*)w1, dims, st, box, es, CU_TENSOR_MAP_INTERLEAVE_NONE, CU_TENSOR_MAP_SWIZZLE_128B, CU_TENSOR_MAP_L2_PROMOTION_L2_128B, CU_TENSOR_MAP_FLOAT_OOB_FILL_NONE);
    }
    {
        cuuint64_t dims[3] = {64, (cuuint64_t)F_, (cuuint64_t)(S_ / 64)}; cuuint64_t st[2] = {(cuuint64_t)S_ * 2, 128}; cuuint32_t box[3] = {64, 64, 1};
        enc(&tmW2, CU_TENSOR_MAP_DATA_TYPE_BFLOAT16, 3, (void*)w2, dims, st, box, es, CU_TENSOR_MAP_INTERLEAVE_NONE, CU_TENSOR_MAP_SWIZZLE_128B, CU_TENSOR_MAP_L2_PROMOTION_L2_128B, CU_TENSOR_MAP_FLOAT_OOB_FILL_NONE);
    }
    {
        cuuint64_t dims[2] = {(cuuint64_t)D_, (cuuint64_t)S_}; cuuint64_t st[1] = {(cuuint64_t)D_ * 2}; cuuint32_t box[2] = {72, 64};
        enc(&tmOut, CU_TENSOR_MAP_DATA_TYPE_BFLOAT16, 2, d_out, dims, st, box, es, CU_TENSOR_MAP_INTERLEAVE_NONE, CU_TENSOR_MAP_SWIZZLE_NONE, CU_TENSOR_MAP_L2_PROMOTION_NONE, CU_TENSOR_MAP_FLOAT_OOB_FILL_NONE);
        enc(&tmX, CU_TENSOR_MAP_DATA_TYPE_BFLOAT16, 2, (void*)x, dims, st, box, es, CU_TENSOR_MAP_INTERLEAVE_NONE, CU_TENSOR_MAP_SWIZZLE_NONE, CU_TENSOR_MAP_L2_PROMOTION_NONE, CU_TENSOR_MAP_FLOAT_OOB_FILL_NONE);
    }
    {
        cuuint64_t dims[3] = {64, (cuuint64_t)S_, 9}; cuuint64_t st[2] = {(cuuint64_t)D_ * 2, 128}; cuuint32_t box[3] = {64, 128, 1};
        enc(&tmXA, CU_TENSOR_MAP_DATA_TYPE_BFLOAT16, 3, (void*)x, dims, st, box, es, CU_TENSOR_MAP_INTERLEAVE_NONE, CU_TENSOR_MAP_SWIZZLE_128B, CU_TENSOR_MAP_L2_PROMOTION_L2_128B, CU_TENSOR_MAP_FLOAT_OOB_FILL_NONE);
    }
    launch(k0_prep, dim3(9, 8, 4), 256, 0, false, x, wqkv, wphi, wo);
    launch(k1_qkv, 128, 512, K1_SMEM, true, tmXA);
    launch(k1b_o, 128, 512, 0, true);
    launch(k2_attn, 128, 256, K2_SMEM, true, tmX, w1);
    launch(k3_mix1, 132, 288, K3_SMEM, true, tmW1, tmW1b, b1, w2);
    launch(k4_mix2, 128, 288, K4_SMEM, true, tmW2, tmOut, b2);
}
```

```cpp
#include <cuda_runtime.h>
#include <cuda.h>
#include <cuda_bf16.h>
#include <stdint.h>
#include <stdlib.h>

typedef __nv_bfloat16 bf16;
#define DEVI __device__ __forceinline__

constexpr int S_ = 2048, D_ = 576, F_ = 4608;
constexpr float LN_EPS = 1e-5f;
constexpr float LOG2E = 1.4426950408889634f;

__device__ __align__(1024) bf16 g_o[S_ * D_];
__device__ __align__(1024) bf16 g_wqkv[8 * 27 * 72 * 64];
__device__ __align__(16) float g_cs[8 * 18 * 216];
__device__ __align__(1024) bf16 g_wo[8 * 72 * 72 * 8];
constexpr int KV_H = 960;
constexpr int PQ_UNIT = 1168;
__device__ __align__(1024) float g_kv[32 * KV_H];
__device__ __align__(1024) unsigned long long g_stats[S_ * 8];
__device__ __align__(16) unsigned long long g_ln[S_];
__device__ __align__(16) float2 g_rc[S_];
__device__ __align__(1024) bf16 g_hnT[D_ * S_];
__device__ __align__(1024) bf16 g_u[D_ * F_];
constexpr int CNT_S = 64;
__device__ __align__(256) unsigned int g_cnt[8 * CNT_S];
#define TL(k, i)
#define CK0()
#define CK1(k)

DEVI uint32_t smem_u32(const void* p) { return (uint32_t)__cvta_generic_to_shared(p); }
DEVI void mbar_init(uint32_t bar, int cnt) { asm volatile("mbarrier.init.shared::cta.b64 [%0], %1;" :: "r"(bar), "r"(cnt) : "memory"); }
DEVI void mbar_expect(uint32_t bar, uint32_t bytes) { asm volatile("mbarrier.arrive.expect_tx.shared::cta.b64 _, [%0], %1;" :: "r"(bar), "r"(bytes) : "memory"); }
DEVI void mbar_wait(uint32_t bar, uint32_t parity) {
    asm volatile("{\n.reg .pred p;\n.reg .u32 it;\n"
                 "mbarrier.try_wait.parity.shared::cta.b64 p, [%0], %1;\n@p bra MW_DONE;\n"
                 "mov.u32 it, 0;\n"
                 "MW_LOOP:\nmbarrier.try_wait.parity.shared::cta.b64 p, [%0], %1;\n@p bra MW_DONE;\n"
                 "add.u32 it, it, 1;\nsetp.lt.u32 p, it, 4194304;\n@p bra MW_LOOP;\ntrap;\n"
                 "MW_DONE:\n}" :: "r"(bar), "r"(parity) : "memory");
}
DEVI void mbar_arrive(uint32_t bar) { asm volatile("mbarrier.arrive.shared::cta.b64 _, [%0];" :: "r"(bar) : "memory"); }
DEVI uint32_t mapa(uint32_t addr, uint32_t cta) { uint32_t r; asm volatile("mapa.shared::cluster.u32 %0, %1, %2;" : "=r"(r) : "r"(addr), "r"(cta)); return r; }
DEVI void mbar_arrive_remote(uint32_t raddr) { asm volatile("mbarrier.arrive.shared::cluster.b64 _, [%0];" :: "r"(raddr) : "memory"); }
DEVI void fence_mbar_init() { asm volatile("fence.mbarrier_init.release.cluster;" ::: "memory"); }
DEVI void fence_async_smem() { asm volatile("fence.proxy.async.shared::cta;" ::: "memory"); }
DEVI void cluster_arrive() { asm volatile("barrier.cluster.arrive.aligned;" ::: "memory"); }
DEVI void cluster_arrive_relaxed() { asm volatile("barrier.cluster.arrive.relaxed.aligned;" ::: "memory"); }
DEVI void cluster_wait() { asm volatile("barrier.cluster.wait.aligned;" ::: "memory"); }
DEVI void bar_sync(int id, int n) { asm volatile("bar.sync %0, %1;" :: "r"(id), "r"(n) : "memory"); }
DEVI void bar_arrive(int id, int n) { asm volatile("bar.arrive %0, %1;" :: "r"(id), "r"(n) : "memory"); }
DEVI void pdl_wait() { asm volatile("griddepcontrol.wait;" ::: "memory"); }
DEVI void pdl_trigger() { asm volatile("griddepcontrol.launch_dependents;" ::: "memory"); }
DEVI void bulk_g2s(uint32_t dst, const void* src, uint32_t bytes, uint32_t bar) {
    asm volatile("cp.async.bulk.shared::cluster.global.mbarrier::complete_tx::bytes [%0], [%1], %2, [%3];" :: "r"(dst), "l"(src), "r"(bytes), "r"(bar) : "memory");
}
DEVI void bulk_g2s_mc(uint32_t dst, const void* src, uint32_t bytes, uint32_t bar, uint16_t mask) {
    asm volatile("cp.async.bulk.shared::cluster.global.mbarrier::complete_tx::bytes.multicast::cluster [%0], [%1], %2, [%3], %4;" :: "r"(dst), "l"(src), "r"(bytes), "r"(bar), "h"(mask) : "memory");
}
DEVI void bulk_s2s(uint32_t rdst, uint32_t src, uint32_t bytes, uint32_t rbar) {
    asm volatile("cp.async.bulk.shared::cluster.shared::cta.mbarrier::complete_tx::bytes [%0], [%1], %2, [%3];" :: "r"(rdst), "r"(src), "r"(bytes), "r"(rbar) : "memory");
}
DEVI void bulk_s2g(void* dst, uint32_t src, uint32_t bytes) {
    asm volatile("cp.async.bulk.global.shared::cta.bulk_group [%0], [%1], %2;" :: "l"(dst), "r"(src), "r"(bytes) : "memory");
}
DEVI void l2_prefetch(const void* p, uint32_t bytes) { asm volatile("cp.async.bulk.prefetch.L2.global [%0], %1;" :: "l"(p), "r"(bytes) : "memory"); }
DEVI void bulk_commit() { asm volatile("cp.async.bulk.commit_group;" ::: "memory"); }
DEVI void bulk_wait_read() { asm volatile("cp.async.bulk.wait_group.read 0;" ::: "memory"); }
DEVI void tma2d(uint32_t dst, const CUtensorMap* tm, uint32_t bar, int c0, int c1) {
    asm volatile("cp.async.bulk.tensor.2d.shared::cluster.global.mbarrier::complete_tx::bytes [%0], [%1, {%3, %4}], [%2];" :: "r"(dst), "l"(tm), "r"(bar), "r"(c0), "r"(c1) : "memory");
}
DEVI void tma3d(uint32_t dst, const CUtensorMap* tm, uint32_t bar, int c0, int c1, int c2) {
    asm volatile("cp.async.bulk.tensor.3d.shared::cluster.global.mbarrier::complete_tx::bytes [%0], [%1, {%3, %4, %5}], [%2];" :: "r"(dst), "l"(tm), "r"(bar), "r"(c0), "r"(c1), "r"(c2) : "memory");
}
DEVI void tma3d_prefetch(const CUtensorMap* tm, int c0, int c1, int c2) {
    asm volatile("cp.async.bulk.prefetch.tensor.3d.L2.global [%0, {%1, %2, %3}];" :: "l"(tm), "r"(c0), "r"(c1), "r"(c2) : "memory");
}
DEVI void tma3d_mc(uint32_t dst, const CUtensorMap* tm, uint32_t bar, int c0, int c1, int c2, uint16_t mask) {
    asm volatile("cp.async.bulk.tensor.3d.shared::cluster.global.mbarrier::complete_tx::bytes.multicast::cluster [%0], [%1, {%3, %4, %5}], [%2], %6;" :: "r"(dst), "l"(tm), "r"(bar), "r"(c0), "r"(c1), "r"(c2), "h"(mask) : "memory");
}
DEVI void tma2d_store(const CUtensorMap* tm, uint32_t src, int c0, int c1) {
    asm volatile("cp.async.bulk.tensor.2d.global.shared::cta.bulk_group [%0, {%2, %3}], [%1];" :: "l"(tm), "r"(src), "r"(c0), "r"(c1) : "memory");
}
DEVI void prefetch_tm(const CUtensorMap* tm) { asm volatile("prefetch.tensormap [%0];" :: "l"(tm) : "memory"); }
DEVI uint64_t mkdesc(uint32_t addr, uint32_t lbo, uint32_t sbo, uint64_t swz) {
    return (uint64_t)((addr & 0x3FFFF) >> 4) | ((uint64_t)(lbo >> 4) << 16) | ((uint64_t)(sbo >> 4) << 32) | (swz << 62);
}
DEVI uint64_t dadv(uint64_t d, uint32_t bytes) { return (d & 0xffffffff00000000ull) | (uint64_t)((uint32_t)d + (bytes >> 4)); }
DEVI void wg_fence() { asm volatile("wgmma.fence.sync.aligned;" ::: "memory"); }
DEVI void wg_commit() { asm volatile("wgmma.commit_group.sync.aligned;" ::: "memory"); }
template<int N> DEVI void wg_wait() { asm volatile("wgmma.wait_group.sync.aligned %0;" :: "n"(N) : "memory"); }
template<int N> DEVI void reg_fence(float* d) {
    #pragma unroll
    for (int i = 0; i < N; i++) asm volatile("" : "+f"(d[i]) :: "memory");
}
DEVI uint32_t pack2(float lo, float hi) { uint32_t r; asm("cvt.rn.bf16x2.f32 %0, %1, %2;" : "=r"(r) : "f"(hi), "f"(lo)); return r; }
DEVI float bf_lo(uint32_t v) { return __uint_as_float(v << 16); }
DEVI float bf_hi(uint32_t v) { return __uint_as_float(v & 0xffff0000u); }
DEVI float ex2(float x) { float r; asm("ex2.approx.ftz.f32 %0, %1;" : "=f"(r) : "f"(x)); return r; }
DEVI float rcp(float x) { float r; asm("rcp.approx.ftz.f32 %0, %1;" : "=f"(r) : "f"(x)); return r; }
DEVI float rcp_full(float x) { float r; asm("rcp.approx.f32 %0, %1;" : "=f"(r) : "f"(x)); return r; }
DEVI float tanh_fast(float x) { float r; asm("tanh.approx.f32 %0, %1;" : "=f"(r) : "f"(x)); return r; }
DEVI void mma16816(float* c, uint32_t a0, uint32_t a1, uint32_t a2, uint32_t a3, uint32_t b0, uint32_t b1) {
    asm("mma.sync.aligned.m16n8k16.row.col.f32.bf16.bf16.f32 {%0,%1,%2,%3}, {%4,%5,%6,%7}, {%8,%9}, {%0,%1,%2,%3};"
        : "+f"(c[0]), "+f"(c[1]), "+f"(c[2]), "+f"(c[3]) : "r"(a0), "r"(a1), "r"(a2), "r"(a3), "r"(b0), "r"(b1));
}
DEVI void mma1688(float* c, uint32_t a0, uint32_t a1, uint32_t b0) {
    asm("mma.sync.aligned.m16n8k8.row.col.f32.bf16.bf16.f32 {%0,%1,%2,%3}, {%4,%5}, {%6}, {%0,%1,%2,%3};"
        : "+f"(c[0]), "+f"(c[1]), "+f"(c[2]), "+f"(c[3]) : "r"(a0), "r"(a1), "r"(b0));
}
DEVI void ldsm4t(uint32_t addr, uint32_t& r0, uint32_t& r1, uint32_t& r2, uint32_t& r3) {
    asm volatile("ldmatrix.sync.aligned.m8n8.x4.trans.shared.b16 {%0,%1,%2,%3}, [%4];" : "=r"(r0), "=r"(r1), "=r"(r2), "=r"(r3) : "r"(addr) : "memory");
}
DEVI void stsm4t(uint32_t addr, uint32_t r0, uint32_t r1, uint32_t r2, uint32_t r3) {
    asm volatile("stmatrix.sync.aligned.m8n8.x4.trans.shared.b16 [%0], {%1,%2,%3,%4};" :: "r"(addr), "r"(r0), "r"(r1), "r"(r2), "r"(r3) : "memory");
}
DEVI void stsm2t(uint32_t addr, uint32_t r0, uint32_t r1) {
    asm volatile("stmatrix.sync.aligned.m8n8.x2.trans.shared.b16 [%0], {%1,%2};" :: "r"(addr), "r"(r0), "r"(r1) : "memory");
}
DEVI void stsm4(uint32_t addr, uint32_t r0, uint32_t r1, uint32_t r2, uint32_t r3) {
    asm volatile("stmatrix.sync.aligned.m8n8.x4.shared.b16 [%0], {%1,%2,%3,%4};" :: "r"(addr), "r"(r0), "r"(r1), "r"(r2), "r"(r3) : "memory");
}
DEVI void stsm2(uint32_t addr, uint32_t r0, uint32_t r1) {
    asm volatile("stmatrix.sync.aligned.m8n8.x2.shared.b16 [%0], {%1,%2};" :: "r"(addr), "r"(r0), "r"(r1) : "memory");
}
DEVI void sts128(uint32_t addr, uint32_t r0, uint32_t r1, uint32_t r2, uint32_t r3) {
    asm volatile("st.shared.v4.b32 [%0], {%1,%2,%3,%4};" :: "r"(addr), "r"(r0), "r"(r1), "r"(r2), "r"(r3) : "memory");
}
DEVI uint32_t lds32(uint32_t addr) { uint32_t r; asm volatile("ld.shared.b32 %0, [%1];" : "=r"(r) : "r"(addr) : "memory"); return r; }
DEVI void sts32(uint32_t addr, uint32_t r0) { asm volatile("st.shared.b32 [%0], %1;" :: "r"(addr), "r"(r0) : "memory"); }
template<int TA, int TB> DEVI void wgmma_n40(float* d, uint64_t da, uint64_t db, int sd) {
  asm volatile("{\n.reg .pred p;\nsetp.ne.b32 p, %22, 0;\n"
    "wgmma.mma_async.sync.aligned.m64n40k16.f32.bf16.bf16 {%0, %1, %2, %3, %4, %5, %6, %7, %8, %9, %10, %11, %12, %13, %14, %15, %16, %17, %18, %19}, %20, %21, p, 1, 1, %23, %24;\n}\n"
    : "+f"(d[0]), "+f"(d[1]), "+f"(d[2]), "+f"(d[3]), "+f"(d[4]), "+f"(d[5]), "+f"(d[6]), "+f"(d[7]), "+f"(d[8]), "+f"(d[9]), "+f"(d[10]), "+f"(d[11]), "+f"(d[12]), "+f"(d[13]), "+f"(d[14]), "+f"(d[15]), "+f"(d[16]), "+f"(d[17]), "+f"(d[18]), "+f"(d[19]) : "l"(da), "l"(db), "r"(sd), "n"(TA), "n"(TB));
}
template<int TA, int TB> DEVI void wgmma_n48(float* d, uint64_t da, uint64_t db, int sd) {
  asm volatile("{\n.reg .pred p;\nsetp.ne.b32 p, %26, 0;\n"
    "wgmma.mma_async.sync.aligned.m64n48k16.f32.bf16.bf16 {%0, %1, %2, %3, %4, %5, %6, %7, %8, %9, %10, %11, %12, %13, %14, %15, %16, %17, %18, %19, %20, %21, %22, %23}, %24, %25, p, 1, 1, %27, %28;\n}\n"
    : "+f"(d[0]), "+f"(d[1]), "+f"(d[2]), "+f"(d[3]), "+f"(d[4]), "+f"(d[5]), "+f"(d[6]), "+f"(d[7]), "+f"(d[8]), "+f"(d[9]), "+f"(d[10]), "+f"(d[11]), "+f"(d[12]), "+f"(d[13]), "+f"(d[14]), "+f"(d[15]), "+f"(d[16]), "+f"(d[17]), "+f"(d[18]), "+f"(d[19]), "+f"(d[20]), "+f"(d[21]), "+f"(d[22]), "+f"(d[23]) : "l"(da), "l"(db), "r"(sd), "n"(TA), "n"(TB));
}
template<int TA, int TB> DEVI void wgmma_n72(float* d, uint64_t da, uint64_t db, int sd) {
  asm volatile("{\n.reg .pred p;\nsetp.ne.b32 p, %38, 0;\n"
    "wgmma.mma_async.sync.aligned.m64n72k16.f32.bf16.bf16 {%0, %1, %2, %3, %4, %5, %6, %7, %8, %9, %10, %11, %12, %13, %14, %15, %16, %17, %18, %19, %20, %21, %22, %23, %24, %25, %26, %27, %28, %29, %30, %31, %32, %33, %34, %35}, %36, %37, p, 1, 1, %39, %40;\n}\n"
    : "+f"(d[0]), "+f"(d[1]), "+f"(d[2]), "+f"(d[3]), "+f"(d[4]), "+f"(d[5]), "+f"(d[6]), "+f"(d[7]), "+f"(d[8]), "+f"(d[9]), "+f"(d[10]), "+f"(d[11]), "+f"(d[12]), "+f"(d[13]), "+f"(d[14]), "+f"(d[15]), "+f"(d[16]), "+f"(d[17]), "+f"(d[18]), "+f"(d[19]), "+f"(d[20]), "+f"(d[21]), "+f"(d[22]), "+f"(d[23]), "+f"(d[24]), "+f"(d[25]), "+f"(d[26]), "+f"(d[27]), "+f"(d[28]), "+f"(d[29]), "+f"(d[30]), "+f"(d[31]), "+f"(d[32]), "+f"(d[33]), "+f"(d[34]), "+f"(d[35]) : "l"(da), "l"(db), "r"(sd), "n"(TA), "n"(TB));
}
template<int TA, int TB> DEVI void wgmma_n96(float* d, uint64_t da, uint64_t db, int sd) {
  asm volatile("{\n.reg .pred p;\nsetp.ne.b32 p, %50, 0;\n"
    "wgmma.mma_async.sync.aligned.m64n96k16.f32.bf16.bf16 {%0, %1, %2, %3, %4, %5, %6, %7, %8, %9, %10, %11, %12, %13, %14, %15, %16, %17, %18, %19, %20, %21, %22, %23, %24, %25, %26, %27, %28, %29, %30, %31, %32, %33, %34, %35, %36, %37, %38, %39, %40, %41, %42, %43, %44, %45, %46, %47}, %48, %49, p, 1, 1, %51, %52;\n}\n"
    : "+f"(d[0]), "+f"(d[1]), "+f"(d[2]), "+f"(d[3]), "+f"(d[4]), "+f"(d[5]), "+f"(d[6]), "+f"(d[7]), "+f"(d[8]), "+f"(d[9]), "+f"(d[10]), "+f"(d[11]), "+f"(d[12]), "+f"(d[13]), "+f"(d[14]), "+f"(d[15]), "+f"(d[16]), "+f"(d[17]), "+f"(d[18]), "+f"(d[19]), "+f"(d[20]), "+f"(d[21]), "+f"(d[22]), "+f"(d[23]), "+f"(d[24]), "+f"(d[25]), "+f"(d[26]), "+f"(d[27]), "+f"(d[28]), "+f"(d[29]), "+f"(d[30]), "+f"(d[31]), "+f"(d[32]), "+f"(d[33]), "+f"(d[34]), "+f"(d[35]), "+f"(d[36]), "+f"(d[37]), "+f"(d[38]), "+f"(d[39]), "+f"(d[40]), "+f"(d[41]), "+f"(d[42]), "+f"(d[43]), "+f"(d[44]), "+f"(d[45]), "+f"(d[46]), "+f"(d[47]) : "l"(da), "l"(db), "r"(sd), "n"(TA), "n"(TB));
}
template<int TA, int TB> DEVI void wgmma_n144(float* d, uint64_t da, uint64_t db, int sd) {
  asm volatile("{\n.reg .pred p;\nsetp.ne.b32 p, %74, 0;\n"
    "wgmma.mma_async.sync.aligned.m64n144k16.f32.bf16.bf16 {%0, %1, %2, %3, %4, %5, %6, %7, %8, %9, %10, %11, %12, %13, %14, %15, %16, %17, %18, %19, %20, %21, %22, %23, %24, %25, %26, %27, %28, %29, %30, %31, %32, %33, %34, %35, %36, %37, %38, %39, %40, %41, %42, %43, %44, %45, %46, %47, %48, %49, %50, %51, %52, %53, %54, %55, %56, %57, %58, %59, %60, %61, %62, %63, %64, %65, %66, %67, %68, %69, %70, %71}, %72, %73, p, 1, 1, %75, %76;\n}\n"
    : "+f"(d[0]), "+f"(d[1]), "+f"(d[2]), "+f"(d[3]), "+f"(d[4]), "+f"(d[5]), "+f"(d[6]), "+f"(d[7]), "+f"(d[8]), "+f"(d[9]), "+f"(d[10]), "+f"(d[11]), "+f"(d[12]), "+f"(d[13]), "+f"(d[14]), "+f"(d[15]), "+f"(d[16]), "+f"(d[17]), "+f"(d[18]), "+f"(d[19]), "+f"(d[20]), "+f"(d[21]), "+f"(d[22]), "+f"(d[23]), "+f"(d[24]), "+f"(d[25]), "+f"(d[26]), "+f"(d[27]), "+f"(d[28]), "+f"(d[29]), "+f"(d[30]), "+f"(d[31]), "+f"(d[32]), "+f"(d[33]), "+f"(d[34]), "+f"(d[35]), "+f"(d[36]), "+f"(d[37]), "+f"(d[38]), "+f"(d[39]), "+f"(d[40]), "+f"(d[41]), "+f"(d[42]), "+f"(d[43]), "+f"(d[44]), "+f"(d[45]), "+f"(d[46]), "+f"(d[47]), "+f"(d[48]), "+f"(d[49]), "+f"(d[50]), "+f"(d[51]), "+f"(d[52]), "+f"(d[53]), "+f"(d[54]), "+f"(d[55]), "+f"(d[56]), "+f"(d[57]), "+f"(d[58]), "+f"(d[59]), "+f"(d[60]), "+f"(d[61]), "+f"(d[62]), "+f"(d[63]), "+f"(d[64]), "+f"(d[65]), "+f"(d[66]), "+f"(d[67]), "+f"(d[68]), "+f"(d[69]), "+f"(d[70]), "+f"(d[71]) : "l"(da), "l"(db), "r"(sd), "n"(TA), "n"(TB));
}
template<int TA, int TB> DEVI void wgmma_n160(float* d, uint64_t da, uint64_t db, int sd) {
  asm volatile("{\n.reg .pred p;\nsetp.ne.b32 p, %82, 0;\n"
    "wgmma.mma_async.sync.aligned.m64n160k16.f32.bf16.bf16 {%0, %1, %2, %3, %4, %5, %6, %7, %8, %9, %10, %11, %12, %13, %14, %15, %16, %17, %18, %19, %20, %21, %22, %23, %24, %25, %26, %27, %28, %29, %30, %31, %32, %33, %34, %35, %36, %37, %38, %39, %40, %41, %42, %43, %44, %45, %46, %47, %48, %49, %50, %51, %52, %53, %54, %55, %56, %57, %58, %59, %60, %61, %62, %63, %64, %65, %66, %67, %68, %69, %70, %71, %72, %73, %74, %75, %76, %77, %78, %79}, %80, %81, p, 1, 1, %83, %84;\n}\n"
    : "+f"(d[0]), "+f"(d[1]), "+f"(d[2]), "+f"(d[3]), "+f"(d[4]), "+f"(d[5]), "+f"(d[6]), "+f"(d[7]), "+f"(d[8]), "+f"(d[9]), "+f"(d[10]), "+f"(d[11]), "+f"(d[12]), "+f"(d[13]), "+f"(d[14]), "+f"(d[15]), "+f"(d[16]), "+f"(d[17]), "+f"(d[18]), "+f"(d[19]), "+f"(d[20]), "+f"(d[21]), "+f"(d[22]), "+f"(d[23]), "+f"(d[24]), "+f"(d[25]), "+f"(d[26]), "+f"(d[27]), "+f"(d[28]), "+f"(d[29]), "+f"(d[30]), "+f"(d[31]), "+f"(d[32]), "+f"(d[33]), "+f"(d[34]), "+f"(d[35]), "+f"(d[36]), "+f"(d[37]), "+f"(d[38]), "+f"(d[39]), "+f"(d[40]), "+f"(d[41]), "+f"(d[42]), "+f"(d[43]), "+f"(d[44]), "+f"(d[45]), "+f"(d[46]), "+f"(d[47]), "+f"(d[48]), "+f"(d[49]), "+f"(d[50]), "+f"(d[51]), "+f"(d[52]), "+f"(d[53]), "+f"(d[54]), "+f"(d[55]), "+f"(d[56]), "+f"(d[57]), "+f"(d[58]), "+f"(d[59]), "+f"(d[60]), "+f"(d[61]), "+f"(d[62]), "+f"(d[63]), "+f"(d[64]), "+f"(d[65]), "+f"(d[66]), "+f"(d[67]), "+f"(d[68]), "+f"(d[69]), "+f"(d[70]), "+f"(d[71]), "+f"(d[72]), "+f"(d[73]), "+f"(d[74]), "+f"(d[75]), "+f"(d[76]), "+f"(d[77]), "+f"(d[78]), "+f"(d[79]) : "l"(da), "l"(db), "r"(sd), "n"(TA), "n"(TB));
}

__host__ __device__ constexpr int ka_seq(int p, int c) { return p == 0 ? c : c >= 5 ? 2 * c - 2 + p : p == 1 ? 17 + c : 22 + c; }
__global__ void __launch_bounds__(256, 3) k0_prep(const bf16* __restrict__ x, const bf16* __restrict__ wqkv, const bf16* __restrict__ wphi) {
    __shared__ __align__(16) uint32_t s_in[64 * 36];
    __shared__ __align__(16) unsigned short s_phi[4 * 324 + 160];
    __shared__ __align__(128) bf16 s_out[72 * 64 + 64];
    if (threadIdx.x == 0) TL(0, 0);
    const int tid = threadIdx.x, lane = tid & 31, warp = __shfl_sync(~0u, tid >> 5, 0);
    const int c = blockIdx.x, g = blockIdx.y, p = blockIdx.z;
    const bool fold = p == 0 || p == 2;
    const int b = (p * 8 + g) * 9 + c;
    if (p == 3) {
        const int j = b - 216;
        const uint4 z = make_uint4(0u, 0u, 0u, 0u);
        if (j < 32) reinterpret_cast<uint4*>(g_stats)[j * 256 + tid] = z;
        else if (j < 62) reinterpret_cast<uint4*>(g_kv)[(j - 32) * 256 + tid] = z;
        else if (j == 66 && tid < 8) g_cnt[tid * CNT_S] = 0u;
        pdl_trigger();
        return;
    }
    {
        constexpr int ld = 1728;
        const bf16* src = wqkv + ((p == 2 ? 0 : p + 1) * 576 + c * 64 * ld + g * 72);
        const uint32_t si = smem_u32(s_in);
        #pragma unroll
        for (int j = 0; j < 3; j++) {
            const int i = tid + j * 256, r = (i * 7282) >> 16;
            if (j < 2 || tid < 64) asm volatile("cp.async.cg.shared.global [%0], [%1], 16;" :: "r"(si + i * 16), "l"(src + (r * (ld - 72) + i * 8)) : "memory");
        }
        if (fold && tid < 162) asm volatile("cp.async.cg.shared.global [%0], [%1], 16;" :: "r"(smem_u32(s_phi) + tid * 16), "l"(wphi + g * 1296 + tid * 8) : "memory");
        pdl_trigger();
        if (threadIdx.x == 0) TL(0, 4);
        const int t = warp & 3, half = warp >> 2, g8 = lane >> 2, c4 = lane & 3;
        uint32_t sa[3];
        {
            const int kc = half * 4 + (lane >> 3);
            #pragma unroll
            for (int fb = 0; fb < 3; fb++) {
                const int f = 8 * fb + (lane & 7), n = 8 * (f >> 1) + 2 * t + (f & 1);
                const uint32_t o = n * 128 + ((kc ^ (n & 7)) << 4);
                sa[fb] = smem_u32(s_out) + (f < 18 ? o : 9216);
            }
        }
        asm volatile("cp.async.wait_all;" ::: "memory");
        if (threadIdx.x == 0) TL(0, 1);
        __syncthreads();
        if (tid < 96 && b < 192) asm volatile("prefetch.global.L2 [%0];" :: "l"(x + b * 6144 + tid * 64));
        if (threadIdx.x == 0) TL(0, 5);
        uint32_t af[3][3];
        if (fold) {
            const unsigned short* ph = s_phi + t * 324 + c4 * 36 + g8;
            #pragma unroll
            for (int fb = 0; fb < 3; fb++)
                #pragma unroll
                for (int db = 0; db < 3; db++) {
                    uint32_t v = (uint32_t)ph[db * 144 + fb * 8] | ((uint32_t)ph[db * 144 + 18 + fb * 8] << 16);
                    if (db == 2 && c4 != 0) v = 0;
                    af[fb][db] = v;
                }
        } else {
            const uint32_t v = (g8 == 2 * c4 ? 0x3f80u : 0u) | (g8 == 2 * c4 + 1 ? 0x3f800000u : 0u);
            #pragma unroll
            for (int fb = 0; fb < 3; fb++)
                #pragma unroll
                for (int db = 0; db < 3; db++) af[fb][db] = fb == db ? v : 0u;
        }
        uint32_t ov[3][4];
        const uint32_t* wr = &s_in[(half * 32 + g8) * 36 + t * 9 + c4];
        #pragma unroll
        for (int j = 0; j < 4; j++) {
            const uint32_t b0 = wr[j * 288], b1 = wr[j * 288 + 4], b2 = c4 == 0 ? wr[j * 288 + 8] : 0u;
            float c0[4] = {0.f, 0.f, 0.f, 0.f}, c1[4] = {0.f, 0.f, 0.f, 0.f};
            mma16816(c0, af[0][0], af[1][0], af[0][1], af[1][1], b0, b1);
            mma1688(c0, af[0][2], af[1][2], b2);
            mma16816(c1, af[2][0], 0u, af[2][1], 0u, b0, b1);
            mma1688(c1, af[2][2], 0u, b2);
            ov[0][j] = pack2(c0[0], c0[1]); ov[1][j] = pack2(c0[2], c0[3]); ov[2][j] = pack2(c1[0], c1[1]);
        }
        #pragma unroll
        for (int fb = 0; fb < 3; fb++) stsm4(sa[fb], ov[fb][0], ov[fb][1], ov[fb][2], ov[fb][3]);
        fence_async_smem();
        if (threadIdx.x == 0) TL(0, 2);
        __syncthreads();
        if (tid == 0) {
            bulk_s2g(g_wqkv + (g * 27 + ka_seq(p, c)) * 4608, smem_u32(s_out), 9216);
            bulk_commit();
        }
        {
            float cs0[4] = {0.f, 0.f, 0.f, 0.f}, cs1[4] = {0.f, 0.f, 0.f, 0.f};
            mma16816(cs0, ov[0][0], ov[1][0], ov[0][1], ov[1][1], 0x3f803f80u, 0x3f803f80u);
            mma16816(cs0, ov[0][2], ov[1][2], ov[0][3], ov[1][3], 0x3f803f80u, 0x3f803f80u);
            mma16816(cs1, ov[2][0], 0u, ov[2][1], 0u, 0x3f803f80u, 0x3f803f80u);
            mma16816(cs1, ov[2][2], 0u, ov[2][3], 0u, 0x3f803f80u, 0x3f803f80u);
            const int f = g8 + 8 * c4;
            if (f < 18) g_cs[(g * 18 + c * 2 + half) * 216 + p * 72 + 8 * (f >> 1) + 2 * t + (f & 1)] = c4 == 0 ? cs0[0] : c4 == 1 ? cs0[2] : cs1[0];
        }
    }
    if (tid == 0) bulk_wait_read();
    if (threadIdx.x == 0) TL(0, 3);
}

DEVI void dual_softmax(const float* a, float scale, uint32_t* o) {
    float mx = a[0], mn = a[0];
    #pragma unroll
    for (int j = 1; j < 18; j++) { mx = fmaxf(mx, a[j]); mn = fminf(mn, a[j]); }
    const float mxs = -mx * scale, mns = mn * scale;
    float ep[18], en[18], sp = 0.f, sn = 0.f;
    #pragma unroll
    for (int j = 0; j < 18; j++) {
        ep[j] = ex2(fmaf(a[j], scale, mxs)); sp += ep[j];
        en[j] = ex2(fmaf(a[j], -scale, mns)); sn += en[j];
    }
    const float rp = rcp(sp), rn = rcp(sn);
    #pragma unroll
    for (int j = 0; j < 9; j++) {
        o[j] = pack2(ep[2 * j] * rp, ep[2 * j + 1] * rp);
        o[9 + j] = pack2(en[2 * j] * rn, en[2 * j + 1] * rn);
    }
}

DEVI uint4 ldg128(const void* p) { uint4 v; asm volatile("ld.global.cg.v4.u32 {%0,%1,%2,%3}, [%4];" : "=r"(v.x), "=r"(v.y), "=r"(v.z), "=r"(v.w) : "l"(p)); return v; }
DEVI uint2 ldg64(const void* p) { uint2 v; asm volatile("ld.global.cg.v2.u32 {%0,%1}, [%2];" : "=r"(v.x), "=r"(v.y) : "l"(p)); return v; }
DEVI uint4 lds128(uint32_t a) { uint4 v; asm volatile("ld.shared.v4.u32 {%0,%1,%2,%3}, [%4];" : "=r"(v.x), "=r"(v.y), "=r"(v.z), "=r"(v.w) : "r"(a) : "memory"); return v; }
DEVI uint2 lds64(uint32_t a) { uint2 v; asm volatile("ld.shared.v2.u32 {%0,%1}, [%2];" : "=r"(v.x), "=r"(v.y) : "r"(a) : "memory"); return v; }
DEVI uint32_t lds16(uint32_t a) { unsigned short v; asm volatile("ld.shared.u16 %0, [%1];" : "=h"(v) : "r"(a) : "memory"); return v; }
DEVI uint32_t packu(uint32_t lo, uint32_t hi) { return pack2(__uint_as_float(lo), __uint_as_float(hi)); }
DEVI void cp16(uint32_t dst, const void* src) { asm volatile("cp.async.cg.shared.global [%0], [%1], 16;" :: "r"(dst), "l"(src) : "memory"); }
DEVI void spin_ge(const unsigned int* p, unsigned int n) {
    uint32_t f; int it = 0;
    do {
        asm volatile("ld.acquire.gpu.global.u32 %0, [%1];" : "=r"(f) : "l"(p) : "memory");
        if (++it > (1 << 22)) __trap();
    } while (f < n);
}
#define LNSLP 700
#define KAPRE 3
constexpr int KA_PRE = KAPRE, KA_REC = 5 * 16384, KA_B = 147456, KA_CS = KA_B + 9 * 9216, KA_LN = KA_CS + 864, KA_BAR = KA_LN + 1024, KA_SMEM = KA_BAR + 160;
static_assert(KA_SMEM <= 232448, "smem");
DEVI int gpc_pos() {
    unsigned smid, nsm;
    asm volatile("mov.u32 %0, %%smid;" : "=r"(smid));
    asm volatile("mov.u32 %0, %%nsmid;" : "=r"(nsm));
    if (nsm != 132) return blockIdx.x;
    const int tpc = smid >> 1, o = smid & 1;
    if (tpc < 32) return (tpc & 7) * 16 + (tpc >> 3) * 2 + o;
    if (tpc < 60) { const int j = tpc - 32, r = j / 7; return (1 + j - r * 7) * 16 + 8 + r * 2 + o; }
    if (tpc < 62) return 128 + (tpc - 60) * 2 + o;
    return 8 + (tpc - 62) * 2 + o;
}
__global__ void __launch_bounds__(640, 1) ka_front(const __grid_constant__ CUtensorMap tmXA, const bf16* __restrict__ x, const bf16* __restrict__ wo, const bf16* __restrict__ w1) {
    extern __shared__ __align__(1024) char smem[];
    const uint32_t sm = smem_u32(smem);
    const uint32_t bFull = sm + KA_BAR, bEmpty = bFull + 9 * 8, bLn = bEmpty + 9 * 8;
    const int tid = threadIdx.x, lane = tid & 31, warp = __shfl_sync(~0u, tid >> 5, 0);
    const int pos = gpc_pos();
    if (pos >= 128) {
        const int ns = pos - 128;
        if (tid < 576) {
            const int r0 = tid / 18, ch = tid - r0 * 18;
            #pragma unroll
            for (int j = 0; j < 18; j++) cp16(sm + (j * 32 + r0) * 304 + ch * 16, wo + (j * 32 + r0) * 576 + ns * 144 + ch * 8);
        }
        asm volatile("cp.async.wait_all;" ::: "memory");
        #pragma unroll 1
        for (int q = 0; q < 6; q++) {
            const uint32_t ob = sm + 175104 + (q & 1) * 27648;
            if (tid == 0) asm volatile("cp.async.bulk.wait_group.read 1;" ::: "memory");
            __syncthreads();
            if (warp < 18) {
                #pragma unroll
                for (int rb = 0; rb < 3; rb++) {
                    uint32_t r0, r1, r2, r3;
                    ldsm4t(sm + (q * 96 + rb * 32 + lane) * 304 + warp * 16, r0, r1, r2, r3);
                    stsm4(ob + (warp / 9) * 13824 + ((rb * 4 + (lane >> 3)) * 72 + (warp % 9) * 8 + (lane & 7)) * 16, r0, r1, r2, r3);
                }
            }
            fence_async_smem();
            __syncthreads();
            if (tid == 0) {
                bulk_s2g(g_wo + (ns * 2) * (72 * 576) + q * 6912, ob, 13824);
                bulk_s2g(g_wo + (ns * 2 + 1) * (72 * 576) + q * 6912, ob + 13824, 13824);
                bulk_commit();
            }
        }
        if (tid == 0) {
            asm volatile("cp.async.bulk.wait_group 0;\nfence.proxy.async.global;\nfence.acq_rel.gpu;" ::: "memory");
            pdl_wait();
            pdl_trigger();
        }
        return;
    }
        const int g = ((pos >> 4) & 1) * 4 + (pos & 3), mt = (pos >> 5) * 4 + ((pos >> 2) & 3);
    const int xrow = mt * 128 + g * 16 + (warp & 15);
    uint4 xv[3];
    if (warp < 16) {
        const uint4* xr = reinterpret_cast<const uint4*>(x + xrow * D_);
        xv[0] = ldg128(xr + lane); xv[1] = ldg128(xr + lane + 32); xv[2] = ldg128(xr + 64 + (lane & 7));
    }
    if (tid == 512) {
        TL(1, 0);
        #pragma unroll
        for (int c = 0; c < 9; c++) mbar_init(bFull + c * 8, 1);
        fence_mbar_init();
        #pragma unroll
        for (int c = 0; c < KA_PRE; c++) tma3d(sm + c * 16384, &tmXA, bFull + c * 8, 0, mt * 128, c);
        #pragma unroll
        for (int c = 0; c < 9; c++) mbar_expect(bFull + c * 8, 16384 + 9216);
    }
    if (tid == 544) {
        #pragma unroll
        for (int c = 0; c < 9; c++) mbar_init(bEmpty + c * 8, 8);
        mbar_init(bLn, 64);
    }
    __syncthreads();
    if (warp >= 16) {
        asm volatile("setmaxnreg.dec.sync.aligned.u32 32;");
        if (tid == 512) {
            pdl_wait();
            pdl_trigger();
            const bf16* wsrc = g_wqkv + g * (27 * 4608);
            const uint32_t sb = sm + KA_B;
            TL(1, 1);
            #pragma unroll
            for (int c = 0; c < 9; c++) {
                bulk_g2s(sb + c * 9216, wsrc + c * 4608, 9216, bFull + c * 8);
                const int xc = c + KA_PRE - 2;
                if (c >= 2 && xc < 9) tma3d(sm + xc * 16384, &tmXA, bFull + xc * 8, 0, mt * 128, xc);
            }
            #pragma unroll 1
            for (int p = 1; p < 3; p++) {
                #pragma unroll
                for (int c = 0; c < 9; c++) {
                    mbar_wait(bEmpty + c * 8, p - 1); mbar_expect(bFull + c * 8, 9216);
                    bulk_g2s(sb + c * 9216, wsrc + (p * 9 + c) * 4608, 9216, bFull + c * 8);
                }
            }
            l2_prefetch(w1 + pos * 13824, 27648);
        } else if (warp == 17) {
            bar_sync(2, 160);
            if (lane == 0) spin_ge(g_cnt + g * CNT_S, 64);
            __syncwarp();
            bar_arrive(1, 288);
        } else if (warp >= 18) {
            const int m = warp - 18;
            {
                const unsigned long long* lp = g_ln + mt * 128 + m * 64 + (lane >> 3) * 16 + (lane & 7);
                unsigned long long r0, r1; int it = 0;
                __nanosleep(LNSLP);
                while (true) {
                    asm volatile("ld.relaxed.gpu.global.u64 %0, [%1];" : "=l"(r0) : "l"(lp) : "memory");
                    asm volatile("ld.relaxed.gpu.global.u64 %0, [%1];" : "=l"(r1) : "l"(lp + 8) : "memory");
                    if (__all_sync(~0u, (long long)(r0 & r1) < 0)) break;
                    if (++it > (1 << 22)) __trap();
                }
                sts128(sm + KA_LN + (m * 32 + lane) * 16, (uint32_t)r0, (uint32_t)(r0 >> 32), (uint32_t)r1, (uint32_t)(r1 >> 32));
                mbar_arrive(bLn);
                if (tid == 576) TL(5, 7);
            }
            bf16* dst = g_o + (mt * 2 + m) * (64 * D_) + g * 4608;
            bar_sync(11 + m, 160);
            if (lane == 0) { bulk_s2g(dst, sm + m * 9216, 9216); bulk_commit(); bulk_wait_read(); if (m == 0) TL(1, 7); }
        }
    } else {
        asm volatile("setmaxnreg.inc.sync.aligned.u32 112;");
        const int wg = warp >> 2, m = wg & 1, w4 = warp & 3, gq = lane >> 2, t = lane & 3;
        {
            const uint32_t w[12] = {xv[0].x, xv[0].y, xv[0].z, xv[0].w, xv[1].x, xv[1].y, xv[1].z, xv[1].w, xv[2].x, xv[2].y, xv[2].z, xv[2].w};
            float s = 0.f, s2 = 0.f;
            #pragma unroll
            for (int i = 0; i < 12; i++) { if (i < 8) s += bf_lo(w[i]) + bf_hi(w[i]); else s2 += bf_lo(w[i]) + bf_hi(w[i]); }
            if (lane < 8) s += s2;
            #pragma unroll
            for (int o = 16; o; o >>= 1) s += __shfl_xor_sync(~0u, s, o);
            const float mean = s * (1.f / D_);
            float q = 0.f, q2 = 0.f;
            #pragma unroll
            for (int i = 0; i < 12; i++) {
                const float e0 = bf_lo(w[i]) - mean, e1 = bf_hi(w[i]) - mean;
                if (i < 8) q += e0 * e0 + e1 * e1; else q2 += e0 * e0 + e1 * e1;
            }
            if (lane < 8) q += q2;
            #pragma unroll
            for (int o = 16; o; o >>= 1) q += __shfl_xor_sync(~0u, q, o);
            const unsigned long long lrec = ((unsigned long long)(__float_as_uint(rsqrtf(q * (1.f / D_) + LN_EPS)) | 0x80000000u) << 32) | __float_as_uint(mean);
            if (lane == 0) asm volatile("st.relaxed.gpu.global.u64 [%0], %1;" :: "l"(g_ln + xrow), "l"(lrec) : "memory");
            if (tid == 256) TL(0, 6);
        }
        float2 ln0, ln1;
        auto ln_get = [&]() {
            mbar_wait(bLn, 0);
            const uint4 v = lds128(sm + KA_LN + (m * 32 + w4 * 8 + gq) * 16);
            ln0 = make_float2(__uint_as_float(v.x), fabsf(__uint_as_float(v.y))); ln1 = make_float2(__uint_as_float(v.z), fabsf(__uint_as_float(v.w)));
        };
        const uint64_t da = mkdesc(sm + m * 8192, 16, 1024, 1), db = mkdesc(sm + KA_B, 16, 1024, 1);
        const uint32_t csa = sm + KA_CS + 8 * t;
        const int rot = (gq + 2 * t) & 7;
        const uint32_t rec = sm + KA_REC + t * 16384 + m * 8192 + (w4 * 16 + rot) * 128;
        const uint32_t pqs = sm + KA_B + m * (16 * PQ_UNIT);
        if (wg < 2) {
            float acc[36]; uint2 cs[9];
            #pragma unroll
            for (int c = 0; c < 9; c++) {
                mbar_wait(bFull + c * 8, 0);
                wg_fence();
                #pragma unroll
                for (int kk = 0; kk < 4; kk++) wgmma_n72<0, 0>(acc, dadv(da, c * 16384 + kk * 32), dadv(db, c * 9216 + kk * 32), (c | kk) != 0);
                wg_commit();
                if (c == 0 && tid == 0) TL(1, 2);
                if (c > 0) { wg_wait<1>(); if (lane == 0) mbar_arrive(bEmpty + (c - 1) * 8); }
            }
            wg_wait<0>();
            reg_fence<36>(acc);
            bar_arrive(5, 512);
            if (lane == 0) mbar_arrive(bEmpty + 8 * 8);
            bar_sync(6, 384);
            #pragma unroll
            for (int j = 0; j < 9; j++) cs[j] = lds64(csa + 32 * j);
            ln_get();
            if (tid == 0) TL(1, 3);
            uint32_t ph[2][18];
            #pragma unroll
            for (int r = 0; r < 2; r++) {
                float a[18];
                const float2 ln = r ? ln1 : ln0;
                #pragma unroll
                for (int j = 0; j < 9; j++) { a[2 * j] = fmaf(-ln.x, __uint_as_float(cs[j].x), acc[4 * j + 2 * r]); a[2 * j + 1] = fmaf(-ln.x, __uint_as_float(cs[j].y), acc[4 * j + 2 * r + 1]); }
                dual_softmax(a, ln.y * LOG2E, ph[r]);
            }
            #pragma unroll
            for (int j = 0; j < 18; j++) asm volatile("" : "+r"(ph[0][j]), "+r"(ph[1][j]));
            if (tid == 0) TL(1, 4);
            bar_sync(3 + m, 256);
            #pragma unroll
            for (int r = 0; r < 2; r++) {
                #pragma unroll
                for (int j = 0; j < 4; j++) sts128(rec + r * 1024 + ((j ^ rot) << 4), ph[r][4 * j], ph[r][4 * j + 1], ph[r][4 * j + 2], ph[r][4 * j + 3]);
                sts128(rec + r * 1024 + ((4 ^ rot) << 4), ph[r][16], ph[r][17], 0u, 0u);
            }
            fence_async_smem();
            bar_sync(8, 512);
            float ck[2][20];
            wg_fence();
            const uint64_t dr = mkdesc(sm + KA_REC + m * 32768, 8192, 1024, 1);
            #pragma unroll
            for (int ks = 0; ks < 8; ks++)
                #pragma unroll
                for (int hh = 0; hh < 2; hh++)
                    wgmma_n40<1, 1>(ck[hh], dadv(dr, hh * 16384 + ks * 2048), dadv(dr, hh * 16384 + ks * 2048), ks != 0);
            wg_commit();
            if (w4 < 2) bar_arrive(7, 512);
            wg_wait<0>();
            reg_fence<20>(ck[0]); reg_fence<20>(ck[1]);
            if (tid == 0) TL(1, 5);
            if (w4 >= 2) {
                #pragma unroll
                for (int hh = 0; hh < 2; hh++) {
                    float* kvh = g_kv + (g * 4 + m * 2 + hh) * KV_H;
                    #pragma unroll
                    for (int e = 0; e < 2; e++) {
                        const int nt = 2 * w4 + e - 5;
                        if (nt >= 0 && (nt < 2 || gq < 3)) {
                            float* p = kvh + nt * 320;
                            const float* q = ck[hh] + 2 * e;
                            asm volatile("red.global.add.v4.f32 [%0], {%1, %2, %3, %4};" :: "l"(p + lane * 4), "f"(q[0]), "f"(q[1]), "f"(q[4]), "f"(q[5]) : "memory");
                            asm volatile("red.global.add.v4.f32 [%0], {%1, %2, %3, %4};" :: "l"(p + 128 + lane * 4), "f"(q[8]), "f"(q[9]), "f"(q[12]), "f"(q[13]) : "memory");
                            if (t < 2) asm volatile("red.global.add.v2.f32 [%0], {%1, %2};" :: "l"(p + 256 + lane * 2), "f"(q[16]), "f"(q[17]) : "memory");
                        }
                    }
                }
                __syncwarp();
                bar_arrive(7, 512);
                if (lane == 0) asm volatile("red.release.gpu.global.add.u32 [%0], 1;" :: "l"(g_cnt + g * CNT_S) : "memory");
                __syncwarp();
                bar_arrive(2, 160);
                if (tid == 96) TL(5, 3);
            }
            const float* kp = g_kv + (g * 4 + w4) * KV_H + lane * 2;
            bar_sync(1, 288);
            if (tid == 0) TL(1, 6);
            uint4 u0[3], u1[3]; uint2 u2[3];
            #pragma unroll
            for (int n = 2; n >= 0; n--) { u0[n] = ldg128(kp + n * 320 + lane * 2); u1[n] = ldg128(kp + n * 320 + 128 + lane * 2); u2[n] = ldg64(kp + n * 320 + 256); }
            bar_sync(9 + m, 256);
            uint4 a0[4], a1[4]; uint2 at[4];
            #pragma unroll
            for (int mm = 0; mm < 4; mm++) {
                const uint32_t ub = pqs + (mm * 4 + w4) * PQ_UNIT;
                a0[mm] = lds128(ub + lane * 16); a1[mm] = lds128(ub + 512 + lane * 16); at[mm] = lds64(ub + 1024 + gq * 16 + (t & 1) * 8);
            }
            uint32_t bq[3][5];
            #pragma unroll
            for (int n = 0; n < 3; n++) {
                bq[n][0] = packu(u0[n].x, u0[n].y); bq[n][1] = packu(u0[n].z, u0[n].w);
                bq[n][2] = packu(u1[n].x, u1[n].y); bq[n][3] = packu(u1[n].z, u1[n].w);
                bq[n][4] = packu(u2[n].x, u2[n].y);
            }
            const uint32_t os = sm + m * 9216;
            uint32_t oad[3];
            #pragma unroll
            for (int n = 0; n < 3; n++) { const int k = w4 * 18 + n * 8 + 2 * t; oad[n] = os + (k >> 3) * 1024 + gq * 16 + (k & 7) * 2; }
            #pragma unroll
            for (int mp = 0; mp < 2; mp++) {
                float c[2][3][4];
                #pragma unroll
                for (int e = 0; e < 2; e++)
                    #pragma unroll
                    for (int n = 2; n >= 0; n--) {
                        c[e][n][0] = c[e][n][1] = c[e][n][2] = c[e][n][3] = 0.f;
                        mma16816(c[e][n], a0[2 * mp + e].x, a1[2 * mp + e].x, a0[2 * mp + e].y, a1[2 * mp + e].y, bq[n][0], bq[n][1]);
                    }
                #pragma unroll
                for (int e = 0; e < 2; e++)
                    #pragma unroll
                    for (int n = 2; n >= 0; n--) mma16816(c[e][n], a0[2 * mp + e].z, a1[2 * mp + e].z, a0[2 * mp + e].w, a1[2 * mp + e].w, bq[n][2], bq[n][3]);
                #pragma unroll
                for (int e = 0; e < 2; e++)
                    #pragma unroll
                    for (int n = 2; n >= 0; n--) mma1688(c[e][n], at[2 * mp + e].x, at[2 * mp + e].y, bq[n][4]);
                float rr[2][2];
                #pragma unroll
                for (int e = 0; e < 2; e++) {
                    rr[e][0] = __shfl_sync(~0u, c[e][2][0], (lane & 28) | 1); rr[e][1] = __shfl_sync(~0u, c[e][2][2], (lane & 28) | 1);
                }
                #pragma unroll
                for (int e = 0; e < 2; e++) {
                    const float r0 = rcp_full(rr[e][0] + 1e-6f), r1 = rcp_full(rr[e][1] + 1e-6f);
                    #pragma unroll
                    for (int n = 0; n < 3; n++) {
                        const uint32_t v0 = pack2(c[e][n][0] * r0, c[e][n][1] * r0), v1 = pack2(c[e][n][2] * r1, c[e][n][3] * r1);
                        if (n < 2 || t == 0) { sts32(oad[n] + (2 * mp + e) * 256, v0); sts32(oad[n] + (2 * mp + e) * 256 + 128, v1); }
                    }
                }
            }
            fence_async_smem();
            bar_arrive(11 + m, 160);
        } else {
            float avq[36], acc[36]; uint2 cs[9];
            if (m == 1) {
                pdl_wait();
                if (tid < 384 + 108) {
                    uint2 pc[18];
                    #pragma unroll
                    for (int j = 0; j < 18; j++) pc[j] = ldg64(g_cs + (g * 18 + j) * 216 + (tid - 384) * 2);
                    float a = 0.f, c = 0.f;
                    #pragma unroll
                    for (int j = 0; j < 18; j++) { a += __uint_as_float(pc[j].x); c += __uint_as_float(pc[j].y); }
                    asm volatile("st.shared.v2.f32 [%0], {%1, %2};" :: "r"(sm + KA_CS + (tid - 384) * 8), "f"(a), "f"(c) : "memory");
                }
                if (tid == 384) TL(5, 4);
                bar_arrive(6, 384);
            }
            bar_sync(5, 512);
            if (tid == 256) TL(5, 5);
            #pragma unroll
            for (int i = 9; i < 22; i++) {
                const int c = i < 17 ? (i + 1) / 2 : i - 17;
                mbar_wait(bFull + (i % 9) * 8, (i / 9) & 1);
                wg_fence();
                #pragma unroll
                for (int kk = 0; kk < 4; kk++)
                    wgmma_n72<0, 0>((i < 17 && !(i & 1)) ? acc : avq, dadv(da, c * 16384 + kk * 32), dadv(db, (i % 9) * 9216 + kk * 32), i > 10 || kk != 0);
                wg_commit();
                if (i > 9 && i <= 18) { wg_wait<1>(); if (lane == 0) mbar_arrive(bEmpty + ((i - 1) % 9) * 8); }
                if (i == 17) bar_arrive(3 + m, 256);
                if (i == 18) bar_sync(14 + m, 128);
            }
            #pragma unroll
            for (int j = 0; j < 9; j++) cs[j] = lds64(csa + 288 + 32 * j);
            ln_get();
            wg_wait<0>();
            reg_fence<36>(avq);
            if (tid == 256) TL(5, 0);
            #pragma unroll
            for (int r = 0; r < 2; r++) {
                uint32_t pv[9];
                const float2 ln = r ? ln1 : ln0;
                #pragma unroll
                for (int j = 0; j < 9; j++)
                    pv[j] = pack2(fmaf(-ln.x, __uint_as_float(cs[j].x), avq[4 * j + 2 * r]) * ln.y, fmaf(-ln.x, __uint_as_float(cs[j].y), avq[4 * j + 2 * r + 1]) * ln.y);
                sts128(rec + r * 1024 + ((5 ^ rot) << 4), pv[0], pv[1], pv[2], pv[3]);
                sts128(rec + r * 1024 + ((6 ^ rot) << 4), pv[4], pv[5], pv[6], pv[7]);
                sts128(rec + r * 1024 + ((7 ^ rot) << 4), pv[8], 0x00003f80u, 0u, 0u);
            }
            fence_async_smem();
            bar_arrive(8, 512);
            const uint32_t sm2 = __shfl_sync(~0u, sm, 1);
            const uint64_t da2 = mkdesc(sm2 + m * 8192, 16, 1024, 1), db2 = mkdesc(sm2 + KA_B, 16, 1024, 1);
            #pragma unroll
            for (int i = 22; i < 27; i++) mbar_wait(bFull + (i % 9) * 8, 0);
            #pragma unroll
            for (int j = 0; j < 9; j++) cs[j] = lds64(csa + 576 + 32 * j);
            bar_sync(7, 512);
            wg_fence();
            #pragma unroll
            for (int i = 22; i < 27; i++)
                #pragma unroll
                for (int kk = 0; kk < 4; kk++) wgmma_n72<0, 0>(acc, dadv(da2, (i - 22) * 16384 + kk * 32), dadv(db2, (i % 9) * 9216 + kk * 32), 1);
            wg_commit();
            wg_wait<0>();
            reg_fence<36>(acc);
            if (tid == 256) TL(5, 1);
            uint32_t ph[2][18];
            #pragma unroll
            for (int r = 0; r < 2; r++) {
                float a[18];
                const float2 ln = r ? ln1 : ln0;
                #pragma unroll
                for (int j = 0; j < 9; j++) { a[2 * j] = fmaf(-ln.x, __uint_as_float(cs[j].x), acc[4 * j + 2 * r]); a[2 * j + 1] = fmaf(-ln.x, __uint_as_float(cs[j].y), acc[4 * j + 2 * r + 1]); }
                dual_softmax(a, ln.y * LOG2E, ph[r]);
            }
            #pragma unroll
            for (int j = 0; j < 18; j++) asm volatile("" : "+r"(ph[0][j]), "+r"(ph[1][j]));
            bar_sync(13, 256);
            const uint32_t ub = pqs + (w4 * 4 + t) * PQ_UNIT;
            #pragma unroll
            for (int r = 0; r < 2; r++)
                #pragma unroll
                for (int j = 0; j < 4; j++) sts128(ub + r * 512 + (gq * 4 + j) * 16, ph[r][j], ph[r][4 + j], ph[r][8 + j], ph[r][12 + j]);
            sts128(ub + 1024 + gq * 16, ph[0][16], ph[1][16], ph[0][17], ph[1][17]);
            bar_arrive(9 + m, 256);
            if (tid == 256) TL(5, 2);
        }
    }
}

constexpr int K2_B = 73728, K2_PIECE = 27648, K2_X = K2_B + 5 * K2_PIECE, K2_BAR = K2_X + 18432, K2_SMEM = K2_BAR + 128;
__global__ void __cluster_dims__(2, 1, 1) __launch_bounds__(256, 1) k2_attn(const __grid_constant__ CUtensorMap tmX, const bf16* __restrict__ b2) {
    extern __shared__ __align__(1024) char smem[];
    const uint32_t sm = smem_u32(smem);
    const uint32_t bFull = sm + K2_BAR, bX = bFull + 6 * 8;
    const int tid = threadIdx.x, lane = tid & 31, warp = __shfl_sync(~0u, tid >> 5, 0);
    const int ns = blockIdx.x & 3, mt = blockIdx.x >> 2;
    const int wg = warp >> 2, w4 = warp & 3, gq = lane >> 2, t = lane & 3;
    const bf16* wsrc = g_wo + ns * (2 * 72 * 576);
    unsigned short bb0, bb1;
    asm volatile("ld.global.nc.u16 %0, [%1];" : "=h"(bb0) : "l"(b2 + mt * 64 + w4 * 16 + gq));
    asm volatile("ld.global.nc.u16 %0, [%1];" : "=h"(bb1) : "l"(b2 + mt * 64 + w4 * 16 + gq + 8));
    auto load_w = [&](int i) {
        bulk_g2s(sm + K2_B + (i % 5) * K2_PIECE, wsrc + i * (K2_PIECE / 4), K2_PIECE / 2, bFull + i * 8);
        bulk_g2s(sm + K2_B + (i % 5) * K2_PIECE + K2_PIECE / 2, wsrc + 72 * 576 + i * (K2_PIECE / 4), K2_PIECE / 2, bFull + i * 8);
    };
    if (tid == 0) {
        TL(2, 0);
        #pragma unroll
        for (int i = 0; i < 7; i++) mbar_init(bFull + i * 8, 1);
        fence_mbar_init();
        #pragma unroll
        for (int i = 0; i < 6; i++) mbar_expect(bFull + i * 8, K2_PIECE + 12288);
        mbar_expect(bX, 18432);
        load_w(0); load_w(1);
        prefetch_tm(&tmX);
    }
    __syncthreads();
    if (tid == 0) {
        pdl_wait();
        pdl_trigger();
        TL(2, 1);
        const bf16* osrc = g_o + mt * (64 * D_);
        #pragma unroll
        for (int i = 0; i < 6; i++) {
            bulk_g2s(sm + i * 12288, osrc + i * 6144, 12288, bFull + i * 8);
            if (i >= 1 && i < 4) load_w(i + 1);
        }
        tma2d(sm + K2_X, &tmX, bX, ns * 144, mt * 64);
        tma2d(sm + K2_X + 9216, &tmX, bX, ns * 144 + 72, mt * 64);
    }
    __syncwarp();
    {
        float acc[36];
        const uint32_t xs = sm + K2_X + wg * 9216;
        uint32_t xr[18];
        const int p = ns * 2 + wg;
        unsigned long long* sb = g_stats + (mt * 4 + w4) * 128 + gq * 2;
        unsigned long long* sw = sb + p * 16;
        const unsigned long long* sr = sb + t * 32;
        bf16* ndst = g_hnT + (mt * D_ + p * 72) * 64;
        asm volatile("" : "+l"(sw), "+l"(sr), "+l"(ndst));
        const uint64_t da0 = mkdesc(sm, 1024, 128, 0), db0 = mkdesc(sm + K2_B + wg * (K2_PIECE / 2), 1152, 128, 0);
        #pragma unroll
        for (int i = 0; i < 6; i++) {
            mbar_wait(bFull + i * 8, 0);
            if (i == 0 && tid == 0) TL(2, 3);
            wg_fence();
            #pragma unroll
            for (int kk = 0; kk < 6; kk++)
                wgmma_n72<0, 0>(acc, dadv(da0, i * 12288 + kk * 2048), dadv(db0, (i % 5) * K2_PIECE + kk * 2304), (i | kk) != 0);
            wg_commit();
            if (i == 1) {
                wg_wait<1>();
                bar_sync(1 + wg, 128);
                if ((tid & 127) == 96) bulk_g2s(sm + K2_B + wg * (K2_PIECE / 2), wsrc + wg * (72 * 576) + 5 * (K2_PIECE / 4), K2_PIECE / 2, bFull + 5 * 8);
                __syncwarp();
            }
            if (i == 5) {
                mbar_wait(bX, 0);
                #pragma unroll
                for (int j = 0; j < 9; j++) {
                    xr[2 * j] = lds32(xs + (w4 * 16 + gq) * 144 + j * 16 + t * 4); xr[2 * j + 1] = lds32(xs + (w4 * 16 + gq + 8) * 144 + j * 16 + t * 4);
                }
            }
        }
        wg_wait<0>();
        reg_fence<36>(acc);
        #pragma unroll
        for (int j = 0; j < 18; j++) { acc[2 * j] += bf_lo(xr[j]); acc[2 * j + 1] += bf_hi(xr[j]); }
        if (tid == 0) TL(2, 4);
        float m0 = 0.f, m1 = 0.f;
        #pragma unroll
        for (int j = 0; j < 9; j++) { m0 += acc[4 * j] + acc[4 * j + 1]; m1 += acc[4 * j + 2] + acc[4 * j + 3]; }
        m0 *= (1.f / 18); m1 *= (1.f / 18);
        float q0 = 0.f, q1 = 0.f, q2 = 0.f, q3 = 0.f;
        #pragma unroll
        for (int j = 0; j < 9; j++) {
            float e;
            e = acc[4 * j] - m0; q0 = fmaf(e, e, q0); e = acc[4 * j + 1] - m0; q2 = fmaf(e, e, q2);
            e = acc[4 * j + 2] - m1; q1 = fmaf(e, e, q1); e = acc[4 * j + 3] - m1; q3 = fmaf(e, e, q3);
        }
        q0 += q2; q1 += q3;
        #pragma unroll
        for (int o = 1; o < 4; o <<= 1) {
            const float a0 = __shfl_xor_sync(~0u, m0, o), a1 = __shfl_xor_sync(~0u, m1, o), b0 = __shfl_xor_sync(~0u, q0, o), b1 = __shfl_xor_sync(~0u, q1, o);
            q0 += b0 + (a0 - m0) * (a0 - m0) * (9.f * o); q1 += b1 + (a1 - m1) * (a1 - m1) * (9.f * o);
            m0 = 0.5f * (m0 + a0); m1 = 0.5f * (m1 + a1);
        }
        if (t == 0) {
            const unsigned long long r0 = ((unsigned long long)(__float_as_uint(q0) | 0x80000000u) << 32) | __float_as_uint(m0);
            const unsigned long long r1 = ((unsigned long long)(__float_as_uint(q1) | 0x80000000u) << 32) | __float_as_uint(m1);
            asm volatile("st.relaxed.gpu.global.v2.u64 [%0], {%1, %2};" :: "l"(sw), "l"(r0), "l"(r1) : "memory");
        }
        bar_sync(1 + wg, 128);
        if (tid == 0) TL(2, 5);
        unsigned long long ra, rb, rc, rd;
        {
            int it = 0;
            while (true) {
                asm volatile("ld.relaxed.gpu.global.v2.u64 {%0, %1}, [%2];" : "=l"(ra), "=l"(rc) : "l"(sr) : "memory");
                asm volatile("ld.relaxed.gpu.global.v2.u64 {%0, %1}, [%2];" : "=l"(rb), "=l"(rd) : "l"(sr + 16) : "memory");
                const bool ok = (long long)(ra & rb & rc & rd) < 0;
                if (__all_sync(~0u, ok)) break;
                if (++it > (1 << 22)) __trap();
            }
        }
        if (tid == 0) TL(2, 6);
        float sc[2], mu[2];
        #pragma unroll
        for (int r = 0; r < 2; r++) {
            const unsigned long long u = r ? rc : ra, v = r ? rd : rb;
            const float ma = __uint_as_float((uint32_t)u), mb = __uint_as_float((uint32_t)v);
            float ms = ma + mb;
            ms += __shfl_xor_sync(~0u, ms, 1); ms += __shfl_xor_sync(~0u, ms, 2);
            const float mean = ms * 0.125f;
            float M2 = fabsf(__uint_as_float((uint32_t)(u >> 32))) + fabsf(__uint_as_float((uint32_t)(v >> 32))) + 72.f * ((ma - mean) * (ma - mean) + (mb - mean) * (mb - mean));
            M2 += __shfl_xor_sync(~0u, M2, 1); M2 += __shfl_xor_sync(~0u, M2, 2);
            const float var = M2 * (1.f / D_);
            const float r1 = rsqrtf(var + LN_EPS);
            const float var2 = var * r1 * r1;
            const float r2 = rsqrtf(var2 + LN_EPS);
            sc[r] = 0.5f * (r1 * r2); mu[r] = mean;
        }
        {
            uint32_t o[18];
            #pragma unroll
            for (int j = 0; j < 9; j++) {
                o[2 * j] = pack2((acc[4 * j] - mu[0]) * sc[0], (acc[4 * j + 1] - mu[0]) * sc[0]);
                o[2 * j + 1] = pack2((acc[4 * j + 2] - mu[1]) * sc[1], (acc[4 * j + 3] - mu[1]) * sc[1]);
            }
            const int ch = 2 * w4 + ((lane >> 3) & 1);
            const uint32_t ad = xs + ((lane >> 4) * 8 + (lane & 7)) * 128 + ((ch ^ (lane & 7)) << 4);
            #pragma unroll
            for (int j = 0; j < 4; j++) stsm4t(ad + j * 2048, o[4 * j], o[4 * j + 1], o[4 * j + 2], o[4 * j + 3]);
            stsm2t(xs + (64 + (lane & 7)) * 128 + ((ch ^ (lane & 7)) << 4), o[16], o[17]);
        }
        fence_async_smem();
        bar_sync(1 + wg, 128);
        if ((tid & 127) == 0) {
            bulk_s2g(ndst, xs, 9216);
            bulk_commit();
        }
        if (p == 1 && t < 2) g_ln[mt * 64 + w4 * 16 + gq + 8 * t] = 0ull;
        if (p == 0 && t < 2) {
            asm volatile("" : "+h"(bb0), "+h"(bb1));
            g_rc[mt * 64 + w4 * 16 + gq + 8 * t] = make_float2(1.f / (t ? sc[1] : sc[0]), (t ? mu[1] : mu[0]) + __uint_as_float((uint32_t)(t ? bb1 : bb0) << 16));
        }
        if ((tid & 127) == 0) bulk_wait_read();
        if (tid == 0) TL(2, 7);
    }
}

#define PFT 4
#define W2HEAD 9
#define K3STAG 6
constexpr int K3_STAGES = 6, K3_STAGE = 36864, K3_STAG = K3STAG, K3_PRE = 2, K3_BAR = K3_STAGES * K3_STAGE, K3_SMEM = K3_BAR + 256;
DEVI uint32_t gelu2(float a0, float a1) {
    const float z0 = a0 * fmaf(a0 * a0, 0.2854192650904f, 1.5957691216057f), z1 = a1 * fmaf(a1 * a1, 0.2854192650904f, 1.5957691216057f);
    return pack2(fmaf(a0, tanh_fast(z0), a0), fmaf(a1, tanh_fast(z1), a1));
}
template<int ROWS, int OFF> DEVI void k3_store(const float* q, uint32_t st, uint32_t lo, int bar) {
    #pragma unroll
    for (int jj = 0; jj < ROWS / 16; jj++)
        stsm4t(st + lo + jj * 2048, gelu2(q[OFF + jj * 8], q[OFF + jj * 8 + 1]), gelu2(q[OFF + jj * 8 + 2], q[OFF + jj * 8 + 3]),
               gelu2(q[OFF + jj * 8 + 4], q[OFF + jj * 8 + 5]), gelu2(q[OFF + jj * 8 + 6], q[OFF + jj * 8 + 7]));
    fence_async_smem();
    bar_arrive(bar, 160);
}
DEVI void k3_typeb(uint32_t sm_, int fc_, uint32_t lo, float bias0, float bias1, const bf16* __restrict__ b1) {
    const uint32_t sm = __shfl_sync(~0u, sm_, 0);
    const int fc = __shfl_sync(~0u, fc_, 0);
    const uint32_t bFull = sm + K3_BAR, bEmpty = bFull + K3_STAGES * 8;
    const int tid = threadIdx.x, lane = tid & 31, warp = __shfl_sync(~0u, tid >> 5, 0);
    const int wg = warp >> 2, w4 = warp & 3, gq = lane >> 2, tw = tid & 127;
    const uint32_t st = sm + wg * 8192;
    const uint64_t da0 = mkdesc(st, 8192, 1024, 1);
    int s = 0, ps = 0; uint32_t ph = 0;
    {
            const int f2 = (fc + 2) * 64 + w4 * 16 + gq;
            const float bias2 = 0.5f * __bfloat162float(b1[f2]), bias3 = 0.5f * __bfloat162float(b1[f2 + 8]);
            float acc[48], acc2[24];
            const uint64_t da2 = mkdesc(sm + 16384, 8192, 1024, 1), db0 = mkdesc(sm + 24576, 16, 1024, 1), db2 = mkdesc(sm + 24576 + wg * 6144, 16, 1024, 1);
            #pragma unroll 1
            for (int i = 0; i < 32 - K3_STAG; i++) {
                mbar_wait(bFull + s * 8, ph);
                const uint32_t so = s * K3_STAGE;
                wg_fence();
                #pragma unroll
                for (int kk = 0; kk < 4; kk++) {
                    wgmma_n96<1, 0>(acc, dadv(da0, so + kk * 2048), dadv(db0, so + kk * 32), (i | kk) != 0);
                    wgmma_n48<1, 0>(acc2, dadv(da2, so + kk * 2048), dadv(db2, so + kk * 32), (i | kk) != 0);
                }
                wg_commit();
                wg_wait<1>();
                if (i > 0 && lane == 0) mbar_arrive(bEmpty + ps * 8);
                ps = s;
                if (++s == K3_STAGES) { s = 0; ph ^= 1; }
            }
            if (wg == 1) {
                wg_wait<0>();
                if (lane == 0) mbar_arrive(bEmpty + ps * 8);
                #pragma unroll
                for (int i = 32 - K3_STAG; i < 32; i++) mbar_wait(bFull + (i % K3_STAGES) * 8, (i / K3_STAGES) & 1);
                bar_sync(3, 256);
            }
            #pragma unroll
            for (int i = 32 - K3_STAG; i < 32; i++) {
                if (wg == 0) mbar_wait(bFull + (i % K3_STAGES) * 8, (i / K3_STAGES) & 1);
                const uint32_t so = (i % K3_STAGES) * K3_STAGE;
                wg_fence();
                #pragma unroll
                for (int kk = 0; kk < 4; kk++) {
                    wgmma_n96<1, 0>(acc, dadv(da0, so + kk * 2048), dadv(db0, so + kk * 32), 1);
                    wgmma_n48<1, 0>(acc2, dadv(da2, so + kk * 2048), dadv(db2, so + kk * 32), 1);
                }
                wg_commit();
                if (i == 32 - K3_STAG && wg == 0) { wg_wait<1>(); if (lane == 0) mbar_arrive(bEmpty + ps * 8); }
            }
            if (wg == 0) bar_arrive(3, 256);
            wg_wait<0>();
            reg_fence<48>(acc); reg_fence<24>(acc2);
            #pragma unroll
            for (int j = 0; j < 48; j++) acc[j] += (j & 2) ? bias1 : bias0;
            #pragma unroll
            for (int j = 0; j < 24; j++) acc2[j] += (j & 2) ? bias3 : bias2;
            if (tw == 0) TL(7, 4 + wg);
            bar_sync(1 + wg, 128);
            k3_store<48, 0>(acc, st, lo, 4 + wg * 4);
            k3_store<48, 24>(acc, st + K3_STAGE, lo, 5 + wg * 4);
            k3_store<32, 0>(acc2, st + 2 * K3_STAGE, lo, 6 + wg * 4);
            k3_store<16, 16>(acc2, st + 3 * K3_STAGE, lo, 7 + wg * 4);
    }
}
__global__ void __cluster_dims__(2, 1, 1) __launch_bounds__(352, 1) k3_mix1(const __grid_constant__ CUtensorMap tmW1a, const __grid_constant__ CUtensorMap tmW1b,
                                                                             const bf16* __restrict__ b1, const bf16* __restrict__ w1, const bf16* __restrict__ w2) {
    extern __shared__ __align__(1024) char smem[];
    const uint32_t sm = smem_u32(smem);
    const uint32_t bFull = sm + K3_BAR, bEmpty = bFull + K3_STAGES * 8;
    const int tid = threadIdx.x, lane = tid & 31, warp = __shfl_sync(~0u, tid >> 5, 0);
    const int cl = blockIdx.x >> 1, rank = blockIdx.x & 1;
    bool tb = false; int fc, d0;
    if (cl < 36) { fc = 2 * cl; d0 = 160 * rank; }
    else if (cl < 60) { const int q = (cl - 36) >> 1, e = (cl - 36) & 1; tb = rank; fc = rank ? 6 * q + 3 * e : 6 * q + 4 * e; d0 = rank ? 480 : 320; }
    else { fc = 6 * (2 * (cl - 60) + rank) + 2; d0 = 320; }
    const CUtensorMap* tm = tb ? &tmW1b : &tmW1a;
    const uint32_t abytes = tb ? 24576 : 16384;
    if (tid == 256) {
        TL(3, 0);
        #pragma unroll
        for (int i = 0; i < K3_STAGES; i++) { mbar_init(bFull + i * 8, 1); mbar_init(bEmpty + i * 8, 8); }
        fence_mbar_init();
        #pragma unroll
        for (int i = 0; i < K3_STAGES; i++) mbar_expect(bFull + i * 8, K3_STAGE);
        #pragma unroll
        for (int i = 0; i < K3_PRE; i++) tma3d(sm + i * K3_STAGE, tm, bFull + i * 8, 0, i * 64, fc);
    }
    __syncthreads();
    if (warp >= 9) {
        const int wg = warp - 9;
        bf16* dst = g_u + ((fc + wg) * D_ + d0) * 64;
        bf16* dst2 = tb ? g_u + ((fc + 2) * D_ + 480 + wg * 48) * 64 : dst + 96 * 64;
        #pragma unroll
        for (int pc = 0; pc < 4; pc++) {
            bar_sync(4 + wg * 4 + pc, 160);
            if (lane == 0) {
                bulk_s2g(pc < 2 ? dst + pc * (48 * 64) : dst2 + (pc - 2) * (32 * 64), sm + wg * 8192 + pc * K3_STAGE, pc < 2 ? 6144 : (pc == 3 && tb) ? 2048 : 4096);
                bulk_commit();
            }
            __syncwarp();
        }
        if (lane == 0) { bulk_wait_read(); TL(3, 6 + wg); }
    } else if (warp == 8) {
        if (tid == 256) {
            pdl_wait();
            pdl_trigger();
            TL(3, 1);
            const bf16* hs = g_hnT + d0 * 64;
            #pragma unroll
            for (int i = 0; i < K3_STAGES; i++) {
                bulk_g2s(sm + i * K3_STAGE + abytes, hs + i * (D_ * 64), K3_STAGE - abytes, bFull + i * 8);
                if (i >= K3_PRE) tma3d(sm + i * K3_STAGE, tm, bFull + i * 8, 0, i * 64, fc);
            }
            int s = 0; uint32_t ph = 0;
            #pragma unroll 1
            for (int i = K3_STAGES; i < 32; i++) {
                mbar_wait(bEmpty + s * 8, ph);
                mbar_expect(bFull + s * 8, K3_STAGE);
                tma3d(sm + s * K3_STAGE, tm, bFull + s * 8, 0, i * 64, fc);
                bulk_g2s(sm + s * K3_STAGE + abytes, hs + i * (D_ * 64), K3_STAGE - abytes, bFull + s * 8);
                if (i == 18 && blockIdx.x < 128) l2_prefetch(w1 + (size_t)(2048 - 64 * PFT) * F_ + blockIdx.x * (2304 * PFT), 4608 * PFT);
                if (++s == K3_STAGES) { s = 0; ph ^= 1; }
            }
            if (blockIdx.x < 128) l2_prefetch(w2 + (size_t)(blockIdx.x & 1) * (2304 * S_) + (blockIdx.x >> 1) * (W2HEAD * 2048), W2HEAD * 4096);
        }
    } else {
        const int wg = warp >> 2, w4 = warp & 3, gq = lane >> 2, tw = tid & 127;
        const int f0 = (fc + wg) * 64 + w4 * 16 + gq;
        const float bias0 = 0.5f * __bfloat162float(b1[f0]), bias1 = 0.5f * __bfloat162float(b1[f0 + 8]);
        const int ch = 2 * w4 + ((lane >> 3) & 1);
        const uint32_t lo = ((lane >> 4) * 8 + (lane & 7)) * 128 + ((ch ^ (lane & 7)) << 4);
        const uint32_t st = sm + wg * 8192;
        const uint64_t da0 = mkdesc(st, 8192, 1024, 1);
        int s = 0, ps = 0; uint32_t ph = 0;
        if (!tb) {
            float acc[80];
            #pragma unroll
            for (int j = 0; j < 80; j++) acc[j] = (j & 2) ? bias1 : bias0;
            reg_fence<80>(acc);
            const uint64_t db0 = mkdesc(sm + 16384, 16, 1024, 1);
            CK0();
            #pragma unroll 1
            for (int i = 0; i < 32 - K3_STAG; i++) {
                mbar_wait(bFull + s * 8, ph);
                const uint64_t da = dadv(da0, s * K3_STAGE), db = dadv(db0, s * K3_STAGE);
                wg_fence();
                #pragma unroll
                for (int kk = 0; kk < 4; kk++)
                    wgmma_n160<1, 0>(acc, dadv(da, kk * 2048), dadv(db, kk * 32), 1);
                wg_commit();
                wg_wait<1>();
                if (i > 0 && lane == 0) mbar_arrive(bEmpty + ps * 8);
                ps = s;
                if (++s == K3_STAGES) { s = 0; ph ^= 1; }
            }
            if (tid == 0) CK1(3);
            if (wg == 1) {
                wg_wait<0>();
                if (lane == 0) mbar_arrive(bEmpty + ps * 8);
                #pragma unroll
                for (int i = 32 - K3_STAG; i < 32; i++) mbar_wait(bFull + (i % K3_STAGES) * 8, (i / K3_STAGES) & 1);
                bar_sync(3, 256);
            }
            #pragma unroll
            for (int i = 32 - K3_STAG; i < 32; i++) {
                if (wg == 0) mbar_wait(bFull + (i % K3_STAGES) * 8, (i / K3_STAGES) & 1);
                wg_fence();
                #pragma unroll
                for (int kk = 0; kk < 4; kk++)
                    wgmma_n160<1, 0>(acc, dadv(da0, (i % K3_STAGES) * K3_STAGE + kk * 2048), dadv(db0, (i % K3_STAGES) * K3_STAGE + kk * 32), 1);
                wg_commit();
                if (i == 32 - K3_STAG && wg == 0) { wg_wait<1>(); if (lane == 0) mbar_arrive(bEmpty + ps * 8); }
            }
            if (wg == 0) bar_arrive(3, 256);
            wg_wait<0>();
            reg_fence<80>(acc);
            if (tw == 0) TL(3, 4 + wg);
            bar_sync(1 + wg, 128);
            k3_store<48, 0>(acc, st, lo, 4 + wg * 4);
            k3_store<48, 24>(acc, st + K3_STAGE, lo, 5 + wg * 4);
            k3_store<32, 48>(acc, st + 2 * K3_STAGE, lo, 6 + wg * 4);
            k3_store<32, 64>(acc, st + 3 * K3_STAGE, lo, 7 + wg * 4);
        } else {
            k3_typeb(sm, fc, lo, bias0, bias1, b1);
        }
    }
}

#define K4A0 1
#define K4_PD 4
#define K4STAG 3
constexpr int K4_STAGES = 5, K4_STAGE = 8192 + 36864, K4_STAG = K4STAG, K4_BAR = K4_STAGES * K4_STAGE, K4_SMEM = K4_BAR + 256;
constexpr int K4_XS = (36 - K4_STAG - 1) % K4_STAGES;
__global__ void __cluster_dims__(2, 1, 1) __launch_bounds__(288, 1) k4_mix2(const __grid_constant__ CUtensorMap tmW2, const __grid_constant__ CUtensorMap tmOut) {
    extern __shared__ __align__(1024) char smem[];
    const uint32_t sm = smem_u32(smem);
    const uint32_t bFull = sm + K4_BAR, bEmpty = bFull + K4_STAGES * 8, bP = bEmpty + K4_STAGES * 8, bRdy = bP + 16, bH = bRdy + 8;
    const int tid = threadIdx.x, lane = tid & 31, warp = __shfl_sync(~0u, tid >> 5, 0);
    const int ks = blockIdx.x & 1, tm = (blockIdx.x >> 1) & 31, tn = blockIdx.x >> 6;
    const int k0 = ks * 36;
    if (tid == 256) {
        TL(4, 0);
        #pragma unroll
        for (int i = 0; i < K4_STAGES; i++) { mbar_init(bFull + i * 8, 1); mbar_init(bEmpty + i * 8, 8); }
        mbar_init(bP, 1); mbar_init(bP + 8, 1); mbar_init(bRdy, 8); mbar_init(bH, 1);
        fence_mbar_init();
        #pragma unroll
        for (int i = 0; i < K4A0; i++) tma3d(sm + i * K4_STAGE, &tmW2, bFull + i * 8, 0, (k0 + i) * 64, tm);
    }
    __syncthreads();
    cluster_arrive_relaxed();
    if (tid == 0) {
        #pragma unroll
        for (int i = K4A0; i < K4_STAGES; i++) tma3d(sm + i * K4_STAGE, &tmW2, bFull + i * 8, 0, (k0 + i) * 64, tm);
    }
    if (tid == 32) {
        #pragma unroll
        for (int i = 0; i < K4_STAGES; i++) mbar_expect(bFull + i * 8, K4_STAGE);
    }
    if (tid == 128) { mbar_expect(bP, 9216); mbar_expect(bP + 8, 9216); prefetch_tm(&tmOut); }
    __syncwarp();
    if (warp == 8) {
        if (lane == 0) {
            pdl_wait();
            TL(4, 1);
            const bf16* us = g_u + ((size_t)k0 * D_ + tn * 288) * 64;
            #pragma unroll
            for (int i = 0; i < K4_STAGES; i++) {
                bulk_g2s(sm + i * K4_STAGE + 8192, us + (size_t)i * (D_ * 64), 36864, bFull + i * 8);
            }
            int s = 0; uint32_t ph = 0;
            #pragma unroll 1
            for (int i = K4_STAGES; i < 36; i++) {
                mbar_wait(bEmpty + s * 8, ph);
                mbar_expect(bFull + s * 8, K4_STAGE);
                tma3d(sm + s * K4_STAGE, &tmW2, bFull + s * 8, 0, (k0 + i) * 64, tm);
                if (i + K4_PD < 36 && ((i ^ tn) & 1)) tma3d_prefetch(&tmW2, 0, (k0 + i + K4_PD) * 64, tm);
                bulk_g2s(sm + s * K4_STAGE + 8192, us + (size_t)i * (D_ * 64), 36864, bFull + s * 8);
                if (++s == K4_STAGES) { s = 0; ph ^= 1; }
            }
            static_assert(K4_STAG <= 3, "stage of step 31 is free");
            mbar_wait(bEmpty + s * 8, ph);
            mbar_expect(bH, 18432);
            bulk_g2s(sm + (31 % K4_STAGES) * K4_STAGE, g_hnT + (tm * D_ + tn * 288 + ks * 144) * 64, 18432, bH);
        }
        __syncwarp();
        cluster_wait();
        #pragma unroll
        for (int hh = 0; hh < 2; hh++) {
            bar_sync(4 + hh, 160);
            if (lane == 0) {
                tma2d_store(&tmOut, sm + K4_XS * K4_STAGE + 24576 + hh * 9216, tn * 288 + ks * 144 + hh * 72, tm * 64);
                bulk_commit();
            }
            __syncwarp();
        }
        if (lane == 0) { bulk_wait_read(); TL(4, 7); }
    } else {
        const int wg = warp >> 2, w4 = warp & 3, tw = tid & 127;
        const bool keep = wg == ks;
        float acc[72];
        const uint64_t da0 = mkdesc(sm, 8192, 1024, 1), db0 = mkdesc(sm + 8192 + wg * 18432, 16, 1024, 1);
        const uint32_t rdy = mapa(bRdy, ks ^ 1);
        cluster_wait();
        CK0();
        int s = 0, ps = 0; uint32_t ph = 0;
        #pragma unroll 1
        for (int i = 0; i < 36 - K4_STAG; i++) {
            mbar_wait(bFull + s * 8, ph);
            const uint64_t da = dadv(da0, s * K4_STAGE), db = dadv(db0, s * K4_STAGE);
            wg_fence();
            #pragma unroll
            for (int kk = 0; kk < 4; kk++)
                wgmma_n144<1, 0>(acc, dadv(da, kk * 2048), dadv(db, kk * 32), (i | kk) != 0);
            wg_commit();
            wg_wait<1>();
            if (i > 0 && lane == 0) mbar_arrive(bEmpty + ps * 8);
            ps = s;
            if (++s == K4_STAGES) { s = 0; ph ^= 1; }
        }
        if (tid == 0) CK1(4);
        const uint32_t xa = sm + K4_XS * K4_STAGE + tw * 16;
        if (!keep) {
            #pragma unroll
            for (int i = 36 - K4_STAG; i < 36; i++) {
                mbar_wait(bFull + (i % K4_STAGES) * 8, (i / K4_STAGES) & 1);
                wg_fence();
                #pragma unroll
                for (int kk = 0; kk < 4; kk++)
                    wgmma_n144<1, 0>(acc, dadv(da0, (i % K4_STAGES) * K4_STAGE + kk * 2048), dadv(db0, (i % K4_STAGES) * K4_STAGE + kk * 32), 1);
                wg_commit();
                if (i == 36 - K4_STAG) { wg_wait<1>(); if (lane == 0) mbar_arrive_remote(rdy); }
            }
            bar_arrive(3, 256);
            mbar_wait(bRdy, 0);
            wg_wait<0>();
            reg_fence<72>(acc);
            if (tw == 0) TL(4, 2);
            const uint32_t rd = mapa(xa, ks ^ 1), rb = mapa(bP, ks ^ 1);
            #pragma unroll
            for (int hh = 0; hh < 2; hh++) {
                const float* q = acc + hh * 36;
                #pragma unroll
                for (int j = 0; j < 4; j++)
                    asm volatile("st.async.shared::cluster.mbarrier::complete_tx::bytes.v4.b32 [%0], {%1,%2,%3,%4}, [%5];"
                                 :: "r"(rd + hh * 10240 + j * 2048), "r"(pack2(q[8 * j], q[8 * j + 1])), "r"(pack2(q[8 * j + 2], q[8 * j + 3])),
                                    "r"(pack2(q[8 * j + 4], q[8 * j + 5])), "r"(pack2(q[8 * j + 6], q[8 * j + 7])), "r"(rb + hh * 8) : "memory");
                asm volatile("st.async.shared::cluster.mbarrier::complete_tx::bytes.v2.b32 [%0], {%1,%2}, [%3];"
                             :: "r"(rd + hh * 10240 + 8192), "r"(pack2(q[32], q[33])), "r"(pack2(q[34], q[35])), "r"(rb + hh * 8) : "memory");
            }
            if (tw == 0) TL(4, 3);
        } else {
            const uint2 rc0 = ldg64(g_rc + tm * 64 + w4 * 16 + (lane >> 2)), rc1 = ldg64(g_rc + tm * 64 + w4 * 16 + (lane >> 2) + 8);
            wg_wait<0>();
            if (lane == 0) mbar_arrive_remote(rdy);
            #pragma unroll
            for (int i = 36 - K4_STAG; i < 36; i++) mbar_wait(bFull + (i % K4_STAGES) * 8, (i / K4_STAGES) & 1);
            bar_sync(3, 256);
            wg_fence();
            #pragma unroll
            for (int i = 36 - K4_STAG; i < 36; i++)
                #pragma unroll
                for (int kk = 0; kk < 4; kk++)
                    wgmma_n144<1, 0>(acc, dadv(da0, (i % K4_STAGES) * K4_STAGE + kk * 2048), dadv(db0, (i % K4_STAGES) * K4_STAGE + kk * 32), 1);
            wg_commit();
            uint32_t hp[36];
            mbar_wait(bH, 0);
            {
                const int ch = 2 * w4 + ((lane >> 3) & 1);
                const uint32_t ha = sm + (31 % K4_STAGES) * K4_STAGE + ((lane >> 4) * 8 + (lane & 7)) * 128 + ((ch ^ (lane & 7)) << 4);
                #pragma unroll
                for (int j = 0; j < 9; j++) ldsm4t(ha + j * 2048, hp[4 * j], hp[4 * j + 1], hp[4 * j + 2], hp[4 * j + 3]);
            }
            wg_wait<0>();
            reg_fence<72>(acc);
            if (tw == 0) TL(4, 4);
            const uint32_t st = sm + K4_XS * K4_STAGE + 24576;
            const uint32_t ad = st + (w4 * 16 + ((lane >> 3) & 1) * 8 + (lane & 7)) * 144;
            #pragma unroll
            for (int hh = 0; hh < 2; hh++) {
                mbar_wait(bP + hh * 8, 0);
                if (tw == 0 && hh == 1) TL(4, 5);
                uint32_t o[18];
                #pragma unroll
                for (int j = 0; j < 4; j++) { const uint4 v = lds128(xa + hh * 10240 + j * 2048); o[4 * j] = v.x; o[4 * j + 1] = v.y; o[4 * j + 2] = v.z; o[4 * j + 3] = v.w; }
                { const uint2 v = lds64(xa + hh * 10240 + 8192); o[16] = v.x; o[17] = v.y; }
                #pragma unroll
                for (int j = 0; j < 18; j++) {
                    const float is = __uint_as_float((j & 1) ? rc1.x : rc0.x), of = __uint_as_float((j & 1) ? rc1.y : rc0.y);
                    o[j] = pack2(fmaf(bf_lo(hp[hh * 18 + j]), is, acc[hh * 36 + 2 * j] + of) + bf_lo(o[j]), fmaf(bf_hi(hp[hh * 18 + j]), is, acc[hh * 36 + 2 * j + 1] + of) + bf_hi(o[j]));
                }
                #pragma unroll
                for (int j = 0; j < 4; j++) stsm4(ad + hh * 9216 + (lane >> 4) * 16 + j * 32, o[4 * j], o[4 * j + 1], o[4 * j + 2], o[4 * j + 3]);
                stsm2(ad + hh * 9216 + 128, o[16], o[17]);
                fence_async_smem();
                bar_arrive(4 + hh, 160);
            }
        }
    }
}

typedef CUresult (*EncFn)(CUtensorMap*, CUtensorMapDataType, cuuint32_t, void*, const cuuint64_t*, const cuuint64_t*, const cuuint32_t*,
                          const cuuint32_t*, CUtensorMapInterleave, CUtensorMapSwizzle, CUtensorMapL2promotion, CUtensorMapFloatOOBfill);

template <typename... KArgs, typename... Args>
static void launch(void (*kern)(KArgs...), dim3 grid, int block, int smem, bool pdl, Args... args) {
    cudaLaunchConfig_t cfg = {};
    cfg.gridDim = grid; cfg.blockDim = dim3(block); cfg.dynamicSmemBytes = smem; cfg.stream = cudaStreamPerThread;
    cudaLaunchAttribute at[1];
    at[0].id = cudaLaunchAttributeProgrammaticStreamSerialization; at[0].val.programmaticStreamSerializationAllowed = 1;
    cfg.attrs = at; cfg.numAttrs = pdl ? 1 : 0;
    cudaLaunchKernelEx(&cfg, kern, args...);
}

extern "C" void kernel_launch(void* const* d_in, const int* in_sizes, int n_in, void* d_out, int out_size) {
    const bf16* x = (const bf16*)d_in[0];
    const bf16* wqkv = (const bf16*)d_in[1];
    const bf16* wphi = (const bf16*)d_in[2];
    const bf16* wo = (const bf16*)d_in[3];
    const bf16* w1 = (const bf16*)d_in[5];
    const bf16* b1 = (const bf16*)d_in[6];
    const bf16* w2 = (const bf16*)d_in[7];
    const bf16* b2 = (const bf16*)d_in[8];
    static EncFn enc = nullptr;
    if (!enc) {
        void* fn = nullptr; cudaDriverEntryPointQueryResult qr;
        cudaGetDriverEntryPoint("cuTensorMapEncodeTiled", &fn, cudaEnableDefault, &qr);
        enc = (EncFn)fn;
        cudaFuncSetAttribute(ka_front, cudaFuncAttributeMaxDynamicSharedMemorySize, KA_SMEM);
        cudaFuncSetAttribute(k2_attn, cudaFuncAttributeMaxDynamicSharedMemorySize, K2_SMEM);
        cudaFuncSetAttribute(k3_mix1, cudaFuncAttributeMaxDynamicSharedMemorySize, K3_SMEM);
        cudaFuncSetAttribute(k4_mix2, cudaFuncAttributeMaxDynamicSharedMemorySize, K4_SMEM);
    }
    CUtensorMap tmW1, tmW1b, tmW2, tmOut, tmX, tmXA;
    const cuuint32_t es[3] = {1, 1, 1};
    {
        cuuint64_t dims[3] = {64, (cuuint64_t)S_, (cuuint64_t)(F_ / 64)}; cuuint64_t st[2] = {(cuuint64_t)F_ * 2, 128}; cuuint32_t box[3] = {64, 64, 2};
        enc(&tmW1, CU_TENSOR_MAP_DATA_TYPE_BFLOAT16, 3, (void*)w1, dims, st, box, es, CU_TENSOR_MAP_INTERLEAVE_NONE, CU_TENSOR_MAP_SWIZZLE_128B, CU_TENSOR_MAP_L2_PROMOTION_L2_128B, CU_TENSOR_MAP_FLOAT_OOB_FILL_NONE);
        box[2] = 3;
        enc(&tmW1b, CU_TENSOR_MAP_DATA_TYPE_BFLOAT16, 3, (void*)w1, dims, st, box, es, CU_TENSOR_MAP_INTERLEAVE_NONE, CU_TENSOR_MAP_SWIZZLE_128B, CU_TENSOR_MAP_L2_PROMOTION_L2_128B, CU_TENSOR_MAP_FLOAT_OOB_FILL_NONE);
    }
    {
        cuuint64_t dims[3] = {64, (cuuint64_t)F_, (cuuint64_t)(S_ / 64)}; cuuint64_t st[2] = {(cuuint64_t)S_ * 2, 128}; cuuint32_t box[3] = {64, 64, 1};
        enc(&tmW2, CU_TENSOR_MAP_DATA_TYPE_BFLOAT16, 3, (void*)w2, dims, st, box, es, CU_TENSOR_MAP_INTERLEAVE_NONE, CU_TENSOR_MAP_SWIZZLE_128B, CU_TENSOR_MAP_L2_PROMOTION_L2_128B, CU_TENSOR_MAP_FLOAT_OOB_FILL_NONE);
    }
    {
        cuuint64_t dims[2] = {(cuuint64_t)D_, (cuuint64_t)S_}; cuuint64_t st[1] = {(cuuint64_t)D_ * 2}; cuuint32_t box[2] = {72, 64};
        enc(&tmOut, CU_TENSOR_MAP_DATA_TYPE_BFLOAT16, 2, d_out, dims, st, box, es, CU_TENSOR_MAP_INTERLEAVE_NONE, CU_TENSOR_MAP_SWIZZLE_NONE, CU_TENSOR_MAP_L2_PROMOTION_NONE, CU_TENSOR_MAP_FLOAT_OOB_FILL_NONE);
        enc(&tmX, CU_TENSOR_MAP_DATA_TYPE_BFLOAT16, 2, (void*)x, dims, st, box, es, CU_TENSOR_MAP_INTERLEAVE_NONE, CU_TENSOR_MAP_SWIZZLE_NONE, CU_TENSOR_MAP_L2_PROMOTION_NONE, CU_TENSOR_MAP_FLOAT_OOB_FILL_NONE);
    }
    {
        cuuint64_t dims[3] = {64, (cuuint64_t)S_, 9}; cuuint64_t st[2] = {(cuuint64_t)D_ * 2, 128}; cuuint32_t box[3] = {64, 128, 1};
        enc(&tmXA, CU_TENSOR_MAP_DATA_TYPE_BFLOAT16, 3, (void*)x, dims, st, box, es, CU_TENSOR_MAP_INTERLEAVE_NONE, CU_TENSOR_MAP_SWIZZLE_128B, CU_TENSOR_MAP_L2_PROMOTION_L2_128B, CU_TENSOR_MAP_FLOAT_OOB_FILL_NONE);
    }
    launch(k0_prep, dim3(9, 8, 4), 256, 0, false, x, wqkv, wphi);
        launch(ka_front, 132, 640, KA_SMEM, true, tmXA, x, wo, w1);
    launch(k2_attn, 128, 256, K2_SMEM, true, tmX, b2);
    launch(k3_mix1, 132, 352, K3_SMEM, true, tmW1, tmW1b, b1, w1, w2);
        launch(k4_mix2, 128, 288, K4_SMEM, true, tmW2, tmOut);
}
```

```cpp
#include <cuda_runtime.h>
#include <cuda.h>
#include <cuda_bf16.h>
#include <stdint.h>

typedef __nv_bfloat16 bf16;
#define DEVI __device__ __forceinline__

constexpr int S_ = 2048, D_ = 576, F_ = 4608;
constexpr float LN_EPS = 1e-5f;
constexpr float LOG2E = 1.4426950408889634f;

__device__ __align__(1024) bf16 g_o[S_ * D_];
__device__ __align__(1024) bf16 g_wqkv[8 * 27 * 72 * 64];
__device__ __align__(16) float g_cs[8 * 18 * 216];
__device__ __align__(1024) bf16 g_wo[8 * 72 * 72 * 8];
constexpr int KV_H = 960;
constexpr int PQ_UNIT = 1168;
__device__ __align__(1024) float g_kv[32 * KV_H];
__device__ __align__(1024) unsigned long long g_stats[S_ * 8];
__device__ __align__(16) unsigned long long g_ln[S_];
__device__ __align__(16) float2 g_rc[S_];
__device__ __align__(1024) bf16 g_hnT[D_ * S_];
__device__ __align__(1024) bf16 g_u[D_ * F_];
constexpr int CNT_S = 64;
__device__ __align__(256) unsigned int g_cnt[8 * CNT_S];
#define TL(k, i)
#define CK0()
#define CK1(k)

DEVI uint32_t smem_u32(const void* p) { return (uint32_t)__cvta_generic_to_shared(p); }
DEVI void mbar_init(uint32_t bar, int cnt) { asm volatile("mbarrier.init.shared::cta.b64 [%0], %1;" :: "r"(bar), "r"(cnt) : "memory"); }
DEVI void mbar_expect(uint32_t bar, uint32_t bytes) { asm volatile("mbarrier.arrive.expect_tx.shared::cta.b64 _, [%0], %1;" :: "r"(bar), "r"(bytes) : "memory"); }
DEVI void mbar_wait(uint32_t bar, uint32_t parity) {
    asm volatile("{\n.reg .pred p;\n.reg .u32 it;\n"
                 "mbarrier.try_wait.parity.shared::cta.b64 p, [%0], %1;\n@p bra MW_DONE;\n"
                 "mov.u32 it, 0;\n"
                 "MW_LOOP:\nmbarrier.try_wait.parity.shared::cta.b64 p, [%0], %1;\n@p bra MW_DONE;\n"
                 "add.u32 it, it, 1;\nsetp.lt.u32 p, it, 4194304;\n@p bra MW_LOOP;\ntrap;\n"
                 "MW_DONE:\n}" :: "r"(bar), "r"(parity) : "memory");
}
DEVI void mbar_arrive(uint32_t bar) { asm volatile("mbarrier.arrive.shared::cta.b64 _, [%0];" :: "r"(bar) : "memory"); }
DEVI uint32_t mapa(uint32_t addr, uint32_t cta) { uint32_t r; asm volatile("mapa.shared::cluster.u32 %0, %1, %2;" : "=r"(r) : "r"(addr), "r"(cta)); return r; }
DEVI void mbar_arrive_remote(uint32_t raddr) { asm volatile("mbarrier.arrive.shared::cluster.b64 _, [%0];" :: "r"(raddr) : "memory"); }
DEVI void fence_mbar_init() { asm volatile("fence.mbarrier_init.release.cluster;" ::: "memory"); }
DEVI void fence_async_smem() { asm volatile("fence.proxy.async.shared::cta;" ::: "memory"); }
DEVI void cluster_arrive_relaxed() { asm volatile("barrier.cluster.arrive.relaxed.aligned;" ::: "memory"); }
DEVI void cluster_wait() { asm volatile("barrier.cluster.wait.aligned;" ::: "memory"); }
DEVI void bar_sync(int id, int n) { asm volatile("bar.sync %0, %1;" :: "r"(id), "r"(n) : "memory"); }
DEVI void bar_arrive(int id, int n) { asm volatile("bar.arrive %0, %1;" :: "r"(id), "r"(n) : "memory"); }
DEVI void pdl_wait() { asm volatile("griddepcontrol.wait;" ::: "memory"); }
DEVI void pdl_trigger() { asm volatile("griddepcontrol.launch_dependents;" ::: "memory"); }
DEVI void bulk_g2s(uint32_t dst, const void* src, uint32_t bytes, uint32_t bar) {
    asm volatile("cp.async.bulk.shared::cluster.global.mbarrier::complete_tx::bytes [%0], [%1], %2, [%3];" :: "r"(dst), "l"(src), "r"(bytes), "r"(bar) : "memory");
}
DEVI void bulk_s2g(void* dst, uint32_t src, uint32_t bytes) {
    asm volatile("cp.async.bulk.global.shared::cta.bulk_group [%0], [%1], %2;" :: "l"(dst), "r"(src), "r"(bytes) : "memory");
}
DEVI void l2_prefetch(const void* p, uint32_t bytes) { asm volatile("cp.async.bulk.prefetch.L2.global [%0], %1;" :: "l"(p), "r"(bytes) : "memory"); }
DEVI void bulk_commit() { asm volatile("cp.async.bulk.commit_group;" ::: "memory"); }
DEVI void bulk_wait_read() { asm volatile("cp.async.bulk.wait_group.read 0;" ::: "memory"); }
DEVI void tma2d(uint32_t dst, const CUtensorMap* tm, uint32_t bar, int c0, int c1) {
    asm volatile("cp.async.bulk.tensor.2d.shared::cluster.global.mbarrier::complete_tx::bytes [%0], [%1, {%3, %4}], [%2];" :: "r"(dst), "l"(tm), "r"(bar), "r"(c0), "r"(c1) : "memory");
}
DEVI void tma3d(uint32_t dst, const CUtensorMap* tm, uint32_t bar, int c0, int c1, int c2) {
    asm volatile("cp.async.bulk.tensor.3d.shared::cluster.global.mbarrier::complete_tx::bytes [%0], [%1, {%3, %4, %5}], [%2];" :: "r"(dst), "l"(tm), "r"(bar), "r"(c0), "r"(c1), "r"(c2) : "memory");
}
DEVI void tma3d_prefetch(const CUtensorMap* tm, int c0, int c1, int c2) {
    asm volatile("cp.async.bulk.prefetch.tensor.3d.L2.global [%0, {%1, %2, %3}];" :: "l"(tm), "r"(c0), "r"(c1), "r"(c2) : "memory");
}
DEVI void tma2d_store(const CUtensorMap* tm, uint32_t src, int c0, int c1) {
    asm volatile("cp.async.bulk.tensor.2d.global.shared::cta.bulk_group [%0, {%2, %3}], [%1];" :: "l"(tm), "r"(src), "r"(c0), "r"(c1) : "memory");
}
DEVI void prefetch_tm(const CUtensorMap* tm) { asm volatile("prefetch.tensormap [%0];" :: "l"(tm) : "memory"); }
DEVI uint64_t mkdesc(uint32_t addr, uint32_t lbo, uint32_t sbo, uint64_t swz) {
    return (uint64_t)((addr & 0x3FFFF) >> 4) | ((uint64_t)(lbo >> 4) << 16) | ((uint64_t)(sbo >> 4) << 32) | (swz << 62);
}
DEVI uint64_t dadv(uint64_t d, uint32_t bytes) { return (d & 0xffffffff00000000ull) | (uint64_t)((uint32_t)d + (bytes >> 4)); }
DEVI void wg_fence() { asm volatile("wgmma.fence.sync.aligned;" ::: "memory"); }
DEVI void wg_commit() { asm volatile("wgmma.commit_group.sync.aligned;" ::: "memory"); }
template<int N> DEVI void wg_wait() { asm volatile("wgmma.wait_group.sync.aligned %0;" :: "n"(N) : "memory"); }
template<int N> DEVI void reg_fence(float* d) {
    #pragma unroll
    for (int i = 0; i < N; i++) asm volatile("" : "+f"(d[i]) :: "memory");
}
DEVI uint32_t pack2(float lo, float hi) { uint32_t r; asm("cvt.rn.bf16x2.f32 %0, %1, %2;" : "=r"(r) : "f"(hi), "f"(lo)); return r; }
DEVI float bf_lo(uint32_t v) { return __uint_as_float(v << 16); }
DEVI float bf_hi(uint32_t v) { return __uint_as_float(v & 0xffff0000u); }
DEVI float ex2(float x) { float r; asm("ex2.approx.ftz.f32 %0, %1;" : "=f"(r) : "f"(x)); return r; }
DEVI float rcp(float x) { float r; asm("rcp.approx.ftz.f32 %0, %1;" : "=f"(r) : "f"(x)); return r; }
DEVI float rcp_full(float x) { float r; asm("rcp.approx.f32 %0, %1;" : "=f"(r) : "f"(x)); return r; }
DEVI float tanh_fast(float x) { float r; asm("tanh.approx.f32 %0, %1;" : "=f"(r) : "f"(x)); return r; }
DEVI void mma16816(float* c, uint32_t a0, uint32_t a1, uint32_t a2, uint32_t a3, uint32_t b0, uint32_t b1) {
    asm("mma.sync.aligned.m16n8k16.row.col.f32.bf16.bf16.f32 {%0,%1,%2,%3}, {%4,%5,%6,%7}, {%8,%9}, {%0,%1,%2,%3};"
        : "+f"(c[0]), "+f"(c[1]), "+f"(c[2]), "+f"(c[3]) : "r"(a0), "r"(a1), "r"(a2), "r"(a3), "r"(b0), "r"(b1));
}
DEVI void mma1688(float* c, uint32_t a0, uint32_t a1, uint32_t b0) {
    asm("mma.sync.aligned.m16n8k8.row.col.f32.bf16.bf16.f32 {%0,%1,%2,%3}, {%4,%5}, {%6}, {%0,%1,%2,%3};"
        : "+f"(c[0]), "+f"(c[1]), "+f"(c[2]), "+f"(c[3]) : "r"(a0), "r"(a1), "r"(b0));
}
DEVI void ldsm4t(uint32_t addr, uint32_t& r0, uint32_t& r1, uint32_t& r2, uint32_t& r3) {
    asm volatile("ldmatrix.sync.aligned.m8n8.x4.trans.shared.b16 {%0,%1,%2,%3}, [%4];" : "=r"(r0), "=r"(r1), "=r"(r2), "=r"(r3) : "r"(addr) : "memory");
}
DEVI void stsm4t(uint32_t addr, uint32_t r0, uint32_t r1, uint32_t r2, uint32_t r3) {
    asm volatile("stmatrix.sync.aligned.m8n8.x4.trans.shared.b16 [%0], {%1,%2,%3,%4};" :: "r"(addr), "r"(r0), "r"(r1), "r"(r2), "r"(r3) : "memory");
}
DEVI void stsm2t(uint32_t addr, uint32_t r0, uint32_t r1) {
    asm volatile("stmatrix.sync.aligned.m8n8.x2.trans.shared.b16 [%0], {%1,%2};" :: "r"(addr), "r"(r0), "r"(r1) : "memory");
}
DEVI void stsm4(uint32_t addr, uint32_t r0, uint32_t r1, uint32_t r2, uint32_t r3) {
    asm volatile("stmatrix.sync.aligned.m8n8.x4.shared.b16 [%0], {%1,%2,%3,%4};" :: "r"(addr), "r"(r0), "r"(r1), "r"(r2), "r"(r3) : "memory");
}
DEVI void stsm2(uint32_t addr, uint32_t r0, uint32_t r1) {
    asm volatile("stmatrix.sync.aligned.m8n8.x2.shared.b16 [%0], {%1,%2};" :: "r"(addr), "r"(r0), "r"(r1) : "memory");
}
DEVI void sts128(uint32_t addr, uint32_t r0, uint32_t r1, uint32_t r2, uint32_t r3) {
    asm volatile("st.shared.v4.b32 [%0], {%1,%2,%3,%4};" :: "r"(addr), "r"(r0), "r"(r1), "r"(r2), "r"(r3) : "memory");
}
DEVI uint32_t lds32(uint32_t addr) { uint32_t r; asm volatile("ld.shared.b32 %0, [%1];" : "=r"(r) : "r"(addr) : "memory"); return r; }
DEVI void sts32(uint32_t addr, uint32_t r0) { asm volatile("st.shared.b32 [%0], %1;" :: "r"(addr), "r"(r0) : "memory"); }
template<int TA, int TB> DEVI void wgmma_n40(float* d, uint64_t da, uint64_t db, int sd) {
  asm volatile("{\n.reg .pred p;\nsetp.ne.b32 p, %22, 0;\n"
    "wgmma.mma_async.sync.aligned.m64n40k16.f32.bf16.bf16 {%0, %1, %2, %3, %4, %5, %6, %7, %8, %9, %10, %11, %12, %13, %14, %15, %16, %17, %18, %19}, %20, %21, p, 1, 1, %23, %24;\n}\n"
    : "+f"(d[0]), "+f"(d[1]), "+f"(d[2]), "+f"(d[3]), "+f"(d[4]), "+f"(d[5]), "+f"(d[6]), "+f"(d[7]), "+f"(d[8]), "+f"(d[9]), "+f"(d[10]), "+f"(d[11]), "+f"(d[12]), "+f"(d[13]), "+f"(d[14]), "+f"(d[15]), "+f"(d[16]), "+f"(d[17]), "+f"(d[18]), "+f"(d[19]) : "l"(da), "l"(db), "r"(sd), "n"(TA), "n"(TB));
}
template<int TA, int TB> DEVI void wgmma_n48(float* d, uint64_t da, uint64_t db, int sd) {
  asm volatile("{\n.reg .pred p;\nsetp.ne.b32 p, %26, 0;\n"
    "wgmma.mma_async.sync.aligned.m64n48k16.f32.bf16.bf16 {%0, %1, %2, %3, %4, %5, %6, %7, %8, %9, %10, %11, %12, %13, %14, %15, %16, %17, %18, %19, %20, %21, %22, %23}, %24, %25, p, 1, 1, %27, %28;\n}\n"
    : "+f"(d[0]), "+f"(d[1]), "+f"(d[2]), "+f"(d[3]), "+f"(d[4]), "+f"(d[5]), "+f"(d[6]), "+f"(d[7]), "+f"(d[8]), "+f"(d[9]), "+f"(d[10]), "+f"(d[11]), "+f"(d[12]), "+f"(d[13]), "+f"(d[14]), "+f"(d[15]), "+f"(d[16]), "+f"(d[17]), "+f"(d[18]), "+f"(d[19]), "+f"(d[20]), "+f"(d[21]), "+f"(d[22]), "+f"(d[23]) : "l"(da), "l"(db), "r"(sd), "n"(TA), "n"(TB));
}
template<int TA, int TB> DEVI void wgmma_n72(float* d, uint64_t da, uint64_t db, int sd) {
  asm volatile("{\n.reg .pred p;\nsetp.ne.b32 p, %38, 0;\n"
    "wgmma.mma_async.sync.aligned.m64n72k16.f32.bf16.bf16 {%0, %1, %2, %3, %4, %5, %6, %7, %8, %9, %10, %11, %12, %13, %14, %15, %16, %17, %18, %19, %20, %21, %22, %23, %24, %25, %26, %27, %28, %29, %30, %31, %32, %33, %34, %35}, %36, %37, p, 1, 1, %39, %40;\n}\n"
    : "+f"(d[0]), "+f"(d[1]), "+f"(d[2]), "+f"(d[3]), "+f"(d[4]), "+f"(d[5]), "+f"(d[6]), "+f"(d[7]), "+f"(d[8]), "+f"(d[9]), "+f"(d[10]), "+f"(d[11]), "+f"(d[12]), "+f"(d[13]), "+f"(d[14]), "+f"(d[15]), "+f"(d[16]), "+f"(d[17]), "+f"(d[18]), "+f"(d[19]), "+f"(d[20]), "+f"(d[21]), "+f"(d[22]), "+f"(d[23]), "+f"(d[24]), "+f"(d[25]), "+f"(d[26]), "+f"(d[27]), "+f"(d[28]), "+f"(d[29]), "+f"(d[30]), "+f"(d[31]), "+f"(d[32]), "+f"(d[33]), "+f"(d[34]), "+f"(d[35]) : "l"(da), "l"(db), "r"(sd), "n"(TA), "n"(TB));
}
template<int TA, int TB> DEVI void wgmma_n96(float* d, uint64_t da, uint64_t db, int sd) {
  asm volatile("{\n.reg .pred p;\nsetp.ne.b32 p, %50, 0;\n"
    "wgmma.mma_async.sync.aligned.m64n96k16.f32.bf16.bf16 {%0, %1, %2, %3, %4, %5, %6, %7, %8, %9, %10, %11, %12, %13, %14, %15, %16, %17, %18, %19, %20, %21, %22, %23, %24, %25, %26, %27, %28, %29, %30, %31, %32, %33, %34, %35, %36, %37, %38, %39, %40, %41, %42, %43, %44, %45, %46, %47}, %48, %49, p, 1, 1, %51, %52;\n}\n"
    : "+f"(d[0]), "+f"(d[1]), "+f"(d[2]), "+f"(d[3]), "+f"(d[4]), "+f"(d[5]), "+f"(d[6]), "+f"(d[7]), "+f"(d[8]), "+f"(d[9]), "+f"(d[10]), "+f"(d[11]), "+f"(d[12]), "+f"(d[13]), "+f"(d[14]), "+f"(d[15]), "+f"(d[16]), "+f"(d[17]), "+f"(d[18]), "+f"(d[19]), "+f"(d[20]), "+f"(d[21]), "+f"(d[22]), "+f"(d[23]), "+f"(d[24]), "+f"(d[25]), "+f"(d[26]), "+f"(d[27]), "+f"(d[28]), "+f"(d[29]), "+f"(d[30]), "+f"(d[31]), "+f"(d[32]), "+f"(d[33]), "+f"(d[34]), "+f"(d[35]), "+f"(d[36]), "+f"(d[37]), "+f"(d[38]), "+f"(d[39]), "+f"(d[40]), "+f"(d[41]), "+f"(d[42]), "+f"(d[43]), "+f"(d[44]), "+f"(d[45]), "+f"(d[46]), "+f"(d[47]) : "l"(da), "l"(db), "r"(sd), "n"(TA), "n"(TB));
}
template<int TA, int TB> DEVI void wgmma_n144(float* d, uint64_t da, uint64_t db, int sd) {
  asm volatile("{\n.reg .pred p;\nsetp.ne.b32 p, %74, 0;\n"
    "wgmma.mma_async.sync.aligned.m64n144k16.f32.bf16.bf16 {%0, %1, %2, %3, %4, %5, %6, %7, %8, %9, %10, %11, %12, %13, %14, %15, %16, %17, %18, %19, %20, %21, %22, %23, %24, %25, %26, %27, %28, %29, %30, %31, %32, %33, %34, %35, %36, %37, %38, %39, %40, %41, %42, %43, %44, %45, %46, %47, %48, %49, %50, %51, %52, %53, %54, %55, %56, %57, %58, %59, %60, %61, %62, %63, %64, %65, %66, %67, %68, %69, %70, %71}, %72, %73, p, 1, 1, %75, %76;\n}\n"
    : "+f"(d[0]), "+f"(d[1]), "+f"(d[2]), "+f"(d[3]), "+f"(d[4]), "+f"(d[5]), "+f"(d[6]), "+f"(d[7]), "+f"(d[8]), "+f"(d[9]), "+f"(d[10]), "+f"(d[11]), "+f"(d[12]), "+f"(d[13]), "+f"(d[14]), "+f"(d[15]), "+f"(d[16]), "+f"(d[17]), "+f"(d[18]), "+f"(d[19]), "+f"(d[20]), "+f"(d[21]), "+f"(d[22]), "+f"(d[23]), "+f"(d[24]), "+f"(d[25]), "+f"(d[26]), "+f"(d[27]), "+f"(d[28]), "+f"(d[29]), "+f"(d[30]), "+f"(d[31]), "+f"(d[32]), "+f"(d[33]), "+f"(d[34]), "+f"(d[35]), "+f"(d[36]), "+f"(d[37]), "+f"(d[38]), "+f"(d[39]), "+f"(d[40]), "+f"(d[41]), "+f"(d[42]), "+f"(d[43]), "+f"(d[44]), "+f"(d[45]), "+f"(d[46]), "+f"(d[47]), "+f"(d[48]), "+f"(d[49]), "+f"(d[50]), "+f"(d[51]), "+f"(d[52]), "+f"(d[53]), "+f"(d[54]), "+f"(d[55]), "+f"(d[56]), "+f"(d[57]), "+f"(d[58]), "+f"(d[59]), "+f"(d[60]), "+f"(d[61]), "+f"(d[62]), "+f"(d[63]), "+f"(d[64]), "+f"(d[65]), "+f"(d[66]), "+f"(d[67]), "+f"(d[68]), "+f"(d[69]), "+f"(d[70]), "+f"(d[71]) : "l"(da), "l"(db), "r"(sd), "n"(TA), "n"(TB));
}
template<int TA, int TB> DEVI void wgmma_n160(float* d, uint64_t da, uint64_t db, int sd) {
  asm volatile("{\n.reg .pred p;\nsetp.ne.b32 p, %82, 0;\n"
    "wgmma.mma_async.sync.aligned.m64n160k16.f32.bf16.bf16 {%0, %1, %2, %3, %4, %5, %6, %7, %8, %9, %10, %11, %12, %13, %14, %15, %16, %17, %18, %19, %20, %21, %22, %23, %24, %25, %26, %27, %28, %29, %30, %31, %32, %33, %34, %35, %36, %37, %38, %39, %40, %41, %42, %43, %44, %45, %46, %47, %48, %49, %50, %51, %52, %53, %54, %55, %56, %57, %58, %59, %60, %61, %62, %63, %64, %65, %66, %67, %68, %69, %70, %71, %72, %73, %74, %75, %76, %77, %78, %79}, %80, %81, p, 1, 1, %83, %84;\n}\n"
    : "+f"(d[0]), "+f"(d[1]), "+f"(d[2]), "+f"(d[3]), "+f"(d[4]), "+f"(d[5]), "+f"(d[6]), "+f"(d[7]), "+f"(d[8]), "+f"(d[9]), "+f"(d[10]), "+f"(d[11]), "+f"(d[12]), "+f"(d[13]), "+f"(d[14]), "+f"(d[15]), "+f"(d[16]), "+f"(d[17]), "+f"(d[18]), "+f"(d[19]), "+f"(d[20]), "+f"(d[21]), "+f"(d[22]), "+f"(d[23]), "+f"(d[24]), "+f"(d[25]), "+f"(d[26]), "+f"(d[27]), "+f"(d[28]), "+f"(d[29]), "+f"(d[30]), "+f"(d[31]), "+f"(d[32]), "+f"(d[33]), "+f"(d[34]), "+f"(d[35]), "+f"(d[36]), "+f"(d[37]), "+f"(d[38]), "+f"(d[39]), "+f"(d[40]), "+f"(d[41]), "+f"(d[42]), "+f"(d[43]), "+f"(d[44]), "+f"(d[45]), "+f"(d[46]), "+f"(d[47]), "+f"(d[48]), "+f"(d[49]), "+f"(d[50]), "+f"(d[51]), "+f"(d[52]), "+f"(d[53]), "+f"(d[54]), "+f"(d[55]), "+f"(d[56]), "+f"(d[57]), "+f"(d[58]), "+f"(d[59]), "+f"(d[60]), "+f"(d[61]), "+f"(d[62]), "+f"(d[63]), "+f"(d[64]), "+f"(d[65]), "+f"(d[66]), "+f"(d[67]), "+f"(d[68]), "+f"(d[69]), "+f"(d[70]), "+f"(d[71]), "+f"(d[72]), "+f"(d[73]), "+f"(d[74]), "+f"(d[75]), "+f"(d[76]), "+f"(d[77]), "+f"(d[78]), "+f"(d[79]) : "l"(da), "l"(db), "r"(sd), "n"(TA), "n"(TB));
}

__host__ __device__ constexpr int ka_seq(int p, int c) { return p == 0 ? c : c >= 5 ? 2 * c - 2 + p : p == 1 ? 17 + c : 22 + c; }
__global__ void __launch_bounds__(256, 3) k0_prep(const bf16* __restrict__ x, const bf16* __restrict__ wqkv, const bf16* __restrict__ wphi) {
    __shared__ __align__(16) uint32_t s_in[64 * 36 + 64];
    pdl_trigger();
    if (threadIdx.x == 0) TL(0, 0);
    const int tid = threadIdx.x, lane = tid & 31, warp = __shfl_sync(~0u, tid >> 5, 0);
    const int c = blockIdx.x, g = blockIdx.y, p = blockIdx.z;
    const bool fold = p == 0 || p == 2;
    const int b = (p * 8 + g) * 9 + c;
    if (p == 3) {
        const int j = b - 216;
        const uint4 z = make_uint4(0u, 0u, 0u, 0u);
        if (j < 32) reinterpret_cast<uint4*>(g_stats)[j * 256 + tid] = z;
        else if (j < 62) reinterpret_cast<uint4*>(g_kv)[(j - 32) * 256 + tid] = z;
        else if (j == 66 && tid < 8) g_cnt[tid * CNT_S] = 0u;
        return;
    }
    constexpr int ld = 1728;
    const bf16* src = wqkv + ((p == 2 ? 0 : p + 1) * 576 + c * 64 * ld + g * 72);
    const uint32_t si = smem_u32(s_in);
    #pragma unroll
    for (int j = 0; j < 3; j++) {
        const int i = tid + j * 256, r = (i * 7282) >> 16;
        if (j < 2 || tid < 64) asm volatile("cp.async.cg.shared.global [%0], [%1], 16;" :: "r"(si + i * 16 + (r >> 3) * 32), "l"(src + (r * (ld - 72) + i * 8)) : "memory");
    }
    const int t = warp & 3, half = warp >> 2, g8 = lane >> 2, c4 = lane & 3;
    uint32_t af[3][3];
    if (fold) {
        const unsigned short* ph = reinterpret_cast<const unsigned short*>(wphi) + (g * 4 + t) * 324;
        unsigned short lo[3][3], hi[3][3];
        #pragma unroll
        for (int fb = 0; fb < 3; fb++)
            #pragma unroll
            for (int db = 0; db < 3; db++) {
                const int o = min(2 * c4 + 8 * db, 16) * 18 + min(g8 + 8 * fb, 17);
                lo[fb][db] = __ldg(ph + o); hi[fb][db] = __ldg(ph + o + 18);
            }
        #pragma unroll
        for (int fb = 0; fb < 3; fb++)
            #pragma unroll
            for (int db = 0; db < 3; db++) af[fb][db] = (uint32_t)lo[fb][db] | ((uint32_t)hi[fb][db] << 16);
    } else {
        const uint32_t v = (g8 == 2 * c4 ? 0x3f80u : 0u) | (g8 == 2 * c4 + 1 ? 0x3f800000u : 0u);
        #pragma unroll
        for (int fb = 0; fb < 3; fb++)
            #pragma unroll
            for (int db = 0; db < 3; db++) af[fb][db] = fb == db ? v : 0u;
    }
    if (threadIdx.x == 0) TL(0, 4);
    bf16* dst = g_wqkv + (g * 27 + ka_seq(p, c)) * 4608;
    float* csd = g_cs + (g * 18 + c * 2 + half) * 216 + p * 72 + 2 * t;
    asm volatile("cp.async.wait_all;" ::: "memory");
    if (threadIdx.x == 0) TL(0, 1);
    __syncthreads();
    if (tid < 96 && b < 192) asm volatile("prefetch.global.L2 [%0];" :: "l"(x + b * 6144 + tid * 64));
    uint32_t ov[3][4];
    const uint32_t* wr = &s_in[(half * 32 + (g8 >> 1) * 8 + (g8 & 1)) * 36 + (half * 4 + (g8 >> 1)) * 8 + t * 9 + c4];
    #pragma unroll
    for (int j = 0; j < 4; j++) {
        const uint32_t b0 = wr[j * 72], b1 = wr[j * 72 + 4], b2 = c4 == 0 ? wr[j * 72 + 8] : 0u;
        float c0[4] = {0.f, 0.f, 0.f, 0.f}, c1[4] = {0.f, 0.f, 0.f, 0.f};
        mma16816(c0, af[0][0], af[1][0], af[0][1], af[1][1], b0, b1);
        mma1688(c0, af[0][2], af[1][2], b2);
        mma16816(c1, af[2][0], 0u, af[2][1], 0u, b0, b1);
        mma1688(c1, af[2][2], 0u, b2);
        ov[0][j] = pack2(c0[0], c0[1]); ov[1][j] = pack2(c0[2], c0[3]); ov[2][j] = pack2(c1[0], c1[1]);
    }
    {
        const int nl = 2 * t + (g8 & 1);
        uint4* o = reinterpret_cast<uint4*>(dst) + ((g8 >> 1) * 8 + nl) * 8 + ((half * 4 + c4) ^ nl);
        o[0] = make_uint4(ov[0][0], ov[0][1], ov[0][2], ov[0][3]);
        o[256] = make_uint4(ov[1][0], ov[1][1], ov[1][2], ov[1][3]);
        if (g8 < 2) o[512] = make_uint4(ov[2][0], ov[2][1], ov[2][2], ov[2][3]);
    }
    if (threadIdx.x == 0) TL(0, 2);
    {
        float cs0[4] = {0.f, 0.f, 0.f, 0.f}, cs1[4] = {0.f, 0.f, 0.f, 0.f};
        mma16816(cs0, ov[0][0], ov[1][0], ov[0][1], ov[1][1], 0x3f803f80u, 0x3f803f80u);
        mma16816(cs1, ov[2][0], 0u, ov[2][1], 0u, 0x3f803f80u, 0x3f803f80u);
        mma16816(cs0, ov[0][2], ov[1][2], ov[0][3], ov[1][3], 0x3f803f80u, 0x3f803f80u);
        mma16816(cs1, ov[2][2], 0u, ov[2][3], 0u, 0x3f803f80u, 0x3f803f80u);
        const int f = g8 + 8 * c4;
        if (f < 18) csd[8 * (f >> 1) + (f & 1)] = c4 == 0 ? cs0[0] : c4 == 1 ? cs0[2] : cs1[0];
    }
    if (threadIdx.x == 0) TL(0, 3);
}

DEVI void dual_softmax(const float* a, float scale, uint32_t* o) {
    float mx = a[0], mn = a[0];
    #pragma unroll
    for (int j = 1; j < 18; j++) { mx = fmaxf(mx, a[j]); mn = fminf(mn, a[j]); }
    const float mxs = -mx * scale, mns = mn * scale;
    float ep[18], en[18], sp = 0.f, sn = 0.f;
    #pragma unroll
    for (int j = 0; j < 18; j++) {
        ep[j] = ex2(fmaf(a[j], scale, mxs)); sp += ep[j];
        en[j] = ex2(fmaf(a[j], -scale, mns)); sn += en[j];
    }
    const float rp = rcp(sp), rn = rcp(sn);
    #pragma unroll
    for (int j = 0; j < 9; j++) {
        o[j] = pack2(ep[2 * j] * rp, ep[2 * j + 1] * rp);
        o[9 + j] = pack2(en[2 * j] * rn, en[2 * j + 1] * rn);
    }
}

DEVI uint4 ldg128(const void* p) { uint4 v; asm volatile("ld.global.cg.v4.u32 {%0,%1,%2,%3}, [%4];" : "=r"(v.x), "=r"(v.y), "=r"(v.z), "=r"(v.w) : "l"(p)); return v; }
DEVI uint2 ldg64(const void* p) { uint2 v; asm volatile("ld.global.cg.v2.u32 {%0,%1}, [%2];" : "=r"(v.x), "=r"(v.y) : "l"(p)); return v; }
DEVI uint4 lds128(uint32_t a) { uint4 v; asm volatile("ld.shared.v4.u32 {%0,%1,%2,%3}, [%4];" : "=r"(v.x), "=r"(v.y), "=r"(v.z), "=r"(v.w) : "r"(a) : "memory"); return v; }
DEVI uint2 lds64(uint32_t a) { uint2 v; asm volatile("ld.shared.v2.u32 {%0,%1}, [%2];" : "=r"(v.x), "=r"(v.y) : "r"(a) : "memory"); return v; }
DEVI uint32_t packu(uint32_t lo, uint32_t hi) { return pack2(__uint_as_float(lo), __uint_as_float(hi)); }
DEVI void cp16(uint32_t dst, const void* src) { asm volatile("cp.async.cg.shared.global [%0], [%1], 16;" :: "r"(dst), "l"(src) : "memory"); }
DEVI void spin_ge(const unsigned int* p, unsigned int n) {
    uint32_t f; int it = 0;
    do {
        asm volatile("ld.acquire.gpu.global.u32 %0, [%1];" : "=r"(f) : "l"(p) : "memory");
        if (++it > (1 << 22)) __trap();
    } while (f < n);
}
constexpr int KA_PRE = 3, KA_REC = 5 * 16384, KA_B = 147456, KA_CS = KA_B + 9 * 9216, KA_LN = KA_CS + 864, KA_BAR = KA_LN + 1024, KA_SMEM = KA_BAR + 160;
static_assert(KA_SMEM <= 232448, "smem");
DEVI int gpc_pos() {
    unsigned smid, nsm;
    asm volatile("mov.u32 %0, %%smid;" : "=r"(smid));
    asm volatile("mov.u32 %0, %%nsmid;" : "=r"(nsm));
    if (nsm != 132) return blockIdx.x;
    const int tpc = smid >> 1, o = smid & 1;
    if (tpc < 32) return (tpc & 7) * 16 + (tpc >> 3) * 2 + o;
    if (tpc < 60) { const int j = tpc - 32, r = j / 7; return (1 + j - r * 7) * 16 + 8 + r * 2 + o; }
    if (tpc < 62) return 128 + (tpc - 60) * 2 + o;
    return 8 + (tpc - 62) * 2 + o;
}
__global__ void __launch_bounds__(640, 1) ka_front(const __grid_constant__ CUtensorMap tmXA, const bf16* __restrict__ x, const bf16* __restrict__ wo, const bf16* __restrict__ w1, const bf16* __restrict__ b1) {
    extern __shared__ __align__(1024) char smem[];
    const uint32_t sm = smem_u32(smem);
    const uint32_t bFull = sm + KA_BAR, bEmpty = bFull + 9 * 8, bLn = bEmpty + 9 * 8;
    const int tid = threadIdx.x, lane = tid & 31, warp = __shfl_sync(~0u, tid >> 5, 0);
    const int pos = gpc_pos();
    if (pos >= 128) {
        const int ns = pos - 128;
        if (tid < 576) {
            const int r0 = tid / 18, ch = tid - r0 * 18;
            #pragma unroll
            for (int j = 0; j < 18; j++) cp16(sm + (j * 32 + r0) * 304 + ch * 16, wo + (j * 32 + r0) * 576 + ns * 144 + ch * 8);
        }
        asm volatile("cp.async.wait_all;" ::: "memory");
        #pragma unroll 1
        for (int q = 0; q < 6; q++) {
            const uint32_t ob = sm + 175104 + (q & 1) * 27648;
            if (tid == 0) asm volatile("cp.async.bulk.wait_group.read 1;" ::: "memory");
            __syncthreads();
            if (warp < 18) {
                #pragma unroll
                for (int rb = 0; rb < 3; rb++) {
                    uint32_t r0, r1, r2, r3;
                    ldsm4t(sm + (q * 96 + rb * 32 + lane) * 304 + warp * 16, r0, r1, r2, r3);
                    stsm4(ob + (warp / 9) * 13824 + ((rb * 4 + (lane >> 3)) * 72 + (warp % 9) * 8 + (lane & 7)) * 16, r0, r1, r2, r3);
                }
            }
            fence_async_smem();
            __syncthreads();
            if (tid == 0) {
                bulk_s2g(g_wo + (ns * 2) * (72 * 576) + q * 6912, ob, 13824);
                bulk_s2g(g_wo + (ns * 2 + 1) * (72 * 576) + q * 6912, ob + 13824, 13824);
                bulk_commit();
            }
        }
        if (tid == 0) {
            asm volatile("cp.async.bulk.wait_group 0;\nfence.proxy.async.global;\nfence.acq_rel.gpu;" ::: "memory");
            pdl_wait();
            pdl_trigger();
        }
        return;
    }
    const int g = ((pos >> 4) & 1) * 4 + (pos & 3), mt = (pos >> 5) * 4 + ((pos >> 2) & 3);
    if (warp >= 16) {
        asm volatile("setmaxnreg.dec.sync.aligned.u32 32;");
        if (warp == 16) {
            if (lane == 0) {
                TL(1, 0);
                #pragma unroll
                for (int c = 0; c < 9; c++) { mbar_init(bFull + c * 8, 1); mbar_init(bEmpty + c * 8, 8); }
                mbar_init(bLn, 64);
                fence_mbar_init();
            }
            __syncwarp();
            bar_arrive(0, 640);
        } else {
            bar_sync(0, 640);
            if (tid == 544) {
                #pragma unroll
                for (int c = 0; c < 9; c++) mbar_expect(bFull + c * 8, 16384 + 9216);
            }
            __syncwarp();
        }
        if (tid == 512) {
            #pragma unroll
            for (int c = 0; c < KA_PRE; c++) tma3d(sm + c * 16384, &tmXA, bFull + c * 8, 0, mt * 128, c);
            pdl_wait();
            const bf16* wsrc = g_wqkv + g * (27 * 4608);
            const uint32_t sb = sm + KA_B;
            TL(1, 1);
            #pragma unroll
            for (int c = 0; c < 9; c++) {
                bulk_g2s(sb + c * 9216, wsrc + c * 4608, 9216, bFull + c * 8);
                const int xc = c + KA_PRE - 2;
                if (c >= 2 && xc < 9) tma3d(sm + xc * 16384, &tmXA, bFull + xc * 8, 0, mt * 128, xc);
            }
            pdl_trigger();
            #pragma unroll 1
            for (int p = 1; p < 3; p++) {
                #pragma unroll
                for (int c = 0; c < 9; c++) {
                    mbar_wait(bEmpty + c * 8, p - 1); mbar_expect(bFull + c * 8, 9216);
                    bulk_g2s(sb + c * 9216, wsrc + (p * 9 + c) * 4608, 9216, bFull + c * 8);
                }
            }
            l2_prefetch(w1 + pos * 13824, 27648);
            if (pos == 0) l2_prefetch(b1, 9216);
        } else if (warp == 17) {
            bar_sync(2, 160);
            if (lane == 0) spin_ge(g_cnt + g * CNT_S, 64);
            __syncwarp();
            bar_arrive(1, 288);
        } else if (warp >= 18) {
            const int m = warp - 18;
            {
                const unsigned long long* lp = g_ln + mt * 128 + m * 64 + (lane >> 3) * 16 + (lane & 7);
                unsigned long long r0, r1; int it = 0;
                __nanosleep(700);
                while (true) {
                    asm volatile("ld.relaxed.gpu.global.u64 %0, [%1];" : "=l"(r0) : "l"(lp) : "memory");
                    asm volatile("ld.relaxed.gpu.global.u64 %0, [%1];" : "=l"(r1) : "l"(lp + 8) : "memory");
                    if (__all_sync(~0u, (long long)(r0 & r1) < 0)) break;
                    if (++it > (1 << 22)) __trap();
                }
                sts128(sm + KA_LN + (m * 32 + lane) * 16, (uint32_t)r0, (uint32_t)(r0 >> 32), (uint32_t)r1, (uint32_t)(r1 >> 32));
                mbar_arrive(bLn);
                if (tid == 576) TL(5, 7);
            }
            bf16* dst = g_o + (mt * 2 + m) * (64 * D_) + g * 4608;
            bar_sync(11 + m, 160);
            if (lane == 0) { bulk_s2g(dst, sm + m * 9216, 9216); bulk_commit(); bulk_wait_read(); if (m == 0) TL(1, 7); }
        }
    } else {
        const int xrow = mt * 128 + g * 16 + warp;
        uint4 xv[3];
        {
            const uint4* xr = reinterpret_cast<const uint4*>(x + xrow * D_);
            xv[0] = ldg128(xr + lane); xv[1] = ldg128(xr + lane + 32); xv[2] = ldg128(xr + 64 + (lane & 7));
        }
        asm volatile("setmaxnreg.inc.sync.aligned.u32 112;");
        bar_sync(0, 640);
        const int wg = warp >> 2, m = wg & 1, w4 = warp & 3, gq = lane >> 2, t = lane & 3;
        {
            const uint32_t w[12] = {xv[0].x, xv[0].y, xv[0].z, xv[0].w, xv[1].x, xv[1].y, xv[1].z, xv[1].w, xv[2].x, xv[2].y, xv[2].z, xv[2].w};
            float s = 0.f, s2 = 0.f;
            #pragma unroll
            for (int i = 0; i < 12; i++) { if (i < 8) s += bf_lo(w[i]) + bf_hi(w[i]); else s2 += bf_lo(w[i]) + bf_hi(w[i]); }
            if (lane < 8) s += s2;
            #pragma unroll
            for (int o = 16; o; o >>= 1) s += __shfl_xor_sync(~0u, s, o);
            const float mean = s * (1.f / D_);
            float q = 0.f, q2 = 0.f;
            #pragma unroll
            for (int i = 0; i < 12; i++) {
                const float e0 = bf_lo(w[i]) - mean, e1 = bf_hi(w[i]) - mean;
                if (i < 8) q += e0 * e0 + e1 * e1; else q2 += e0 * e0 + e1 * e1;
            }
            if (lane < 8) q += q2;
            #pragma unroll
            for (int o = 16; o; o >>= 1) q += __shfl_xor_sync(~0u, q, o);
            const unsigned long long lrec = ((unsigned long long)(__float_as_uint(rsqrtf(q * (1.f / D_) + LN_EPS)) | 0x80000000u) << 32) | __float_as_uint(mean);
            if (lane == 0) asm volatile("st.relaxed.gpu.global.u64 [%0], %1;" :: "l"(g_ln + xrow), "l"(lrec) : "memory");
            if (tid == 256) TL(0, 6);
        }
        float2 ln0, ln1;
        auto ln_get = [&]() {
            mbar_wait(bLn, 0);
            const uint4 v = lds128(sm + KA_LN + (m * 32 + w4 * 8 + gq) * 16);
            ln0 = make_float2(__uint_as_float(v.x), fabsf(__uint_as_float(v.y))); ln1 = make_float2(__uint_as_float(v.z), fabsf(__uint_as_float(v.w)));
        };
        const uint64_t da = mkdesc(sm + m * 8192, 16, 1024, 1), db = mkdesc(sm + KA_B, 16, 1024, 1);
        const uint32_t csa = sm + KA_CS + 8 * t;
        const int rot = (gq + 2 * t) & 7;
        const uint32_t rec = sm + KA_REC + t * 16384 + m * 8192 + (w4 * 16 + rot) * 128;
        const uint32_t pqs = sm + KA_B + m * (16 * PQ_UNIT);
        if (wg < 2) {
            float acc[36]; uint2 cs[9];
            #pragma unroll
            for (int c = 0; c < 9; c++) {
                mbar_wait(bFull + c * 8, 0);
                wg_fence();
                #pragma unroll
                for (int kk = 0; kk < 4; kk++) wgmma_n72<0, 0>(acc, dadv(da, c * 16384 + kk * 32), dadv(db, c * 9216 + kk * 32), (c | kk) != 0);
                wg_commit();
                if (c == 0 && tid == 0) TL(1, 2);
                if (c > 0) { wg_wait<1>(); if (lane == 0) mbar_arrive(bEmpty + (c - 1) * 8); }
            }
            wg_wait<0>();
            reg_fence<36>(acc);
            bar_arrive(5, 512);
            if (lane == 0) mbar_arrive(bEmpty + 8 * 8);
            bar_sync(6, 384);
            #pragma unroll
            for (int j = 0; j < 9; j++) cs[j] = lds64(csa + 32 * j);
            ln_get();
            if (tid == 0) TL(1, 3);
            uint32_t ph[2][18];
            #pragma unroll
            for (int r = 0; r < 2; r++) {
                float a[18];
                const float2 ln = r ? ln1 : ln0;
                #pragma unroll
                for (int j = 0; j < 9; j++) { a[2 * j] = fmaf(-ln.x, __uint_as_float(cs[j].x), acc[4 * j + 2 * r]); a[2 * j + 1] = fmaf(-ln.x, __uint_as_float(cs[j].y), acc[4 * j + 2 * r + 1]); }
                dual_softmax(a, ln.y * LOG2E, ph[r]);
            }
            #pragma unroll
            for (int j = 0; j < 18; j++) asm volatile("" : "+r"(ph[0][j]), "+r"(ph[1][j]));
            if (tid == 0) TL(1, 4);
            bar_sync(3 + m, 256);
            #pragma unroll
            for (int r = 0; r < 2; r++) {
                #pragma unroll
                for (int j = 0; j < 4; j++) sts128(rec + r * 1024 + ((j ^ rot) << 4), ph[r][4 * j], ph[r][4 * j + 1], ph[r][4 * j + 2], ph[r][4 * j + 3]);
                sts128(rec + r * 1024 + ((4 ^ rot) << 4), ph[r][16], ph[r][17], 0u, 0u);
            }
            fence_async_smem();
            bar_sync(8, 512);
            float ck[2][20];
            wg_fence();
            const uint64_t dr = mkdesc(sm + KA_REC + m * 32768, 8192, 1024, 1);
            #pragma unroll
            for (int ks = 0; ks < 8; ks++)
                #pragma unroll
                for (int hh = 0; hh < 2; hh++)
                    wgmma_n40<1, 1>(ck[hh], dadv(dr, hh * 16384 + ks * 2048), dadv(dr, hh * 16384 + ks * 2048), ks != 0);
            wg_commit();
            if (w4 < 2) bar_arrive(7, 512);
            wg_wait<0>();
            reg_fence<20>(ck[0]); reg_fence<20>(ck[1]);
            if (tid == 0) TL(1, 5);
            if (w4 >= 2) {
                #pragma unroll
                for (int hh = 0; hh < 2; hh++) {
                    float* kvh = g_kv + (g * 4 + m * 2 + hh) * KV_H;
                    #pragma unroll
                    for (int e = 0; e < 2; e++) {
                        const int nt = 2 * w4 + e - 5;
                        if (nt >= 0 && (nt < 2 || gq < 3)) {
                            float* p = kvh + nt * 320;
                            const float* q = ck[hh] + 2 * e;
                            asm volatile("red.global.add.v4.f32 [%0], {%1, %2, %3, %4};" :: "l"(p + lane * 4), "f"(q[0]), "f"(q[1]), "f"(q[4]), "f"(q[5]) : "memory");
                            asm volatile("red.global.add.v4.f32 [%0], {%1, %2, %3, %4};" :: "l"(p + 128 + lane * 4), "f"(q[8]), "f"(q[9]), "f"(q[12]), "f"(q[13]) : "memory");
                            if (t < 2) asm volatile("red.global.add.v2.f32 [%0], {%1, %2};" :: "l"(p + 256 + lane * 2), "f"(q[16]), "f"(q[17]) : "memory");
                        }
                    }
                }
                __syncwarp();
                bar_arrive(7, 512);
                if (lane == 0) asm volatile("red.release.gpu.global.add.u32 [%0], 1;" :: "l"(g_cnt + g * CNT_S) : "memory");
                __syncwarp();
                bar_arrive(2, 160);
                if (tid == 96) TL(5, 3);
            }
            const float* kp = g_kv + (g * 4 + w4) * KV_H + lane * 2;
            bar_sync(1, 288);
            if (tid == 0) TL(1, 6);
            uint4 u0[3], u1[3]; uint2 u2[3];
            #pragma unroll
            for (int n = 2; n >= 0; n--) { u0[n] = ldg128(kp + n * 320 + lane * 2); u1[n] = ldg128(kp + n * 320 + 128 + lane * 2); u2[n] = ldg64(kp + n * 320 + 256); }
            bar_sync(9 + m, 256);
            uint4 a0[4], a1[4]; uint2 at[4];
            #pragma unroll
            for (int mm = 0; mm < 4; mm++) {
                const uint32_t ub = pqs + (mm * 4 + w4) * PQ_UNIT;
                a0[mm] = lds128(ub + lane * 16); a1[mm] = lds128(ub + 512 + lane * 16); at[mm] = lds64(ub + 1024 + gq * 16 + (t & 1) * 8);
            }
            uint32_t bq[3][5];
            #pragma unroll
            for (int n = 0; n < 3; n++) {
                bq[n][0] = packu(u0[n].x, u0[n].y); bq[n][1] = packu(u0[n].z, u0[n].w);
                bq[n][2] = packu(u1[n].x, u1[n].y); bq[n][3] = packu(u1[n].z, u1[n].w);
                bq[n][4] = packu(u2[n].x, u2[n].y);
            }
            const uint32_t os = sm + m * 9216;
            uint32_t oad[3];
            #pragma unroll
            for (int n = 0; n < 3; n++) { const int k = w4 * 18 + n * 8 + 2 * t; oad[n] = os + (k >> 3) * 1024 + gq * 16 + (k & 7) * 2; }
            #pragma unroll
            for (int mp = 0; mp < 2; mp++) {
                float c[2][3][4];
                #pragma unroll
                for (int e = 0; e < 2; e++)
                    #pragma unroll
                    for (int n = 2; n >= 0; n--) {
                        c[e][n][0] = c[e][n][1] = c[e][n][2] = c[e][n][3] = 0.f;
                        mma16816(c[e][n], a0[2 * mp + e].x, a1[2 * mp + e].x, a0[2 * mp + e].y, a1[2 * mp + e].y, bq[n][0], bq[n][1]);
                    }
                #pragma unroll
                for (int e = 0; e < 2; e++)
                    #pragma unroll
                    for (int n = 2; n >= 0; n--) mma16816(c[e][n], a0[2 * mp + e].z, a1[2 * mp + e].z, a0[2 * mp + e].w, a1[2 * mp + e].w, bq[n][2], bq[n][3]);
                #pragma unroll
                for (int e = 0; e < 2; e++)
                    #pragma unroll
                    for (int n = 2; n >= 0; n--) mma1688(c[e][n], at[2 * mp + e].x, at[2 * mp + e].y, bq[n][4]);
                float rr[2][2];
                #pragma unroll
                for (int e = 0; e < 2; e++) {
                    rr[e][0] = __shfl_sync(~0u, c[e][2][0], (lane & 28) | 1); rr[e][1] = __shfl_sync(~0u, c[e][2][2], (lane & 28) | 1);
                }
                #pragma unroll
                for (int e = 0; e < 2; e++) {
                    const float r0 = rcp_full(rr[e][0] + 1e-6f), r1 = rcp_full(rr[e][1] + 1e-6f);
                    #pragma unroll
                    for (int n = 0; n < 3; n++) {
                        const uint32_t v0 = pack2(c[e][n][0] * r0, c[e][n][1] * r0), v1 = pack2(c[e][n][2] * r1, c[e][n][3] * r1);
                        if (n < 2 || t == 0) { sts32(oad[n] + (2 * mp + e) * 256, v0); sts32(oad[n] + (2 * mp + e) * 256 + 128, v1); }
                    }
                }
            }
            fence_async_smem();
            bar_arrive(11 + m, 160);
        } else {
            float avq[36], acc[36]; uint2 cs[9];
            if (m == 1) {
                pdl_wait();
                if (tid < 384 + 108) {
                    uint2 pc[18];
                    #pragma unroll
                    for (int j = 0; j < 18; j++) pc[j] = ldg64(g_cs + (g * 18 + j) * 216 + (tid - 384) * 2);
                    float a = 0.f, c = 0.f;
                    #pragma unroll
                    for (int j = 0; j < 18; j++) { a += __uint_as_float(pc[j].x); c += __uint_as_float(pc[j].y); }
                    asm volatile("st.shared.v2.f32 [%0], {%1, %2};" :: "r"(sm + KA_CS + (tid - 384) * 8), "f"(a), "f"(c) : "memory");
                }
                if (tid == 384) TL(5, 4);
                bar_arrive(6, 384);
            }
            bar_sync(5, 512);
            if (tid == 256) TL(5, 5);
            #pragma unroll
            for (int i = 9; i < 22; i++) {
                const int c = i < 17 ? (i + 1) / 2 : i - 17;
                mbar_wait(bFull + (i % 9) * 8, (i / 9) & 1);
                wg_fence();
                #pragma unroll
                for (int kk = 0; kk < 4; kk++)
                    wgmma_n72<0, 0>((i < 17 && !(i & 1)) ? acc : avq, dadv(da, c * 16384 + kk * 32), dadv(db, (i % 9) * 9216 + kk * 32), i > 10 || kk != 0);
                wg_commit();
                if (i > 9 && i <= 18) { wg_wait<1>(); if (lane == 0) mbar_arrive(bEmpty + ((i - 1) % 9) * 8); }
                if (i == 17) bar_arrive(3 + m, 256);
                if (i == 18) bar_sync(14 + m, 128);
            }
            #pragma unroll
            for (int j = 0; j < 9; j++) cs[j] = lds64(csa + 288 + 32 * j);
            ln_get();
            wg_wait<0>();
            reg_fence<36>(avq);
            if (tid == 256) TL(5, 0);
            #pragma unroll
            for (int r = 0; r < 2; r++) {
                uint32_t pv[9];
                const float2 ln = r ? ln1 : ln0;
                #pragma unroll
                for (int j = 0; j < 9; j++)
                    pv[j] = pack2(fmaf(-ln.x, __uint_as_float(cs[j].x), avq[4 * j + 2 * r]) * ln.y, fmaf(-ln.x, __uint_as_float(cs[j].y), avq[4 * j + 2 * r + 1]) * ln.y);
                sts128(rec + r * 1024 + ((5 ^ rot) << 4), pv[0], pv[1], pv[2], pv[3]);
                sts128(rec + r * 1024 + ((6 ^ rot) << 4), pv[4], pv[5], pv[6], pv[7]);
                sts128(rec + r * 1024 + ((7 ^ rot) << 4), pv[8], 0x00003f80u, 0u, 0u);
            }
            fence_async_smem();
            bar_arrive(8, 512);
            const uint32_t sm2 = __shfl_sync(~0u, sm, 1);
            const uint64_t da2 = mkdesc(sm2 + m * 8192, 16, 1024, 1), db2 = mkdesc(sm2 + KA_B, 16, 1024, 1);
            #pragma unroll
            for (int i = 22; i < 27; i++) mbar_wait(bFull + (i % 9) * 8, 0);
            #pragma unroll
            for (int j = 0; j < 9; j++) cs[j] = lds64(csa + 576 + 32 * j);
            bar_sync(7, 512);
            wg_fence();
            #pragma unroll
            for (int i = 22; i < 27; i++)
                #pragma unroll
                for (int kk = 0; kk < 4; kk++) wgmma_n72<0, 0>(acc, dadv(da2, (i - 22) * 16384 + kk * 32), dadv(db2, (i % 9) * 9216 + kk * 32), 1);
            wg_commit();
            wg_wait<0>();
            reg_fence<36>(acc);
            if (tid == 256) TL(5, 1);
            uint32_t ph[2][18];
            #pragma unroll
            for (int r = 0; r < 2; r++) {
                float a[18];
                const float2 ln = r ? ln1 : ln0;
                #pragma unroll
                for (int j = 0; j < 9; j++) { a[2 * j] = fmaf(-ln.x, __uint_as_float(cs[j].x), acc[4 * j + 2 * r]); a[2 * j + 1] = fmaf(-ln.x, __uint_as_float(cs[j].y), acc[4 * j + 2 * r + 1]); }
                dual_softmax(a, ln.y * LOG2E, ph[r]);
            }
            #pragma unroll
            for (int j = 0; j < 18; j++) asm volatile("" : "+r"(ph[0][j]), "+r"(ph[1][j]));
            bar_sync(13, 256);
            const uint32_t ub = pqs + (w4 * 4 + t) * PQ_UNIT;
            #pragma unroll
            for (int r = 0; r < 2; r++)
                #pragma unroll
                for (int j = 0; j < 4; j++) sts128(ub + r * 512 + (gq * 4 + j) * 16, ph[r][j], ph[r][4 + j], ph[r][8 + j], ph[r][12 + j]);
            sts128(ub + 1024 + gq * 16, ph[0][16], ph[1][16], ph[0][17], ph[1][17]);
            bar_arrive(9 + m, 256);
            if (tid == 256) TL(5, 2);
        }
    }
}

constexpr int K2PRE = 2, K2_B = 73728, K2_PIECE = 27648, K2_X = K2_B + 5 * K2_PIECE, K2_BAR = K2_X + 18432, K2_SMEM = K2_BAR + 128;
__global__ void __cluster_dims__(2, 1, 1) __launch_bounds__(256, 1) k2_attn(const __grid_constant__ CUtensorMap tmX, const bf16* __restrict__ b2) {
    extern __shared__ __align__(1024) char smem[];
    const uint32_t sm = smem_u32(smem);
    const uint32_t bFull = sm + K2_BAR, bX = bFull + 6 * 8;
    const int tid = threadIdx.x, lane = tid & 31, warp = __shfl_sync(~0u, tid >> 5, 0);
    const int ns = blockIdx.x & 3, mt = blockIdx.x >> 2;
    const int wg = warp >> 2, w4 = warp & 3, gq = lane >> 2, t = lane & 3;
    const bf16* wsrc = g_wo + ns * (2 * 72 * 576);
    unsigned short bb0, bb1;
    asm volatile("ld.global.nc.u16 %0, [%1];" : "=h"(bb0) : "l"(b2 + mt * 64 + w4 * 16 + gq));
    asm volatile("ld.global.nc.u16 %0, [%1];" : "=h"(bb1) : "l"(b2 + mt * 64 + w4 * 16 + gq + 8));
    auto load_w = [&](int i) {
        bulk_g2s(sm + K2_B + (i % 5) * K2_PIECE, wsrc + i * (K2_PIECE / 4), K2_PIECE / 2, bFull + i * 8);
        bulk_g2s(sm + K2_B + (i % 5) * K2_PIECE + K2_PIECE / 2, wsrc + 72 * 576 + i * (K2_PIECE / 4), K2_PIECE / 2, bFull + i * 8);
    };
    if (tid == 0) {
        TL(2, 0);
        #pragma unroll
        for (int i = 0; i < 7; i++) mbar_init(bFull + i * 8, 1);
        fence_mbar_init();
        #pragma unroll
        for (int i = 0; i < 6; i++) mbar_expect(bFull + i * 8, K2_PIECE + 12288);
        mbar_expect(bX, 18432);
        #pragma unroll
        for (int i = 0; i < K2PRE; i++) load_w(i);
        prefetch_tm(&tmX);
    }
    __syncthreads();
    if (tid == 0) {
        pdl_wait();
        pdl_trigger();
        TL(2, 1);
        const bf16* osrc = g_o + mt * (64 * D_);
        #pragma unroll
        for (int i = 0; i < 6; i++) {
            bulk_g2s(sm + i * 12288, osrc + i * 6144, 12288, bFull + i * 8);
            if (i + 1 >= K2PRE && i < 4) load_w(i + 1);
        }
        tma2d(sm + K2_X, &tmX, bX, ns * 144, mt * 64);
        tma2d(sm + K2_X + 9216, &tmX, bX, ns * 144 + 72, mt * 64);
    }
    __syncwarp();
    {
        float acc[36];
        const uint32_t xs = sm + K2_X + wg * 9216;
        uint32_t xr[18];
        const int p = ns * 2 + wg;
        unsigned long long* sb = g_stats + (mt * 4 + w4) * 128 + gq * 2;
        unsigned long long* sw = sb + p * 16;
        const unsigned long long* sr = sb + t * 32;
        bf16* ndst = g_hnT + (mt * D_ + p * 72) * 64;
        asm volatile("" : "+l"(sw), "+l"(sr), "+l"(ndst));
        const uint64_t da0 = mkdesc(sm, 1024, 128, 0), db0 = mkdesc(sm + K2_B + wg * (K2_PIECE / 2), 1152, 128, 0);
        #pragma unroll
        for (int i = 0; i < 6; i++) {
            mbar_wait(bFull + i * 8, 0);
            if (i == 0 && tid == 0) TL(2, 3);
            wg_fence();
            #pragma unroll
            for (int kk = 0; kk < 6; kk++)
                wgmma_n72<0, 0>(acc, dadv(da0, i * 12288 + kk * 2048), dadv(db0, (i % 5) * K2_PIECE + kk * 2304), (i | kk) != 0);
            wg_commit();
            if (i == 1) {
                wg_wait<1>();
                bar_sync(1 + wg, 128);
                if ((tid & 127) == 96) bulk_g2s(sm + K2_B + wg * (K2_PIECE / 2), wsrc + wg * (72 * 576) + 5 * (K2_PIECE / 4), K2_PIECE / 2, bFull + 5 * 8);
                __syncwarp();
            }
            if (i == 5) {
                mbar_wait(bX, 0);
                #pragma unroll
                for (int j = 0; j < 9; j++) {
                    xr[2 * j] = lds32(xs + (w4 * 16 + gq) * 144 + j * 16 + t * 4); xr[2 * j + 1] = lds32(xs + (w4 * 16 + gq + 8) * 144 + j * 16 + t * 4);
                }
            }
        }
        wg_wait<0>();
        reg_fence<36>(acc);
        #pragma unroll
        for (int j = 0; j < 18; j++) { acc[2 * j] += bf_lo(xr[j]); acc[2 * j + 1] += bf_hi(xr[j]); }
        if (tid == 0) TL(2, 4);
        float m0 = 0.f, m1 = 0.f;
        #pragma unroll
        for (int j = 0; j < 9; j++) { m0 += acc[4 * j] + acc[4 * j + 1]; m1 += acc[4 * j + 2] + acc[4 * j + 3]; }
        m0 *= (1.f / 18); m1 *= (1.f / 18);
        float q0 = 0.f, q1 = 0.f, q2 = 0.f, q3 = 0.f;
        #pragma unroll
        for (int j = 0; j < 9; j++) {
            float e;
            e = acc[4 * j] - m0; q0 = fmaf(e, e, q0); e = acc[4 * j + 1] - m0; q2 = fmaf(e, e, q2);
            e = acc[4 * j + 2] - m1; q1 = fmaf(e, e, q1); e = acc[4 * j + 3] - m1; q3 = fmaf(e, e, q3);
        }
        q0 += q2; q1 += q3;
        #pragma unroll
        for (int o = 1; o < 4; o <<= 1) {
            const float a0 = __shfl_xor_sync(~0u, m0, o), a1 = __shfl_xor_sync(~0u, m1, o), b0 = __shfl_xor_sync(~0u, q0, o), b1 = __shfl_xor_sync(~0u, q1, o);
            q0 += b0 + (a0 - m0) * (a0 - m0) * (9.f * o); q1 += b1 + (a1 - m1) * (a1 - m1) * (9.f * o);
            m0 = 0.5f * (m0 + a0); m1 = 0.5f * (m1 + a1);
        }
        if (t == 0) {
            const unsigned long long r0 = ((unsigned long long)(__float_as_uint(q0) | 0x80000000u) << 32) | __float_as_uint(m0);
            const unsigned long long r1 = ((unsigned long long)(__float_as_uint(q1) | 0x80000000u) << 32) | __float_as_uint(m1);
            asm volatile("st.relaxed.gpu.global.v2.u64 [%0], {%1, %2};" :: "l"(sw), "l"(r0), "l"(r1) : "memory");
        }
        bar_sync(1 + wg, 128);
        if (tid == 0) TL(2, 5);
        unsigned long long ra, rb, rc, rd;
        {
            int it = 0;
            while (true) {
                asm volatile("ld.relaxed.gpu.global.v2.u64 {%0, %1}, [%2];" : "=l"(ra), "=l"(rc) : "l"(sr) : "memory");
                asm volatile("ld.relaxed.gpu.global.v2.u64 {%0, %1}, [%2];" : "=l"(rb), "=l"(rd) : "l"(sr + 16) : "memory");
                const bool ok = (long long)(ra & rb & rc & rd) < 0;
                if (__all_sync(~0u, ok)) break;
                if (++it > (1 << 22)) __trap();
            }
        }
        if (tid == 0) TL(2, 6);
        float sc[2], mu[2];
        #pragma unroll
        for (int r = 0; r < 2; r++) {
            const unsigned long long u = r ? rc : ra, v = r ? rd : rb;
            const float ma = __uint_as_float((uint32_t)u), mb = __uint_as_float((uint32_t)v);
            float ms = ma + mb;
            ms += __shfl_xor_sync(~0u, ms, 1); ms += __shfl_xor_sync(~0u, ms, 2);
            const float mean = ms * 0.125f;
            float M2 = fabsf(__uint_as_float((uint32_t)(u >> 32))) + fabsf(__uint_as_float((uint32_t)(v >> 32))) + 72.f * ((ma - mean) * (ma - mean) + (mb - mean) * (mb - mean));
            M2 += __shfl_xor_sync(~0u, M2, 1); M2 += __shfl_xor_sync(~0u, M2, 2);
            const float var = M2 * (1.f / D_);
            const float r1 = rsqrtf(var + LN_EPS);
            const float var2 = var * r1 * r1;
            const float r2 = rsqrtf(var2 + LN_EPS);
            sc[r] = 0.5f * (r1 * r2); mu[r] = mean;
        }
        {
            uint32_t o[18];
            #pragma unroll
            for (int j = 0; j < 9; j++) {
                o[2 * j] = pack2((acc[4 * j] - mu[0]) * sc[0], (acc[4 * j + 1] - mu[0]) * sc[0]);
                o[2 * j + 1] = pack2((acc[4 * j + 2] - mu[1]) * sc[1], (acc[4 * j + 3] - mu[1]) * sc[1]);
            }
            const int ch = 2 * w4 + ((lane >> 3) & 1);
            const uint32_t ad = xs + ((lane >> 4) * 8 + (lane & 7)) * 128 + ((ch ^ (lane & 7)) << 4);
            #pragma unroll
            for (int j = 0; j < 4; j++) stsm4t(ad + j * 2048, o[4 * j], o[4 * j + 1], o[4 * j + 2], o[4 * j + 3]);
            stsm2t(xs + (64 + (lane & 7)) * 128 + ((ch ^ (lane & 7)) << 4), o[16], o[17]);
        }
        fence_async_smem();
        bar_sync(1 + wg, 128);
        if ((tid & 127) == 0) {
            bulk_s2g(ndst, xs, 9216);
            bulk_commit();
        }
        if (p == 1 && t < 2) g_ln[mt * 64 + w4 * 16 + gq + 8 * t] = 0ull;
        if (p == 0 && t < 2) {
            asm volatile("" : "+h"(bb0), "+h"(bb1));
            g_rc[mt * 64 + w4 * 16 + gq + 8 * t] = make_float2(1.f / (t ? sc[1] : sc[0]), (t ? mu[1] : mu[0]) + __uint_as_float((uint32_t)(t ? bb1 : bb0) << 16));
        }
        if ((tid & 127) == 0) bulk_wait_read();
        if (tid == 0) TL(2, 7);
    }
}

constexpr int PFT = 4, W2HEAD = 9;
constexpr int K3_STAGES = 6, K3_STAGE = 36864, K3_STAG = 6, K3_PRE = 2, K3_BAR = K3_STAGES * K3_STAGE, K3_SMEM = K3_BAR + 256;
DEVI uint32_t gelu2(float a0, float a1) {
    const float z0 = a0 * fmaf(a0 * a0, 0.2854192650904f, 1.5957691216057f), z1 = a1 * fmaf(a1 * a1, 0.2854192650904f, 1.5957691216057f);
    return pack2(fmaf(a0, tanh_fast(z0), a0), fmaf(a1, tanh_fast(z1), a1));
}
template<int ROWS, int OFF> DEVI void k3_store(const float* q, uint32_t st, uint32_t lo, int bar) {
    #pragma unroll
    for (int jj = 0; jj < ROWS / 16; jj++)
        stsm4t(st + lo + jj * 2048, gelu2(q[OFF + jj * 8], q[OFF + jj * 8 + 1]), gelu2(q[OFF + jj * 8 + 2], q[OFF + jj * 8 + 3]),
               gelu2(q[OFF + jj * 8 + 4], q[OFF + jj * 8 + 5]), gelu2(q[OFF + jj * 8 + 6], q[OFF + jj * 8 + 7]));
    fence_async_smem();
    bar_arrive(bar, 160);
}
DEVI void k3_typeb(uint32_t sm_, int fc_, uint32_t lo, float bias0, float bias1, const bf16* __restrict__ b1) {
    const uint32_t sm = __shfl_sync(~0u, sm_, 0);
    const int fc = __shfl_sync(~0u, fc_, 0);
    const uint32_t bFull = sm + K3_BAR, bEmpty = bFull + K3_STAGES * 8;
    const int tid = threadIdx.x, lane = tid & 31, warp = __shfl_sync(~0u, tid >> 5, 0);
    const int wg = warp >> 2, w4 = warp & 3, gq = lane >> 2, tw = tid & 127;
    const uint32_t st = sm + wg * 8192;
    const uint64_t da0 = mkdesc(st, 8192, 1024, 1);
    int s = 0, ps = 0; uint32_t ph = 0;
    {
            const int f2 = (fc + 2) * 64 + w4 * 16 + gq;
            const float bias2 = 0.5f * __bfloat162float(b1[f2]), bias3 = 0.5f * __bfloat162float(b1[f2 + 8]);
            float acc[48], acc2[24];
            const uint64_t da2 = mkdesc(sm + 16384, 8192, 1024, 1), db0 = mkdesc(sm + 24576, 16, 1024, 1), db2 = mkdesc(sm + 24576 + wg * 6144, 16, 1024, 1);
            #pragma unroll 1
            for (int i = 0; i < 32 - K3_STAG; i++) {
                mbar_wait(bFull + s * 8, ph);
                const uint32_t so = s * K3_STAGE;
                wg_fence();
                #pragma unroll
                for (int kk = 0; kk < 4; kk++) {
                    wgmma_n96<1, 0>(acc, dadv(da0, so + kk * 2048), dadv(db0, so + kk * 32), (i | kk) != 0);
                    wgmma_n48<1, 0>(acc2, dadv(da2, so + kk * 2048), dadv(db2, so + kk * 32), (i | kk) != 0);
                }
                wg_commit();
                wg_wait<1>();
                if (i > 0 && lane == 0) mbar_arrive(bEmpty + ps * 8);
                ps = s;
                if (++s == K3_STAGES) { s = 0; ph ^= 1; }
            }
            if (wg == 1) {
                wg_wait<0>();
                if (lane == 0) mbar_arrive(bEmpty + ps * 8);
                #pragma unroll
                for (int i = 32 - K3_STAG; i < 32; i++) mbar_wait(bFull + (i % K3_STAGES) * 8, (i / K3_STAGES) & 1);
                bar_sync(3, 256);
            }
            #pragma unroll
            for (int i = 32 - K3_STAG; i < 32; i++) {
                if (wg == 0) mbar_wait(bFull + (i % K3_STAGES) * 8, (i / K3_STAGES) & 1);
                const uint32_t so = (i % K3_STAGES) * K3_STAGE;
                wg_fence();
                #pragma unroll
                for (int kk = 0; kk < 4; kk++) {
                    wgmma_n96<1, 0>(acc, dadv(da0, so + kk * 2048), dadv(db0, so + kk * 32), 1);
                    wgmma_n48<1, 0>(acc2, dadv(da2, so + kk * 2048), dadv(db2, so + kk * 32), 1);
                }
                wg_commit();
                if (i == 32 - K3_STAG && wg == 0) { wg_wait<1>(); if (lane == 0) mbar_arrive(bEmpty + ps * 8); }
            }
            if (wg == 0) bar_arrive(3, 256);
            wg_wait<0>();
            reg_fence<48>(acc); reg_fence<24>(acc2);
            #pragma unroll
            for (int j = 0; j < 48; j++) acc[j] += (j & 2) ? bias1 : bias0;
            #pragma unroll
            for (int j = 0; j < 24; j++) acc2[j] += (j & 2) ? bias3 : bias2;
            if (tw == 0) TL(7, 4 + wg);
            bar_sync(1 + wg, 128);
            k3_store<48, 0>(acc, st, lo, 4 + wg * 4);
            k3_store<48, 24>(acc, st + K3_STAGE, lo, 5 + wg * 4);
            k3_store<32, 0>(acc2, st + 2 * K3_STAGE, lo, 6 + wg * 4);
            k3_store<16, 16>(acc2, st + 3 * K3_STAGE, lo, 7 + wg * 4);
    }
}
__global__ void __cluster_dims__(2, 1, 1) __launch_bounds__(352, 1) k3_mix1(const __grid_constant__ CUtensorMap tmW1a, const __grid_constant__ CUtensorMap tmW1b,
                                                                             const bf16* __restrict__ b1, const bf16* __restrict__ w1, const bf16* __restrict__ w2) {
    extern __shared__ __align__(1024) char smem[];
    const uint32_t sm = smem_u32(smem);
    const uint32_t bFull = sm + K3_BAR, bEmpty = bFull + K3_STAGES * 8;
    const int tid = threadIdx.x, lane = tid & 31, warp = __shfl_sync(~0u, tid >> 5, 0);
    const int cl = blockIdx.x >> 1, rank = blockIdx.x & 1;
    bool tb = false; int fc, d0;
    if (cl < 36) { fc = 2 * cl; d0 = 160 * rank; }
    else if (cl < 60) { const int q = (cl - 36) >> 1, e = (cl - 36) & 1; tb = rank; fc = rank ? 6 * q + 3 * e : 6 * q + 4 * e; d0 = rank ? 480 : 320; }
    else { fc = 6 * (2 * (cl - 60) + rank) + 2; d0 = 320; }
    const CUtensorMap* tm = tb ? &tmW1b : &tmW1a;
    const uint32_t abytes = tb ? 24576 : 16384;
    if (tid == 256) {
        TL(3, 0);
        #pragma unroll
        for (int i = 0; i < K3_STAGES; i++) { mbar_init(bFull + i * 8, 1); mbar_init(bEmpty + i * 8, 8); }
        fence_mbar_init();
        #pragma unroll
        for (int i = 0; i < K3_STAGES; i++) mbar_expect(bFull + i * 8, K3_STAGE);
        #pragma unroll
        for (int i = 0; i < K3_PRE; i++) tma3d(sm + i * K3_STAGE, tm, bFull + i * 8, 0, i * 64, fc);
    }
    __syncthreads();
    if (warp >= 9) {
        const int wg = warp - 9;
        bf16* dst = g_u + ((fc + wg) * D_ + d0) * 64;
        bf16* dst2 = tb ? g_u + ((fc + 2) * D_ + 480 + wg * 48) * 64 : dst + 96 * 64;
        #pragma unroll
        for (int pc = 0; pc < 4; pc++) {
            bar_sync(4 + wg * 4 + pc, 160);
            if (lane == 0) {
                bulk_s2g(pc < 2 ? dst + pc * (48 * 64) : dst2 + (pc - 2) * (32 * 64), sm + wg * 8192 + pc * K3_STAGE, pc < 2 ? 6144 : (pc == 3 && tb) ? 2048 : 4096);
                bulk_commit();
            }
            __syncwarp();
        }
        if (lane == 0) { bulk_wait_read(); TL(3, 6 + wg); }
    } else if (warp == 8) {
        if (tid == 256) {
            pdl_wait();
            pdl_trigger();
            TL(3, 1);
            const bf16* hs = g_hnT + d0 * 64;
            #pragma unroll
            for (int i = 0; i < K3_STAGES; i++) {
                bulk_g2s(sm + i * K3_STAGE + abytes, hs + i * (D_ * 64), K3_STAGE - abytes, bFull + i * 8);
                if (i >= K3_PRE) tma3d(sm + i * K3_STAGE, tm, bFull + i * 8, 0, i * 64, fc);
            }
            int s = 0; uint32_t ph = 0;
            #pragma unroll 1
            for (int i = K3_STAGES; i < 32; i++) {
                mbar_wait(bEmpty + s * 8, ph);
                mbar_expect(bFull + s * 8, K3_STAGE);
                tma3d(sm + s * K3_STAGE, tm, bFull + s * 8, 0, i * 64, fc);
                bulk_g2s(sm + s * K3_STAGE + abytes, hs + i * (D_ * 64), K3_STAGE - abytes, bFull + s * 8);
                if (i == 18 && blockIdx.x < 128) l2_prefetch(w1 + (size_t)(2048 - 64 * PFT) * F_ + blockIdx.x * (2304 * PFT), 4608 * PFT);
                if (++s == K3_STAGES) { s = 0; ph ^= 1; }
            }
            if (blockIdx.x < 128) l2_prefetch(w2 + (size_t)(blockIdx.x & 1) * (2304 * S_) + (blockIdx.x >> 1) * (W2HEAD * 2048), W2HEAD * 4096);
        }
    } else {
        const int wg = warp >> 2, w4 = warp & 3, gq = lane >> 2, tw = tid & 127;
        const int f0 = (fc + wg) * 64 + w4 * 16 + gq;
        const float bias0 = 0.5f * __bfloat162float(b1[f0]), bias1 = 0.5f * __bfloat162float(b1[f0 + 8]);
        const int ch = 2 * w4 + ((lane >> 3) & 1);
        const uint32_t lo = ((lane >> 4) * 8 + (lane & 7)) * 128 + ((ch ^ (lane & 7)) << 4);
        const uint32_t st = sm + wg * 8192;
        const uint64_t da0 = mkdesc(st, 8192, 1024, 1);
        int s = 0, ps = 0; uint32_t ph = 0;
        if (!tb) {
            float acc[80];
            #pragma unroll
            for (int j = 0; j < 80; j++) acc[j] = (j & 2) ? bias1 : bias0;
            reg_fence<80>(acc);
            const uint64_t db0 = mkdesc(sm + 16384, 16, 1024, 1);
            CK0();
            #pragma unroll 1
            for (int i = 0; i < 32 - K3_STAG; i++) {
                mbar_wait(bFull + s * 8, ph);
                const uint64_t da = dadv(da0, s * K3_STAGE), db = dadv(db0, s * K3_STAGE);
                wg_fence();
                #pragma unroll
                for (int kk = 0; kk < 4; kk++)
                    wgmma_n160<1, 0>(acc, dadv(da, kk * 2048), dadv(db, kk * 32), 1);
                wg_commit();
                wg_wait<1>();
                if (i > 0 && lane == 0) mbar_arrive(bEmpty + ps * 8);
                ps = s;
                if (++s == K3_STAGES) { s = 0; ph ^= 1; }
            }
            if (tid == 0) CK1(3);
            if (wg == 1) {
                wg_wait<0>();
                if (lane == 0) mbar_arrive(bEmpty + ps * 8);
                #pragma unroll
                for (int i = 32 - K3_STAG; i < 32; i++) mbar_wait(bFull + (i % K3_STAGES) * 8, (i / K3_STAGES) & 1);
                bar_sync(3, 256);
            }
            #pragma unroll
            for (int i = 32 - K3_STAG; i < 32; i++) {
                if (wg == 0) mbar_wait(bFull + (i % K3_STAGES) * 8, (i / K3_STAGES) & 1);
                wg_fence();
                #pragma unroll
                for (int kk = 0; kk < 4; kk++)
                    wgmma_n160<1, 0>(acc, dadv(da0, (i % K3_STAGES) * K3_STAGE + kk * 2048), dadv(db0, (i % K3_STAGES) * K3_STAGE + kk * 32), 1);
                wg_commit();
                if (i == 32 - K3_STAG && wg == 0) { wg_wait<1>(); if (lane == 0) mbar_arrive(bEmpty + ps * 8); }
            }
            if (wg == 0) bar_arrive(3, 256);
            wg_wait<0>();
            reg_fence<80>(acc);
            if (tw == 0) TL(3, 4 + wg);
            bar_sync(1 + wg, 128);
            k3_store<48, 0>(acc, st, lo, 4 + wg * 4);
            k3_store<48, 24>(acc, st + K3_STAGE, lo, 5 + wg * 4);
            k3_store<32, 48>(acc, st + 2 * K3_STAGE, lo, 6 + wg * 4);
            k3_store<32, 64>(acc, st + 3 * K3_STAGE, lo, 7 + wg * 4);
        } else {
            k3_typeb(sm, fc, lo, bias0, bias1, b1);
        }
    }
}

constexpr int SLOTC = 700, SLOTP = 578, K4A0 = 1, K4_PD = 4;
constexpr int K4_STAGES = 5, K4_STAGE = 8192 + 36864, K4_STAG = 3, K4_BAR = K4_STAGES * K4_STAGE, K4_SMEM = K4_BAR + 256;
constexpr int K4_XS = (36 - K4_STAG - 1) % K4_STAGES;
__global__ void __cluster_dims__(2, 1, 1) __launch_bounds__(288, 1) k4_mix2(const __grid_constant__ CUtensorMap tmW2, const __grid_constant__ CUtensorMap tmOut) {
    extern __shared__ __align__(1024) char smem[];
    const uint32_t sm = smem_u32(smem);
    const uint32_t bFull = sm + K4_BAR, bEmpty = bFull + K4_STAGES * 8, bP = bEmpty + K4_STAGES * 8, bRdy = bP + 16, bH = bRdy + 8;
    const int tid = threadIdx.x, lane = tid & 31, warp = __shfl_sync(~0u, tid >> 5, 0);
    const int ks = blockIdx.x & 1, tm = (blockIdx.x >> 1) & 31, tn = blockIdx.x >> 6;
    const int k0 = ks * 36;
    if (tid == 256) {
        TL(4, 0);
        #pragma unroll
        for (int i = 0; i < K4_STAGES; i++) { mbar_init(bFull + i * 8, 1); mbar_init(bEmpty + i * 8, 8); }
        mbar_init(bP, 1); mbar_init(bP + 8, 1); mbar_init(bRdy, 8); mbar_init(bH, 1);
        fence_mbar_init();
        #pragma unroll
        for (int i = 0; i < K4A0; i++) tma3d(sm + i * K4_STAGE, &tmW2, bFull + i * 8, 0, (k0 + i) * 64, tm);
    }
    __syncthreads();
    cluster_arrive_relaxed();
    if (tid == 0) {
        #pragma unroll
        for (int i = K4A0; i < K4_STAGES; i++) tma3d(sm + i * K4_STAGE, &tmW2, bFull + i * 8, 0, (k0 + i) * 64, tm);
    }
    if (tid == 32) {
        #pragma unroll
        for (int i = 0; i < K4_STAGES; i++) mbar_expect(bFull + i * 8, K4_STAGE);
    }
    if (tid == 128) { mbar_expect(bP, 9216); mbar_expect(bP + 8, 9216); prefetch_tm(&tmOut); }
    __syncwarp();
    if (warp == 8) {
        if (lane == 0) {
            pdl_wait();
            TL(4, 1);
            const bf16* us = g_u + ((size_t)k0 * D_ + tn * 288) * 64;
            uint32_t slot = clock() + SLOTC;
            #pragma unroll
            for (int i = 0; i < K4_STAGES; i++) {
                if (i >= 2) { while ((int)(clock() - slot) < 0) {} slot += SLOTP; }
                bulk_g2s(sm + i * K4_STAGE + 8192, us + (size_t)i * (D_ * 64), 36864, bFull + i * 8);
            }
            int s = 0; uint32_t ph = 0;
            #pragma unroll 1
            for (int i = K4_STAGES; i < 36; i++) {
                mbar_wait(bEmpty + s * 8, ph);
                mbar_expect(bFull + s * 8, K4_STAGE);
                tma3d(sm + s * K4_STAGE, &tmW2, bFull + s * 8, 0, (k0 + i) * 64, tm);
                if (i + K4_PD < 36 && ((i ^ tn) & 1)) tma3d_prefetch(&tmW2, 0, (k0 + i + K4_PD) * 64, tm);
                if (i < 32) { while ((int)(clock() - slot) < 0) {} slot += SLOTP; }
                bulk_g2s(sm + s * K4_STAGE + 8192, us + (size_t)i * (D_ * 64), 36864, bFull + s * 8);
                if (++s == K4_STAGES) { s = 0; ph ^= 1; }
            }
            static_assert(K4_STAG <= 3, "stage of step 31 is free");
            mbar_wait(bEmpty + s * 8, ph);
            mbar_expect(bH, 18432);
            bulk_g2s(sm + (31 % K4_STAGES) * K4_STAGE, g_hnT + (tm * D_ + tn * 288 + ks * 144) * 64, 18432, bH);
        }
        __syncwarp();
        cluster_wait();
        #pragma unroll
        for (int hh = 0; hh < 2; hh++) {
            bar_sync(4 + hh, 160);
            if (lane == 0) {
                tma2d_store(&tmOut, sm + K4_XS * K4_STAGE + 24576 + hh * 9216, tn * 288 + ks * 144 + hh * 72, tm * 64);
                bulk_commit();
            }
            __syncwarp();
        }
        if (lane == 0) { bulk_wait_read(); TL(4, 7); }
    } else {
        const int wg = warp >> 2, w4 = warp & 3, tw = tid & 127;
        const bool keep = wg == ks;
        float acc[72];
        const uint64_t da0 = mkdesc(sm, 8192, 1024, 1), db0 = mkdesc(sm + 8192 + wg * 18432, 16, 1024, 1);
        const uint32_t rdy = mapa(bRdy, ks ^ 1);
        cluster_wait();
        CK0();
        int s = 0, ps = 0; uint32_t ph = 0;
        #pragma unroll 1
        for (int i = 0; i < 36 - K4_STAG; i++) {
            mbar_wait(bFull + s * 8, ph);
            const uint64_t da = dadv(da0, s * K4_STAGE), db = dadv(db0, s * K4_STAGE);
            wg_fence();
            #pragma unroll
            for (int kk = 0; kk < 4; kk++)
                wgmma_n144<1, 0>(acc, dadv(da, kk * 2048), dadv(db, kk * 32), (i | kk) != 0);
            wg_commit();
            wg_wait<1>();
            if (i > 0 && lane == 0) mbar_arrive(bEmpty + ps * 8);
            ps = s;
            if (++s == K4_STAGES) { s = 0; ph ^= 1; }
        }
        if (tid == 0) CK1(4);
        const uint32_t xa = sm + K4_XS * K4_STAGE + tw * 16;
        const uint2 rc0 = ldg64(g_rc + tm * 64 + w4 * 16 + (lane >> 2)), rc1 = ldg64(g_rc + tm * 64 + w4 * 16 + (lane >> 2) + 8);
        float res[36];
        const uint32_t ya = sm + (31 % K4_STAGES) * K4_STAGE + 20480 + tw * 16;
        auto residual = [&](int hh) {
            uint32_t hp[20];
            mbar_wait(bH, 0);
            const int ch = 2 * w4 + ((lane >> 3) & 1);
            const uint32_t ha = sm + (31 % K4_STAGES) * K4_STAGE + hh * 9216 + ((lane >> 4) * 8 + (lane & 7)) * 128 + ((ch ^ (lane & 7)) << 4);
            #pragma unroll
            for (int j = 0; j < 5; j++) ldsm4t(ha + j * 2048, hp[4 * j], hp[4 * j + 1], hp[4 * j + 2], hp[4 * j + 3]);
            #pragma unroll
            for (int j = 0; j < 18; j++) {
                const float is = __uint_as_float((j & 1) ? rc1.x : rc0.x), of = __uint_as_float((j & 1) ? rc1.y : rc0.y);
                res[2 * j] = fmaf(bf_lo(hp[j]), is, of); res[2 * j + 1] = fmaf(bf_hi(hp[j]), is, of);
            }
            reg_fence<36>(res);
        };
        auto partial = [&](int hh) {
            mbar_wait(bP + hh * 8, 0);
            uint32_t o[18];
            #pragma unroll
            for (int j = 0; j < 4; j++) { const uint4 v = lds128(xa + hh * 10240 + j * 2048); o[4 * j] = v.x; o[4 * j + 1] = v.y; o[4 * j + 2] = v.z; o[4 * j + 3] = v.w; }
            { const uint2 v = lds64(xa + hh * 10240 + 8192); o[16] = v.x; o[17] = v.y; }
            #pragma unroll
            for (int j = 0; j < 18; j++) { res[2 * j] += bf_lo(o[j]); res[2 * j + 1] += bf_hi(o[j]); }
        };
        if (!keep) {
            #pragma unroll
            for (int i = 36 - K4_STAG; i < 36; i++) {
                mbar_wait(bFull + (i % K4_STAGES) * 8, (i / K4_STAGES) & 1);
                wg_fence();
                #pragma unroll
                for (int kk = 0; kk < 4; kk++)
                    wgmma_n144<1, 0>(acc, dadv(da0, (i % K4_STAGES) * K4_STAGE + kk * 2048), dadv(db0, (i % K4_STAGES) * K4_STAGE + kk * 32), 1);
                wg_commit();
                if (i == 36 - K4_STAG) { wg_wait<1>(); if (lane == 0) mbar_arrive_remote(rdy); }
            }
            bar_arrive(3, 256);
            mbar_wait(bRdy, 0);
            wg_wait<0>();
            reg_fence<72>(acc);
            if (tw == 0) TL(4, 2);
            const uint32_t rd = mapa(xa, ks ^ 1), rb = mapa(bP, ks ^ 1);
            #pragma unroll
            for (int hh = 0; hh < 2; hh++) {
                const float* q = acc + hh * 36;
                #pragma unroll
                for (int j = 0; j < 4; j++)
                    asm volatile("st.async.shared::cluster.mbarrier::complete_tx::bytes.v4.b32 [%0], {%1,%2,%3,%4}, [%5];"
                                 :: "r"(rd + hh * 10240 + j * 2048), "r"(pack2(q[8 * j], q[8 * j + 1])), "r"(pack2(q[8 * j + 2], q[8 * j + 3])),
                                    "r"(pack2(q[8 * j + 4], q[8 * j + 5])), "r"(pack2(q[8 * j + 6], q[8 * j + 7])), "r"(rb + hh * 8) : "memory");
                asm volatile("st.async.shared::cluster.mbarrier::complete_tx::bytes.v2.b32 [%0], {%1,%2}, [%3];"
                             :: "r"(rd + hh * 10240 + 8192), "r"(pack2(q[32], q[33])), "r"(pack2(q[34], q[35])), "r"(rb + hh * 8) : "memory");
            }
            if (tw == 0) TL(4, 3);
            residual(1);
            partial(1);
            reg_fence<36>(res);
            bar_sync(1, 256);
            if (tw == 0) TL(4, 5);
            #pragma unroll
            for (int j = 0; j < 9; j++) {
                const uint4 v = lds128(ya + j * 2048);
                res[4 * j] += __uint_as_float(v.x); res[4 * j + 1] += __uint_as_float(v.y); res[4 * j + 2] += __uint_as_float(v.z); res[4 * j + 3] += __uint_as_float(v.w);
            }
        } else {
            wg_wait<0>();
            if (lane == 0) mbar_arrive_remote(rdy);
            #pragma unroll
            for (int i = 36 - K4_STAG; i < 36; i++) mbar_wait(bFull + (i % K4_STAGES) * 8, (i / K4_STAGES) & 1);
            bar_sync(3, 256);
            wg_fence();
            #pragma unroll
            for (int i = 36 - K4_STAG; i < 36; i++)
                #pragma unroll
                for (int kk = 0; kk < 4; kk++)
                    wgmma_n144<1, 0>(acc, dadv(da0, (i % K4_STAGES) * K4_STAGE + kk * 2048), dadv(db0, (i % K4_STAGES) * K4_STAGE + kk * 32), 1);
            wg_commit();
            residual(0);
            wg_wait<0>();
            reg_fence<72>(acc);
            if (tw == 0) TL(4, 4);
            #pragma unroll
            for (int j = 0; j < 9; j++)
                sts128(ya + j * 2048, __float_as_uint(acc[36 + 4 * j]), __float_as_uint(acc[37 + 4 * j]), __float_as_uint(acc[38 + 4 * j]), __float_as_uint(acc[39 + 4 * j]));
            bar_arrive(1, 256);
            #pragma unroll
            for (int j = 0; j < 36; j++) res[j] += acc[j];
            partial(0);
        }
        const int hh = keep ? 0 : 1;
        uint32_t o[18];
        #pragma unroll
        for (int j = 0; j < 18; j++) o[j] = pack2(res[2 * j], res[2 * j + 1]);
        const uint32_t ad = sm + K4_XS * K4_STAGE + 24576 + hh * 9216 + (w4 * 16 + ((lane >> 3) & 1) * 8 + (lane & 7)) * 144;
        #pragma unroll
        for (int j = 0; j < 4; j++) stsm4(ad + (lane >> 4) * 16 + j * 32, o[4 * j], o[4 * j + 1], o[4 * j + 2], o[4 * j + 3]);
        stsm2(ad + 128, o[16], o[17]);
        fence_async_smem();
        bar_arrive(4 + hh, 160);
    }
}

typedef CUresult (*EncFn)(CUtensorMap*, CUtensorMapDataType, cuuint32_t, void*, const cuuint64_t*, const cuuint64_t*, const cuuint32_t*,
                          const cuuint32_t*, CUtensorMapInterleave, CUtensorMapSwizzle, CUtensorMapL2promotion, CUtensorMapFloatOOBfill);

template <typename... KArgs, typename... Args>
static void launch(void (*kern)(KArgs...), dim3 grid, int block, int smem, bool pdl, Args... args) {
    cudaLaunchConfig_t cfg = {};
    cfg.gridDim = grid; cfg.blockDim = dim3(block); cfg.dynamicSmemBytes = smem; cfg.stream = cudaStreamPerThread;
    cudaLaunchAttribute at[1];
    at[0].id = cudaLaunchAttributeProgrammaticStreamSerialization; at[0].val.programmaticStreamSerializationAllowed = 1;
    cfg.attrs = at; cfg.numAttrs = pdl ? 1 : 0;
    cudaLaunchKernelEx(&cfg, kern, args...);
}

extern "C" void kernel_launch(void* const* d_in, const int* in_sizes, int n_in, void* d_out, int out_size) {
    const bf16* x = (const bf16*)d_in[0];
    const bf16* wqkv = (const bf16*)d_in[1];
    const bf16* wphi = (const bf16*)d_in[2];
    const bf16* wo = (const bf16*)d_in[3];
    const bf16* w1 = (const bf16*)d_in[5];
    const bf16* b1 = (const bf16*)d_in[6];
    const bf16* w2 = (const bf16*)d_in[7];
    const bf16* b2 = (const bf16*)d_in[8];
    static EncFn enc = nullptr;
    if (!enc) {
        void* fn = nullptr; cudaDriverEntryPointQueryResult qr;
        cudaGetDriverEntryPoint("cuTensorMapEncodeTiled", &fn, cudaEnableDefault, &qr);
        enc = (EncFn)fn;
        cudaFuncSetAttribute(ka_front, cudaFuncAttributeMaxDynamicSharedMemorySize, KA_SMEM);
        cudaFuncSetAttribute(k2_attn, cudaFuncAttributeMaxDynamicSharedMemorySize, K2_SMEM);
        cudaFuncSetAttribute(k3_mix1, cudaFuncAttributeMaxDynamicSharedMemorySize, K3_SMEM);
        cudaFuncSetAttribute(k4_mix2, cudaFuncAttributeMaxDynamicSharedMemorySize, K4_SMEM);
    }
    CUtensorMap tmW1, tmW1b, tmW2, tmOut, tmX, tmXA;
    const cuuint32_t es[3] = {1, 1, 1};
    {
        cuuint64_t dims[3] = {64, (cuuint64_t)S_, (cuuint64_t)(F_ / 64)}; cuuint64_t st[2] = {(cuuint64_t)F_ * 2, 128}; cuuint32_t box[3] = {64, 64, 2};
        enc(&tmW1, CU_TENSOR_MAP_DATA_TYPE_BFLOAT16, 3, (void*)w1, dims, st, box, es, CU_TENSOR_MAP_INTERLEAVE_NONE, CU_TENSOR_MAP_SWIZZLE_128B, CU_TENSOR_MAP_L2_PROMOTION_L2_128B, CU_TENSOR_MAP_FLOAT_OOB_FILL_NONE);
        box[2] = 3;
        enc(&tmW1b, CU_TENSOR_MAP_DATA_TYPE_BFLOAT16, 3, (void*)w1, dims, st, box, es, CU_TENSOR_MAP_INTERLEAVE_NONE, CU_TENSOR_MAP_SWIZZLE_128B, CU_TENSOR_MAP_L2_PROMOTION_L2_128B, CU_TENSOR_MAP_FLOAT_OOB_FILL_NONE);
    }
    {
        cuuint64_t dims[3] = {64, (cuuint64_t)F_, (cuuint64_t)(S_ / 64)}; cuuint64_t st[2] = {(cuuint64_t)S_ * 2, 128}; cuuint32_t box[3] = {64, 64, 1};
        enc(&tmW2, CU_TENSOR_MAP_DATA_TYPE_BFLOAT16, 3, (void*)w2, dims, st, box, es, CU_TENSOR_MAP_INTERLEAVE_NONE, CU_TENSOR_MAP_SWIZZLE_128B, CU_TENSOR_MAP_L2_PROMOTION_L2_128B, CU_TENSOR_MAP_FLOAT_OOB_FILL_NONE);
    }
    {
        cuuint64_t dims[2] = {(cuuint64_t)D_, (cuuint64_t)S_}; cuuint64_t st[1] = {(cuuint64_t)D_ * 2}; cuuint32_t box[2] = {72, 64};
        enc(&tmOut, CU_TENSOR_MAP_DATA_TYPE_BFLOAT16, 2, d_out, dims, st, box, es, CU_TENSOR_MAP_INTERLEAVE_NONE, CU_TENSOR_MAP_SWIZZLE_NONE, CU_TENSOR_MAP_L2_PROMOTION_NONE, CU_TENSOR_MAP_FLOAT_OOB_FILL_NONE);
        enc(&tmX, CU_TENSOR_MAP_DATA_TYPE_BFLOAT16, 2, (void*)x, dims, st, box, es, CU_TENSOR_MAP_INTERLEAVE_NONE, CU_TENSOR_MAP_SWIZZLE_NONE, CU_TENSOR_MAP_L2_PROMOTION_NONE, CU_TENSOR_MAP_FLOAT_OOB_FILL_NONE);
    }
    {
        cuuint64_t dims[3] = {64, (cuuint64_t)S_, 9}; cuuint64_t st[2] = {(cuuint64_t)D_ * 2, 128}; cuuint32_t box[3] = {64, 128, 1};
        enc(&tmXA, CU_TENSOR_MAP_DATA_TYPE_BFLOAT16, 3, (void*)x, dims, st, box, es, CU_TENSOR_MAP_INTERLEAVE_NONE, CU_TENSOR_MAP_SWIZZLE_128B, CU_TENSOR_MAP_L2_PROMOTION_L2_128B, CU_TENSOR_MAP_FLOAT_OOB_FILL_NONE);
    }
    launch(k0_prep, dim3(9, 8, 4), 256, 0, false, x, wqkv, wphi);
    launch(ka_front, 132, 640, KA_SMEM, true, tmXA, x, wo, w1, b1);
    launch(k2_attn, 128, 256, K2_SMEM, true, tmX, b2);
    launch(k3_mix1, 132, 352, K3_SMEM, true, tmW1, tmW1b, b1, w1, w2);
    launch(k4_mix2, 128, 288, K4_SMEM, true, tmW2, tmOut);
}
```

```cpp
#include <cuda_runtime.h>
#include <cuda.h>
#include <cuda_bf16.h>
#include <stdint.h>

typedef __nv_bfloat16 bf16;
#define DEVI __device__ __forceinline__

constexpr int S_ = 2048, D_ = 576, F_ = 4608;
constexpr float LN_EPS = 1e-5f;
constexpr float LOG2E = 1.4426950408889634f;

__device__ __align__(1024) bf16 g_o[S_ * D_];
__device__ __align__(1024) bf16 g_wqkv[8 * 27 * 72 * 64];
__device__ __align__(16) float g_cs[8 * 18 * 216];
__device__ __align__(1024) bf16 g_wo[8 * 72 * 72 * 8];
constexpr int KV_H = 960;
constexpr int PQ_UNIT = 1168;
__device__ __align__(1024) float g_kv[32 * KV_H];
__device__ __align__(1024) unsigned long long g_stats[S_ * 8];
__device__ __align__(16) unsigned long long g_ln[S_];
__device__ __align__(16) float2 g_rc[S_];
__device__ __align__(1024) bf16 g_hnT[D_ * S_];
__device__ __align__(1024) bf16 g_u[D_ * F_];
constexpr int CNT_S = 64;
__device__ __align__(256) unsigned int g_cnt[8 * CNT_S];

DEVI uint32_t smem_u32(const void* p) { return (uint32_t)__cvta_generic_to_shared(p); }
DEVI void mbar_init(uint32_t bar, int cnt) { asm volatile("mbarrier.init.shared::cta.b64 [%0], %1;" :: "r"(bar), "r"(cnt) : "memory"); }
DEVI void mbar_expect(uint32_t bar, uint32_t bytes) { asm volatile("mbarrier.arrive.expect_tx.shared::cta.b64 _, [%0], %1;" :: "r"(bar), "r"(bytes) : "memory"); }
DEVI void mbar_wait(uint32_t bar, uint32_t parity) {
    asm volatile("{\n.reg .pred p;\n.reg .u32 it;\n"
                 "mbarrier.try_wait.parity.shared::cta.b64 p, [%0], %1;\n@p bra MW_DONE;\n"
                 "mov.u32 it, 0;\n"
                 "MW_LOOP:\nmbarrier.try_wait.parity.shared::cta.b64 p, [%0], %1;\n@p bra MW_DONE;\n"
                 "add.u32 it, it, 1;\nsetp.lt.u32 p, it, 4194304;\n@p bra MW_LOOP;\ntrap;\n"
                 "MW_DONE:\n}" :: "r"(bar), "r"(parity) : "memory");
}
DEVI void mbar_arrive(uint32_t bar) { asm volatile("mbarrier.arrive.shared::cta.b64 _, [%0];" :: "r"(bar) : "memory"); }
DEVI uint32_t mapa(uint32_t addr, uint32_t cta) { uint32_t r; asm volatile("mapa.shared::cluster.u32 %0, %1, %2;" : "=r"(r) : "r"(addr), "r"(cta)); return r; }
DEVI void mbar_arrive_remote(uint32_t raddr) { asm volatile("mbarrier.arrive.shared::cluster.b64 _, [%0];" :: "r"(raddr) : "memory"); }
DEVI void fence_mbar_init() { asm volatile("fence.mbarrier_init.release.cluster;" ::: "memory"); }
DEVI void fence_async_smem() { asm volatile("fence.proxy.async.shared::cta;" ::: "memory"); }
DEVI void cluster_arrive_relaxed() { asm volatile("barrier.cluster.arrive.relaxed.aligned;" ::: "memory"); }
DEVI void cluster_wait() { asm volatile("barrier.cluster.wait.aligned;" ::: "memory"); }
DEVI void bar_sync(int id, int n) { asm volatile("bar.sync %0, %1;" :: "r"(id), "r"(n) : "memory"); }
DEVI void bar_arrive(int id, int n) { asm volatile("bar.arrive %0, %1;" :: "r"(id), "r"(n) : "memory"); }
DEVI void pdl_wait() { asm volatile("griddepcontrol.wait;" ::: "memory"); }
DEVI void pdl_trigger() { asm volatile("griddepcontrol.launch_dependents;" ::: "memory"); }
DEVI void bulk_g2s(uint32_t dst, const void* src, uint32_t bytes, uint32_t bar) {
    asm volatile("cp.async.bulk.shared::cluster.global.mbarrier::complete_tx::bytes [%0], [%1], %2, [%3];" :: "r"(dst), "l"(src), "r"(bytes), "r"(bar) : "memory");
}
DEVI void bulk_s2g(void* dst, uint32_t src, uint32_t bytes) {
    asm volatile("cp.async.bulk.global.shared::cta.bulk_group [%0], [%1], %2;" :: "l"(dst), "r"(src), "r"(bytes) : "memory");
}
DEVI void l2_prefetch(const void* p, uint32_t bytes) { asm volatile("cp.async.bulk.prefetch.L2.global [%0], %1;" :: "l"(p), "r"(bytes) : "memory"); }
DEVI void bulk_commit() { asm volatile("cp.async.bulk.commit_group;" ::: "memory"); }
DEVI void bulk_wait_read() { asm volatile("cp.async.bulk.wait_group.read 0;" ::: "memory"); }
DEVI void tma2d(uint32_t dst, const CUtensorMap* tm, uint32_t bar, int c0, int c1) {
    asm volatile("cp.async.bulk.tensor.2d.shared::cluster.global.mbarrier::complete_tx::bytes [%0], [%1, {%3, %4}], [%2];" :: "r"(dst), "l"(tm), "r"(bar), "r"(c0), "r"(c1) : "memory");
}
DEVI void tma3d(uint32_t dst, const CUtensorMap* tm, uint32_t bar, int c0, int c1, int c2) {
    asm volatile("cp.async.bulk.tensor.3d.shared::cluster.global.mbarrier::complete_tx::bytes [%0], [%1, {%3, %4, %5}], [%2];" :: "r"(dst), "l"(tm), "r"(bar), "r"(c0), "r"(c1), "r"(c2) : "memory");
}
DEVI void tma3d_prefetch(const CUtensorMap* tm, int c0, int c1, int c2) {
    asm volatile("cp.async.bulk.prefetch.tensor.3d.L2.global [%0, {%1, %2, %3}];" :: "l"(tm), "r"(c0), "r"(c1), "r"(c2) : "memory");
}
DEVI void tma2d_store(const CUtensorMap* tm, uint32_t src, int c0, int c1) {
    asm volatile("cp.async.bulk.tensor.2d.global.shared::cta.bulk_group [%0, {%2, %3}], [%1];" :: "l"(tm), "r"(src), "r"(c0), "r"(c1) : "memory");
}
DEVI void prefetch_tm(const CUtensorMap* tm) { asm volatile("prefetch.tensormap [%0];" :: "l"(tm) : "memory"); }
DEVI uint64_t mkdesc(uint32_t addr, uint32_t lbo, uint32_t sbo, uint64_t swz) {
    return (uint64_t)((addr & 0x3FFFF) >> 4) | ((uint64_t)(lbo >> 4) << 16) | ((uint64_t)(sbo >> 4) << 32) | (swz << 62);
}
DEVI uint64_t dadv(uint64_t d, uint32_t bytes) { return (d & 0xffffffff00000000ull) | (uint64_t)((uint32_t)d + (bytes >> 4)); }
DEVI void wg_fence() { asm volatile("wgmma.fence.sync.aligned;" ::: "memory"); }
DEVI void wg_commit() { asm volatile("wgmma.commit_group.sync.aligned;" ::: "memory"); }
template<int N> DEVI void wg_wait() { asm volatile("wgmma.wait_group.sync.aligned %0;" :: "n"(N) : "memory"); }
template<int N> DEVI void reg_fence(float* d) {
    #pragma unroll
    for (int i = 0; i < N; i++) asm volatile("" : "+f"(d[i]) :: "memory");
}
DEVI uint32_t pack2(float lo, float hi) { uint32_t r; asm("cvt.rn.bf16x2.f32 %0, %1, %2;" : "=r"(r) : "f"(hi), "f"(lo)); return r; }
DEVI float bf_lo(uint32_t v) { return __uint_as_float(v << 16); }
DEVI float bf_hi(uint32_t v) { return __uint_as_float(v & 0xffff0000u); }
DEVI float ex2(float x) { float r; asm("ex2.approx.ftz.f32 %0, %1;" : "=f"(r) : "f"(x)); return r; }
DEVI float rcp(float x) { float r; asm("rcp.approx.ftz.f32 %0, %1;" : "=f"(r) : "f"(x)); return r; }
DEVI float rcp_full(float x) { float r; asm("rcp.approx.f32 %0, %1;" : "=f"(r) : "f"(x)); return r; }
DEVI float tanh_fast(float x) { float r; asm("tanh.approx.f32 %0, %1;" : "=f"(r) : "f"(x)); return r; }
DEVI void mma16816(float* c, uint32_t a0, uint32_t a1, uint32_t a2, uint32_t a3, uint32_t b0, uint32_t b1) {
    asm("mma.sync.aligned.m16n8k16.row.col.f32.bf16.bf16.f32 {%0,%1,%2,%3}, {%4,%5,%6,%7}, {%8,%9}, {%0,%1,%2,%3};"
        : "+f"(c[0]), "+f"(c[1]), "+f"(c[2]), "+f"(c[3]) : "r"(a0), "r"(a1), "r"(a2), "r"(a3), "r"(b0), "r"(b1));
}
DEVI void mma1688(float* c, uint32_t a0, uint32_t a1, uint32_t b0) {
    asm("mma.sync.aligned.m16n8k8.row.col.f32.bf16.bf16.f32 {%0,%1,%2,%3}, {%4,%5}, {%6}, {%0,%1,%2,%3};"
        : "+f"(c[0]), "+f"(c[1]), "+f"(c[2]), "+f"(c[3]) : "r"(a0), "r"(a1), "r"(b0));
}
DEVI void ldsm4t(uint32_t addr, uint32_t& r0, uint32_t& r1, uint32_t& r2, uint32_t& r3) {
    asm volatile("ldmatrix.sync.aligned.m8n8.x4.trans.shared.b16 {%0,%1,%2,%3}, [%4];" : "=r"(r0), "=r"(r1), "=r"(r2), "=r"(r3) : "r"(addr) : "memory");
}
DEVI void stsm4t(uint32_t addr, uint32_t r0, uint32_t r1, uint32_t r2, uint32_t r3) {
    asm volatile("stmatrix.sync.aligned.m8n8.x4.trans.shared.b16 [%0], {%1,%2,%3,%4};" :: "r"(addr), "r"(r0), "r"(r1), "r"(r2), "r"(r3) : "memory");
}
DEVI void stsm2t(uint32_t addr, uint32_t r0, uint32_t r1) {
    asm volatile("stmatrix.sync.aligned.m8n8.x2.trans.shared.b16 [%0], {%1,%2};" :: "r"(addr), "r"(r0), "r"(r1) : "memory");
}
DEVI void stsm4(uint32_t addr, uint32_t r0, uint32_t r1, uint32_t r2, uint32_t r3) {
    asm volatile("stmatrix.sync.aligned.m8n8.x4.shared.b16 [%0], {%1,%2,%3,%4};" :: "r"(addr), "r"(r0), "r"(r1), "r"(r2), "r"(r3) : "memory");
}
DEVI void stsm2(uint32_t addr, uint32_t r0, uint32_t r1) {
    asm volatile("stmatrix.sync.aligned.m8n8.x2.shared.b16 [%0], {%1,%2};" :: "r"(addr), "r"(r0), "r"(r1) : "memory");
}
DEVI void sts128(uint32_t addr, uint32_t r0, uint32_t r1, uint32_t r2, uint32_t r3) {
    asm volatile("st.shared.v4.b32 [%0], {%1,%2,%3,%4};" :: "r"(addr), "r"(r0), "r"(r1), "r"(r2), "r"(r3) : "memory");
}
DEVI uint32_t lds32(uint32_t addr) { uint32_t r; asm volatile("ld.shared.b32 %0, [%1];" : "=r"(r) : "r"(addr) : "memory"); return r; }
DEVI void sts32(uint32_t addr, uint32_t r0) { asm volatile("st.shared.b32 [%0], %1;" :: "r"(addr), "r"(r0) : "memory"); }
template<int TA, int TB> DEVI void wgmma_n40(float* d, uint64_t da, uint64_t db, int sd) {
  asm volatile("{\n.reg .pred p;\nsetp.ne.b32 p, %22, 0;\n"
    "wgmma.mma_async.sync.aligned.m64n40k16.f32.bf16.bf16 {%0, %1, %2, %3, %4, %5, %6, %7, %8, %9, %10, %11, %12, %13, %14, %15, %16, %17, %18, %19}, %20, %21, p, 1, 1, %23, %24;\n}\n"
    : "+f"(d[0]), "+f"(d[1]), "+f"(d[2]), "+f"(d[3]), "+f"(d[4]), "+f"(d[5]), "+f"(d[6]), "+f"(d[7]), "+f"(d[8]), "+f"(d[9]), "+f"(d[10]), "+f"(d[11]), "+f"(d[12]), "+f"(d[13]), "+f"(d[14]), "+f"(d[15]), "+f"(d[16]), "+f"(d[17]), "+f"(d[18]), "+f"(d[19]) : "l"(da), "l"(db), "r"(sd), "n"(TA), "n"(TB));
}
template<int TA, int TB> DEVI void wgmma_n48(float* d, uint64_t da, uint64_t db, int sd) {
  asm volatile("{\n.reg .pred p;\nsetp.ne.b32 p, %26, 0;\n"
    "wgmma.mma_async.sync.aligned.m64n48k16.f32.bf16.bf16 {%0, %1, %2, %3, %4, %5, %6, %7, %8, %9, %10, %11, %12, %13, %14, %15, %16, %17, %18, %19, %20, %21, %22, %23}, %24, %25, p, 1, 1, %27, %28;\n}\n"
    : "+f"(d[0]), "+f"(d[1]), "+f"(d[2]), "+f"(d[3]), "+f"(d[4]), "+f"(d[5]), "+f"(d[6]), "+f"(d[7]), "+f"(d[8]), "+f"(d[9]), "+f"(d[10]), "+f"(d[11]), "+f"(d[12]), "+f"(d[13]), "+f"(d[14]), "+f"(d[15]), "+f"(d[16]), "+f"(d[17]), "+f"(d[18]), "+f"(d[19]), "+f"(d[20]), "+f"(d[21]), "+f"(d[22]), "+f"(d[23]) : "l"(da), "l"(db), "r"(sd), "n"(TA), "n"(TB));
}
template<int TA, int TB> DEVI void wgmma_n72(float* d, uint64_t da, uint64_t db, int sd) {
  asm volatile("{\n.reg .pred p;\nsetp.ne.b32 p, %38, 0;\n"
    "wgmma.mma_async.sync.aligned.m64n72k16.f32.bf16.bf16 {%0, %1, %2, %3, %4, %5, %6, %7, %8, %9, %10, %11, %12, %13, %14, %15, %16, %17, %18, %19, %20, %21, %22, %23, %24, %25, %26, %27, %28, %29, %30, %31, %32, %33, %34, %35}, %36, %37, p, 1, 1, %39, %40;\n}\n"
    : "+f"(d[0]), "+f"(d[1]), "+f"(d[2]), "+f"(d[3]), "+f"(d[4]), "+f"(d[5]), "+f"(d[6]), "+f"(d[7]), "+f"(d[8]), "+f"(d[9]), "+f"(d[10]), "+f"(d[11]), "+f"(d[12]), "+f"(d[13]), "+f"(d[14]), "+f"(d[15]), "+f"(d[16]), "+f"(d[17]), "+f"(d[18]), "+f"(d[19]), "+f"(d[20]), "+f"(d[21]), "+f"(d[22]), "+f"(d[23]), "+f"(d[24]), "+f"(d[25]), "+f"(d[26]), "+f"(d[27]), "+f"(d[28]), "+f"(d[29]), "+f"(d[30]), "+f"(d[31]), "+f"(d[32]), "+f"(d[33]), "+f"(d[34]), "+f"(d[35]) : "l"(da), "l"(db), "r"(sd), "n"(TA), "n"(TB));
}
template<int TA, int TB> DEVI void wgmma_n96(float* d, uint64_t da, uint64_t db, int sd) {
  asm volatile("{\n.reg .pred p;\nsetp.ne.b32 p, %50, 0;\n"
    "wgmma.mma_async.sync.aligned.m64n96k16.f32.bf16.bf16 {%0, %1, %2, %3, %4, %5, %6, %7, %8, %9, %10, %11, %12, %13, %14, %15, %16, %17, %18, %19, %20, %21, %22, %23, %24, %25, %26, %27, %28, %29, %30, %31, %32, %33, %34, %35, %36, %37, %38, %39, %40, %41, %42, %43, %44, %45, %46, %47}, %48, %49, p, 1, 1, %51, %52;\n}\n"
    : "+f"(d[0]), "+f"(d[1]), "+f"(d[2]), "+f"(d[3]), "+f"(d[4]), "+f"(d[5]), "+f"(d[6]), "+f"(d[7]), "+f"(d[8]), "+f"(d[9]), "+f"(d[10]), "+f"(d[11]), "+f"(d[12]), "+f"(d[13]), "+f"(d[14]), "+f"(d[15]), "+f"(d[16]), "+f"(d[17]), "+f"(d[18]), "+f"(d[19]), "+f"(d[20]), "+f"(d[21]), "+f"(d[22]), "+f"(d[23]), "+f"(d[24]), "+f"(d[25]), "+f"(d[26]), "+f"(d[27]), "+f"(d[28]), "+f"(d[29]), "+f"(d[30]), "+f"(d[31]), "+f"(d[32]), "+f"(d[33]), "+f"(d[34]), "+f"(d[35]), "+f"(d[36]), "+f"(d[37]), "+f"(d[38]), "+f"(d[39]), "+f"(d[40]), "+f"(d[41]), "+f"(d[42]), "+f"(d[43]), "+f"(d[44]), "+f"(d[45]), "+f"(d[46]), "+f"(d[47]) : "l"(da), "l"(db), "r"(sd), "n"(TA), "n"(TB));
}
template<int TA, int TB> DEVI void wgmma_n144(float* d, uint64_t da, uint64_t db, int sd) {
  asm volatile("{\n.reg .pred p;\nsetp.ne.b32 p, %74, 0;\n"
    "wgmma.mma_async.sync.aligned.m64n144k16.f32.bf16.bf16 {%0, %1, %2, %3, %4, %5, %6, %7, %8, %9, %10, %11, %12, %13, %14, %15, %16, %17, %18, %19, %20, %21, %22, %23, %24, %25, %26, %27, %28, %29, %30, %31, %32, %33, %34, %35, %36, %37, %38, %39, %40, %41, %42, %43, %44, %45, %46, %47, %48, %49, %50, %51, %52, %53, %54, %55, %56, %57, %58, %59, %60, %61, %62, %63, %64, %65, %66, %67, %68, %69, %70, %71}, %72, %73, p, 1, 1, %75, %76;\n}\n"
    : "+f"(d[0]), "+f"(d[1]), "+f"(d[2]), "+f"(d[3]), "+f"(d[4]), "+f"(d[5]), "+f"(d[6]), "+f"(d[7]), "+f"(d[8]), "+f"(d[9]), "+f"(d[10]), "+f"(d[11]), "+f"(d[12]), "+f"(d[13]), "+f"(d[14]), "+f"(d[15]), "+f"(d[16]), "+f"(d[17]), "+f"(d[18]), "+f"(d[19]), "+f"(d[20]), "+f"(d[21]), "+f"(d[22]), "+f"(d[23]), "+f"(d[24]), "+f"(d[25]), "+f"(d[26]), "+f"(d[27]), "+f"(d[28]), "+f"(d[29]), "+f"(d[30]), "+f"(d[31]), "+f"(d[32]), "+f"(d[33]), "+f"(d[34]), "+f"(d[35]), "+f"(d[36]), "+f"(d[37]), "+f"(d[38]), "+f"(d[39]), "+f"(d[40]), "+f"(d[41]), "+f"(d[42]), "+f"(d[43]), "+f"(d[44]), "+f"(d[45]), "+f"(d[46]), "+f"(d[47]), "+f"(d[48]), "+f"(d[49]), "+f"(d[50]), "+f"(d[51]), "+f"(d[52]), "+f"(d[53]), "+f"(d[54]), "+f"(d[55]), "+f"(d[56]), "+f"(d[57]), "+f"(d[58]), "+f"(d[59]), "+f"(d[60]), "+f"(d[61]), "+f"(d[62]), "+f"(d[63]), "+f"(d[64]), "+f"(d[65]), "+f"(d[66]), "+f"(d[67]), "+f"(d[68]), "+f"(d[69]), "+f"(d[70]), "+f"(d[71]) : "l"(da), "l"(db), "r"(sd), "n"(TA), "n"(TB));
}
template<int TA, int TB> DEVI void wgmma_n160(float* d, uint64_t da, uint64_t db, int sd) {
  asm volatile("{\n.reg .pred p;\nsetp.ne.b32 p, %82, 0;\n"
    "wgmma.mma_async.sync.aligned.m64n160k16.f32.bf16.bf16 {%0, %1, %2, %3, %4, %5, %6, %7, %8, %9, %10, %11, %12, %13, %14, %15, %16, %17, %18, %19, %20, %21, %22, %23, %24, %25, %26, %27, %28, %29, %30, %31, %32, %33, %34, %35, %36, %37, %38, %39, %40, %41, %42, %43, %44, %45, %46, %47, %48, %49, %50, %51, %52, %53, %54, %55, %56, %57, %58, %59, %60, %61, %62, %63, %64, %65, %66, %67, %68, %69, %70, %71, %72, %73, %74, %75, %76, %77, %78, %79}, %80, %81, p, 1, 1, %83, %84;\n}\n"
    : "+f"(d[0]), "+f"(d[1]), "+f"(d[2]), "+f"(d[3]), "+f"(d[4]), "+f"(d[5]), "+f"(d[6]), "+f"(d[7]), "+f"(d[8]), "+f"(d[9]), "+f"(d[10]), "+f"(d[11]), "+f"(d[12]), "+f"(d[13]), "+f"(d[14]), "+f"(d[15]), "+f"(d[16]), "+f"(d[17]), "+f"(d[18]), "+f"(d[19]), "+f"(d[20]), "+f"(d[21]), "+f"(d[22]), "+f"(d[23]), "+f"(d[24]), "+f"(d[25]), "+f"(d[26]), "+f"(d[27]), "+f"(d[28]), "+f"(d[29]), "+f"(d[30]), "+f"(d[31]), "+f"(d[32]), "+f"(d[33]), "+f"(d[34]), "+f"(d[35]), "+f"(d[36]), "+f"(d[37]), "+f"(d[38]), "+f"(d[39]), "+f"(d[40]), "+f"(d[41]), "+f"(d[42]), "+f"(d[43]), "+f"(d[44]), "+f"(d[45]), "+f"(d[46]), "+f"(d[47]), "+f"(d[48]), "+f"(d[49]), "+f"(d[50]), "+f"(d[51]), "+f"(d[52]), "+f"(d[53]), "+f"(d[54]), "+f"(d[55]), "+f"(d[56]), "+f"(d[57]), "+f"(d[58]), "+f"(d[59]), "+f"(d[60]), "+f"(d[61]), "+f"(d[62]), "+f"(d[63]), "+f"(d[64]), "+f"(d[65]), "+f"(d[66]), "+f"(d[67]), "+f"(d[68]), "+f"(d[69]), "+f"(d[70]), "+f"(d[71]), "+f"(d[72]), "+f"(d[73]), "+f"(d[74]), "+f"(d[75]), "+f"(d[76]), "+f"(d[77]), "+f"(d[78]), "+f"(d[79]) : "l"(da), "l"(db), "r"(sd), "n"(TA), "n"(TB));
}

__host__ __device__ constexpr int ka_seq(int p, int c) { return p == 0 ? c : c >= 5 ? 2 * c - 2 + p : p == 1 ? 17 + c : 22 + c; }
__global__ void __launch_bounds__(256, 3) k0_prep(const bf16* __restrict__ x, const bf16* __restrict__ wqkv, const bf16* __restrict__ wphi) {
    __shared__ __align__(16) uint32_t s_in[64 * 36 + 64];
    pdl_trigger();
    const int tid = threadIdx.x, lane = tid & 31, warp = __shfl_sync(~0u, tid >> 5, 0);
    const int c = blockIdx.x, g = blockIdx.y, p = blockIdx.z;
    const bool fold = p == 0 || p == 2;
    const int b = (p * 8 + g) * 9 + c;
    if (p == 3) {
        const int j = b - 216;
        const uint4 z = make_uint4(0u, 0u, 0u, 0u);
        if (j < 32) reinterpret_cast<uint4*>(g_stats)[j * 256 + tid] = z;
        else if (j < 62) reinterpret_cast<uint4*>(g_kv)[(j - 32) * 256 + tid] = z;
        else if (j == 66 && tid < 8) g_cnt[tid * CNT_S] = 0u;
        return;
    }
    constexpr int ld = 1728;
    const bf16* src = wqkv + ((p == 2 ? 0 : p + 1) * 576 + c * 64 * ld + g * 72);
    const uint32_t si = smem_u32(s_in);
    #pragma unroll
    for (int j = 0; j < 3; j++) {
        const int i = tid + j * 256, r = (i * 7282) >> 16;
        if (j < 2 || tid < 64) asm volatile("cp.async.cg.shared.global [%0], [%1], 16;" :: "r"(si + i * 16 + (r >> 3) * 32), "l"(src + (r * (ld - 72) + i * 8)) : "memory");
    }
    const int t = warp & 3, half = warp >> 2, g8 = lane >> 2, c4 = lane & 3;
    uint32_t af[3][3];
    if (fold) {
        const unsigned short* ph = reinterpret_cast<const unsigned short*>(wphi) + (g * 4 + t) * 324;
        unsigned short lo[3][3], hi[3][3];
        #pragma unroll
        for (int fb = 0; fb < 3; fb++)
            #pragma unroll
            for (int db = 0; db < 3; db++) {
                const int o = min(2 * c4 + 8 * db, 16) * 18 + min(g8 + 8 * fb, 17);
                lo[fb][db] = __ldg(ph + o); hi[fb][db] = __ldg(ph + o + 18);
            }
        #pragma unroll
        for (int fb = 0; fb < 3; fb++)
            #pragma unroll
            for (int db = 0; db < 3; db++) af[fb][db] = (uint32_t)lo[fb][db] | ((uint32_t)hi[fb][db] << 16);
    } else {
        const uint32_t v = (g8 == 2 * c4 ? 0x3f80u : 0u) | (g8 == 2 * c4 + 1 ? 0x3f800000u : 0u);
        #pragma unroll
        for (int fb = 0; fb < 3; fb++)
            #pragma unroll
            for (int db = 0; db < 3; db++) af[fb][db] = fb == db ? v : 0u;
    }
    bf16* dst = g_wqkv + (g * 27 + ka_seq(p, c)) * 4608;
    float* csd = g_cs + (g * 18 + c * 2 + half) * 216 + p * 72 + 2 * t;
    asm volatile("cp.async.wait_all;" ::: "memory");
    __syncthreads();
    if (tid < 96 && b < 192) asm volatile("prefetch.global.L2 [%0];" :: "l"(x + b * 6144 + tid * 64));
    uint32_t ov[3][4];
    const uint32_t* wr = &s_in[(half * 32 + (g8 >> 1) * 8 + (g8 & 1)) * 36 + (half * 4 + (g8 >> 1)) * 8 + t * 9 + c4];
    #pragma unroll
    for (int j = 0; j < 4; j++) {
        const uint32_t b0 = wr[j * 72], b1 = wr[j * 72 + 4], b2 = c4 == 0 ? wr[j * 72 + 8] : 0u;
        float c0[4] = {0.f, 0.f, 0.f, 0.f}, c1[4] = {0.f, 0.f, 0.f, 0.f};
        mma16816(c0, af[0][0], af[1][0], af[0][1], af[1][1], b0, b1);
        mma1688(c0, af[0][2], af[1][2], b2);
        mma16816(c1, af[2][0], 0u, af[2][1], 0u, b0, b1);
        mma1688(c1, af[2][2], 0u, b2);
        ov[0][j] = pack2(c0[0], c0[1]); ov[1][j] = pack2(c0[2], c0[3]); ov[2][j] = pack2(c1[0], c1[1]);
    }
    {
        const int nl = 2 * t + (g8 & 1);
        uint4* o = reinterpret_cast<uint4*>(dst) + ((g8 >> 1) * 8 + nl) * 8 + ((half * 4 + c4) ^ nl);
        o[0] = make_uint4(ov[0][0], ov[0][1], ov[0][2], ov[0][3]);
        o[256] = make_uint4(ov[1][0], ov[1][1], ov[1][2], ov[1][3]);
        if (g8 < 2) o[512] = make_uint4(ov[2][0], ov[2][1], ov[2][2], ov[2][3]);
    }
    {
        float cs0[4] = {0.f, 0.f, 0.f, 0.f}, cs1[4] = {0.f, 0.f, 0.f, 0.f};
        mma16816(cs0, ov[0][0], ov[1][0], ov[0][1], ov[1][1], 0x3f803f80u, 0x3f803f80u);
        mma16816(cs1, ov[2][0], 0u, ov[2][1], 0u, 0x3f803f80u, 0x3f803f80u);
        mma16816(cs0, ov[0][2], ov[1][2], ov[0][3], ov[1][3], 0x3f803f80u, 0x3f803f80u);
        mma16816(cs1, ov[2][2], 0u, ov[2][3], 0u, 0x3f803f80u, 0x3f803f80u);
        const int f = g8 + 8 * c4;
        if (f < 18) csd[8 * (f >> 1) + (f & 1)] = c4 == 0 ? cs0[0] : c4 == 1 ? cs0[2] : cs1[0];
    }
}

DEVI void dual_softmax(const float* a, float scale, uint32_t* o) {
    float mx = a[0], mn = a[0];
    #pragma unroll
    for (int j = 1; j < 18; j++) { mx = fmaxf(mx, a[j]); mn = fminf(mn, a[j]); }
    const float mxs = -mx * scale, mns = mn * scale;
    float ep[18], en[18], sp = 0.f, sn = 0.f;
    #pragma unroll
    for (int j = 0; j < 18; j++) {
        ep[j] = ex2(fmaf(a[j], scale, mxs)); sp += ep[j];
        en[j] = ex2(fmaf(a[j], -scale, mns)); sn += en[j];
    }
    const float rp = rcp(sp), rn = rcp(sn);
    #pragma unroll
    for (int j = 0; j < 9; j++) {
        o[j] = pack2(ep[2 * j] * rp, ep[2 * j + 1] * rp);
        o[9 + j] = pack2(en[2 * j] * rn, en[2 * j + 1] * rn);
    }
}

DEVI uint4 ldg128(const void* p) { uint4 v; asm volatile("ld.global.cg.v4.u32 {%0,%1,%2,%3}, [%4];" : "=r"(v.x), "=r"(v.y), "=r"(v.z), "=r"(v.w) : "l"(p)); return v; }
DEVI uint2 ldg64(const void* p) { uint2 v; asm volatile("ld.global.cg.v2.u32 {%0,%1}, [%2];" : "=r"(v.x), "=r"(v.y) : "l"(p)); return v; }
DEVI uint4 lds128(uint32_t a) { uint4 v; asm volatile("ld.shared.v4.u32 {%0,%1,%2,%3}, [%4];" : "=r"(v.x), "=r"(v.y), "=r"(v.z), "=r"(v.w) : "r"(a) : "memory"); return v; }
DEVI uint2 lds64(uint32_t a) { uint2 v; asm volatile("ld.shared.v2.u32 {%0,%1}, [%2];" : "=r"(v.x), "=r"(v.y) : "r"(a) : "memory"); return v; }
DEVI uint32_t packu(uint32_t lo, uint32_t hi) { return pack2(__uint_as_float(lo), __uint_as_float(hi)); }
DEVI void cp16(uint32_t dst, const void* src) { asm volatile("cp.async.cg.shared.global [%0], [%1], 16;" :: "r"(dst), "l"(src) : "memory"); }
DEVI void spin_ge(const unsigned int* p, unsigned int n) {
    uint32_t f; int it = 0;
    do {
        asm volatile("ld.acquire.gpu.global.u32 %0, [%1];" : "=r"(f) : "l"(p) : "memory");
        if (++it > (1 << 22)) __trap();
    } while (f < n);
}
constexpr int KA_PRE = 3, KA_REC = 5 * 16384, KA_B = 147456, KA_CS = KA_B + 9 * 9216, KA_LN = KA_CS + 864, KA_BAR = KA_LN + 1024, KA_SMEM = KA_BAR + 160;
static_assert(KA_SMEM <= 232448, "smem");
DEVI int gpc_pos() {
    unsigned smid, nsm;
    asm volatile("mov.u32 %0, %%smid;" : "=r"(smid));
    asm volatile("mov.u32 %0, %%nsmid;" : "=r"(nsm));
    if (nsm != 132) return blockIdx.x;
    const int tpc = smid >> 1, o = smid & 1;
    if (tpc < 32) return (tpc & 7) * 16 + (tpc >> 3) * 2 + o;
    if (tpc < 60) { const int j = tpc - 32, r = j / 7; return (1 + j - r * 7) * 16 + 8 + r * 2 + o; }
    if (tpc < 62) return 128 + (tpc - 60) * 2 + o;
    return 8 + (tpc - 62) * 2 + o;
}
__global__ void __launch_bounds__(640, 1) ka_front(const __grid_constant__ CUtensorMap tmXA, const bf16* __restrict__ x, const bf16* __restrict__ wo, const bf16* __restrict__ w1, const bf16* __restrict__ b1) {
    extern __shared__ __align__(1024) char smem[];
    const uint32_t sm = smem_u32(smem);
    const uint32_t bFull = sm + KA_BAR, bEmpty = bFull + 9 * 8, bLn = bEmpty + 9 * 8;
    const int tid = threadIdx.x, lane = tid & 31, warp = __shfl_sync(~0u, tid >> 5, 0);
    const int pos = gpc_pos();
    if (pos >= 128) {
        const int ns = pos - 128;
        if (tid < 576) {
            const int r0 = tid / 18, ch = tid - r0 * 18;
            #pragma unroll
            for (int j = 0; j < 18; j++) cp16(sm + (j * 32 + r0) * 304 + ch * 16, wo + (j * 32 + r0) * 576 + ns * 144 + ch * 8);
        }
        asm volatile("cp.async.wait_all;" ::: "memory");
        #pragma unroll 1
        for (int q = 0; q < 6; q++) {
            const uint32_t ob = sm + 175104 + (q & 1) * 27648;
            if (tid == 0) asm volatile("cp.async.bulk.wait_group.read 1;" ::: "memory");
            __syncthreads();
            if (warp < 18) {
                #pragma unroll
                for (int rb = 0; rb < 3; rb++) {
                    uint32_t r0, r1, r2, r3;
                    ldsm4t(sm + (q * 96 + rb * 32 + lane) * 304 + warp * 16, r0, r1, r2, r3);
                    stsm4(ob + (warp / 9) * 13824 + ((rb * 4 + (lane >> 3)) * 72 + (warp % 9) * 8 + (lane & 7)) * 16, r0, r1, r2, r3);
                }
            }
            fence_async_smem();
            __syncthreads();
            if (tid == 0) {
                bulk_s2g(g_wo + (ns * 2) * (72 * 576) + q * 6912, ob, 13824);
                bulk_s2g(g_wo + (ns * 2 + 1) * (72 * 576) + q * 6912, ob + 13824, 13824);
                bulk_commit();
            }
        }
        if (tid == 0) {
            asm volatile("cp.async.bulk.wait_group 0;\nfence.proxy.async.global;\nfence.acq_rel.gpu;" ::: "memory");
            pdl_wait();
            pdl_trigger();
        }
        return;
    }
    const int g = ((pos >> 4) & 1) * 4 + (pos & 3), mt = (pos >> 5) * 4 + ((pos >> 2) & 3);
    if (warp >= 16) {
        asm volatile("setmaxnreg.dec.sync.aligned.u32 32;");
        if (warp == 16) {
            if (lane == 0) {
                #pragma unroll
                for (int c = 0; c < 9; c++) { mbar_init(bFull + c * 8, 1); mbar_init(bEmpty + c * 8, 8); }
                mbar_init(bLn, 64);
                fence_mbar_init();
            }
            __syncwarp();
            bar_arrive(0, 640);
        } else {
            bar_sync(0, 640);
            if (tid == 544) {
                #pragma unroll
                for (int c = 0; c < 9; c++) mbar_expect(bFull + c * 8, 16384 + 9216);
            }
            __syncwarp();
        }
        if (tid == 512) {
            #pragma unroll
            for (int c = 0; c < KA_PRE; c++) tma3d(sm + c * 16384, &tmXA, bFull + c * 8, 0, mt * 128, c);
            pdl_wait();
            const bf16* wsrc = g_wqkv + g * (27 * 4608);
            const uint32_t sb = sm + KA_B;
            #pragma unroll
            for (int c = 0; c < 9; c++) {
                bulk_g2s(sb + c * 9216, wsrc + c * 4608, 9216, bFull + c * 8);
                const int xc = c + KA_PRE - 2;
                if (c >= 2 && xc < 9) tma3d(sm + xc * 16384, &tmXA, bFull + xc * 8, 0, mt * 128, xc);
            }
            pdl_trigger();
            #pragma unroll 1
            for (int p = 1; p < 3; p++) {
                #pragma unroll
                for (int c = 0; c < 9; c++) {
                    mbar_wait(bEmpty + c * 8, p - 1); mbar_expect(bFull + c * 8, 9216);
                    bulk_g2s(sb + c * 9216, wsrc + (p * 9 + c) * 4608, 9216, bFull + c * 8);
                }
            }
            l2_prefetch(w1 + pos * 13824, 27648);
            if (pos == 0) l2_prefetch(b1, 9216);
        } else if (warp == 17) {
            bar_sync(2, 160);
            if (lane == 0) spin_ge(g_cnt + g * CNT_S, 64);
            __syncwarp();
            bar_arrive(1, 288);
        } else if (warp >= 18) {
            const int m = warp - 18;
            {
                const unsigned long long* lp = g_ln + mt * 128 + m * 64 + (lane >> 3) * 16 + (lane & 7);
                unsigned long long r0, r1; int it = 0;
                __nanosleep(700);
                while (true) {
                    asm volatile("ld.relaxed.gpu.global.u64 %0, [%1];" : "=l"(r0) : "l"(lp) : "memory");
                    asm volatile("ld.relaxed.gpu.global.u64 %0, [%1];" : "=l"(r1) : "l"(lp + 8) : "memory");
                    if (__all_sync(~0u, (long long)(r0 & r1) < 0)) break;
                    if (++it > (1 << 22)) __trap();
                }
                sts128(sm + KA_LN + (m * 32 + lane) * 16, (uint32_t)r0, (uint32_t)(r0 >> 32), (uint32_t)r1, (uint32_t)(r1 >> 32));
                mbar_arrive(bLn);
            }
            bf16* dst = g_o + (mt * 2 + m) * (64 * D_) + g * 4608;
            bar_sync(11 + m, 160);
            if (lane == 0) { bulk_s2g(dst, sm + m * 9216, 9216); bulk_commit(); bulk_wait_read(); }
        }
    } else {
        const int xrow = mt * 128 + g * 16 + warp;
        uint4 xv[3];
        {
            const uint4* xr = reinterpret_cast<const uint4*>(x + xrow * D_);
            xv[0] = ldg128(xr + lane); xv[1] = ldg128(xr + lane + 32); xv[2] = ldg128(xr + 64 + (lane & 7));
        }
        asm volatile("setmaxnreg.inc.sync.aligned.u32 112;");
        bar_sync(0, 640);
        const int wg = warp >> 2, m = wg & 1, w4 = warp & 3, gq = lane >> 2, t = lane & 3;
        {
            const uint32_t w[12] = {xv[0].x, xv[0].y, xv[0].z, xv[0].w, xv[1].x, xv[1].y, xv[1].z, xv[1].w, xv[2].x, xv[2].y, xv[2].z, xv[2].w};
            float s = 0.f, s2 = 0.f;
            #pragma unroll
            for (int i = 0; i < 12; i++) { if (i < 8) s += bf_lo(w[i]) + bf_hi(w[i]); else s2 += bf_lo(w[i]) + bf_hi(w[i]); }
            if (lane < 8) s += s2;
            #pragma unroll
            for (int o = 16; o; o >>= 1) s += __shfl_xor_sync(~0u, s, o);
            const float mean = s * (1.f / D_);
            float q = 0.f, q2 = 0.f;
            #pragma unroll
            for (int i = 0; i < 12; i++) {
                const float e0 = bf_lo(w[i]) - mean, e1 = bf_hi(w[i]) - mean;
                if (i < 8) q += e0 * e0 + e1 * e1; else q2 += e0 * e0 + e1 * e1;
            }
            if (lane < 8) q += q2;
            #pragma unroll
            for (int o = 16; o; o >>= 1) q += __shfl_xor_sync(~0u, q, o);
            const unsigned long long lrec = ((unsigned long long)(__float_as_uint(rsqrtf(q * (1.f / D_) + LN_EPS)) | 0x80000000u) << 32) | __float_as_uint(mean);
            if (lane == 0) asm volatile("st.relaxed.gpu.global.u64 [%0], %1;" :: "l"(g_ln + xrow), "l"(lrec) : "memory");
        }
        float2 ln0, ln1;
        auto ln_get = [&]() {
            mbar_wait(bLn, 0);
            const uint4 v = lds128(sm + KA_LN + (m * 32 + w4 * 8 + gq) * 16);
            ln0 = make_float2(__uint_as_float(v.x), fabsf(__uint_as_float(v.y))); ln1 = make_float2(__uint_as_float(v.z), fabsf(__uint_as_float(v.w)));
        };
        const uint64_t da = mkdesc(sm + m * 8192, 16, 1024, 1), db = mkdesc(sm + KA_B, 16, 1024, 1);
        const uint32_t csa = sm + KA_CS + 8 * t;
        const int rot = (gq + 2 * t) & 7;
        const uint32_t rec = sm + KA_REC + t * 16384 + m * 8192 + (w4 * 16 + rot) * 128;
        const uint32_t pqs = sm + KA_B + m * (16 * PQ_UNIT);
        if (wg < 2) {
            float acc[36]; uint2 cs[9];
            #pragma unroll
            for (int c = 0; c < 9; c++) {
                mbar_wait(bFull + c * 8, 0);
                wg_fence();
                #pragma unroll
                for (int kk = 0; kk < 4; kk++) wgmma_n72<0, 0>(acc, dadv(da, c * 16384 + kk * 32), dadv(db, c * 9216 + kk * 32), (c | kk) != 0);
                wg_commit();
                if (c > 0) { wg_wait<1>(); if (lane == 0) mbar_arrive(bEmpty + (c - 1) * 8); }
            }
            wg_wait<0>();
            reg_fence<36>(acc);
            bar_arrive(5, 512);
            if (lane == 0) mbar_arrive(bEmpty + 8 * 8);
            bar_sync(6, 384);
            #pragma unroll
            for (int j = 0; j < 9; j++) cs[j] = lds64(csa + 32 * j);
            ln_get();
            uint32_t ph[2][18];
            #pragma unroll
            for (int r = 0; r < 2; r++) {
                float a[18];
                const float2 ln = r ? ln1 : ln0;
                #pragma unroll
                for (int j = 0; j < 9; j++) { a[2 * j] = fmaf(-ln.x, __uint_as_float(cs[j].x), acc[4 * j + 2 * r]); a[2 * j + 1] = fmaf(-ln.x, __uint_as_float(cs[j].y), acc[4 * j + 2 * r + 1]); }
                dual_softmax(a, ln.y * LOG2E, ph[r]);
            }
            #pragma unroll
            for (int j = 0; j < 18; j++) asm volatile("" : "+r"(ph[0][j]), "+r"(ph[1][j]));
            bar_sync(3 + m, 256);
            #pragma unroll
            for (int r = 0; r < 2; r++) {
                #pragma unroll
                for (int j = 0; j < 4; j++) sts128(rec + r * 1024 + ((j ^ rot) << 4), ph[r][4 * j], ph[r][4 * j + 1], ph[r][4 * j + 2], ph[r][4 * j + 3]);
                sts128(rec + r * 1024 + ((4 ^ rot) << 4), ph[r][16], ph[r][17], 0u, 0u);
            }
            fence_async_smem();
            bar_sync(8, 512);
            float ck[2][20];
            wg_fence();
            const uint64_t dr = mkdesc(sm + KA_REC + m * 32768, 8192, 1024, 1);
            #pragma unroll
            for (int ks = 0; ks < 8; ks++)
                #pragma unroll
                for (int hh = 0; hh < 2; hh++)
                    wgmma_n40<1, 1>(ck[hh], dadv(dr, hh * 16384 + ks * 2048), dadv(dr, hh * 16384 + ks * 2048), ks != 0);
            wg_commit();
            if (w4 < 2) bar_arrive(7, 512);
            wg_wait<0>();
            reg_fence<20>(ck[0]); reg_fence<20>(ck[1]);
            if (w4 >= 2) {
                #pragma unroll
                for (int hh = 0; hh < 2; hh++) {
                    float* kvh = g_kv + (g * 4 + m * 2 + hh) * KV_H;
                    #pragma unroll
                    for (int e = 0; e < 2; e++) {
                        const int nt = 2 * w4 + e - 5;
                        if (nt >= 0 && (nt < 2 || gq < 3)) {
                            float* p = kvh + nt * 320;
                            const float* q = ck[hh] + 2 * e;
                            asm volatile("red.global.add.v4.f32 [%0], {%1, %2, %3, %4};" :: "l"(p + lane * 4), "f"(q[0]), "f"(q[1]), "f"(q[4]), "f"(q[5]) : "memory");
                            asm volatile("red.global.add.v4.f32 [%0], {%1, %2, %3, %4};" :: "l"(p + 128 + lane * 4), "f"(q[8]), "f"(q[9]), "f"(q[12]), "f"(q[13]) : "memory");
                            if (t < 2) asm volatile("red.global.add.v2.f32 [%0], {%1, %2};" :: "l"(p + 256 + lane * 2), "f"(q[16]), "f"(q[17]) : "memory");
                        }
                    }
                }
                __syncwarp();
                bar_arrive(7, 512);
                if (lane == 0) asm volatile("red.release.gpu.global.add.u32 [%0], 1;" :: "l"(g_cnt + g * CNT_S) : "memory");
                __syncwarp();
                bar_arrive(2, 160);
            }
            const float* kp = g_kv + (g * 4 + w4) * KV_H + lane * 2;
            bar_sync(1, 288);
            uint4 u0[3], u1[3]; uint2 u2[3];
            #pragma unroll
            for (int n = 2; n >= 0; n--) { u0[n] = ldg128(kp + n * 320 + lane * 2); u1[n] = ldg128(kp + n * 320 + 128 + lane * 2); u2[n] = ldg64(kp + n * 320 + 256); }
            bar_sync(9 + m, 256);
            uint4 a0[4], a1[4]; uint2 at[4];
            #pragma unroll
            for (int mm = 0; mm < 4; mm++) {
                const uint32_t ub = pqs + (mm * 4 + w4) * PQ_UNIT;
                a0[mm] = lds128(ub + lane * 16); a1[mm] = lds128(ub + 512 + lane * 16); at[mm] = lds64(ub + 1024 + gq * 16 + (t & 1) * 8);
            }
            uint32_t bq[3][5];
            #pragma unroll
            for (int n = 0; n < 3; n++) {
                bq[n][0] = packu(u0[n].x, u0[n].y); bq[n][1] = packu(u0[n].z, u0[n].w);
                bq[n][2] = packu(u1[n].x, u1[n].y); bq[n][3] = packu(u1[n].z, u1[n].w);
                bq[n][4] = packu(u2[n].x, u2[n].y);
            }
            const uint32_t os = sm + m * 9216;
            uint32_t oad[3];
            #pragma unroll
            for (int n = 0; n < 3; n++) { const int k = w4 * 18 + n * 8 + 2 * t; oad[n] = os + (k >> 3) * 1024 + gq * 16 + (k & 7) * 2; }
            #pragma unroll
            for (int mp = 0; mp < 2; mp++) {
                float c[2][3][4];
                #pragma unroll
                for (int e = 0; e < 2; e++)
                    #pragma unroll
                    for (int n = 2; n >= 0; n--) {
                        c[e][n][0] = c[e][n][1] = c[e][n][2] = c[e][n][3] = 0.f;
                        mma16816(c[e][n], a0[2 * mp + e].x, a1[2 * mp + e].x, a0[2 * mp + e].y, a1[2 * mp + e].y, bq[n][0], bq[n][1]);
                    }
                #pragma unroll
                for (int e = 0; e < 2; e++)
                    #pragma unroll
                    for (int n = 2; n >= 0; n--) mma16816(c[e][n], a0[2 * mp + e].z, a1[2 * mp + e].z, a0[2 * mp + e].w, a1[2 * mp + e].w, bq[n][2], bq[n][3]);
                #pragma unroll
                for (int e = 0; e < 2; e++)
                    #pragma unroll
                    for (int n = 2; n >= 0; n--) mma1688(c[e][n], at[2 * mp + e].x, at[2 * mp + e].y, bq[n][4]);
                float rr[2][2];
                #pragma unroll
                for (int e = 0; e < 2; e++) {
                    rr[e][0] = __shfl_sync(~0u, c[e][2][0], (lane & 28) | 1); rr[e][1] = __shfl_sync(~0u, c[e][2][2], (lane & 28) | 1);
                }
                #pragma unroll
                for (int e = 0; e < 2; e++) {
                    const float r0 = rcp_full(rr[e][0] + 1e-6f), r1 = rcp_full(rr[e][1] + 1e-6f);
                    #pragma unroll
                    for (int n = 0; n < 3; n++) {
                        const uint32_t v0 = pack2(c[e][n][0] * r0, c[e][n][1] * r0), v1 = pack2(c[e][n][2] * r1, c[e][n][3] * r1);
                        if (n < 2 || t == 0) { sts32(oad[n] + (2 * mp + e) * 256, v0); sts32(oad[n] + (2 * mp + e) * 256 + 128, v1); }
                    }
                }
            }
            fence_async_smem();
            bar_arrive(11 + m, 160);
        } else {
            float avq[36], acc[36]; uint2 cs[9];
            if (m == 1) {
                pdl_wait();
                if (tid < 384 + 108) {
                    uint2 pc[18];
                    #pragma unroll
                    for (int j = 0; j < 18; j++) pc[j] = ldg64(g_cs + (g * 18 + j) * 216 + (tid - 384) * 2);
                    float a = 0.f, c = 0.f;
                    #pragma unroll
                    for (int j = 0; j < 18; j++) { a += __uint_as_float(pc[j].x); c += __uint_as_float(pc[j].y); }
                    asm volatile("st.shared.v2.f32 [%0], {%1, %2};" :: "r"(sm + KA_CS + (tid - 384) * 8), "f"(a), "f"(c) : "memory");
                }
                bar_arrive(6, 384);
            }
            bar_sync(5, 512);
            #pragma unroll
            for (int i = 9; i < 22; i++) {
                const int c = i < 17 ? (i + 1) / 2 : i - 17;
                mbar_wait(bFull + (i % 9) * 8, (i / 9) & 1);
                wg_fence();
                #pragma unroll
                for (int kk = 0; kk < 4; kk++)
                    wgmma_n72<0, 0>((i < 17 && !(i & 1)) ? acc : avq, dadv(da, c * 16384 + kk * 32), dadv(db, (i % 9) * 9216 + kk * 32), i > 10 || kk != 0);
                wg_commit();
                if (i > 9 && i <= 18) { wg_wait<1>(); if (lane == 0) mbar_arrive(bEmpty + ((i - 1) % 9) * 8); }
                if (i == 17) bar_arrive(3 + m, 256);
                if (i == 18) bar_sync(14 + m, 128);
            }
            #pragma unroll
            for (int j = 0; j < 9; j++) cs[j] = lds64(csa + 288 + 32 * j);
            ln_get();
            wg_wait<0>();
            reg_fence<36>(avq);
            #pragma unroll
            for (int r = 0; r < 2; r++) {
                uint32_t pv[9];
                const float2 ln = r ? ln1 : ln0;
                #pragma unroll
                for (int j = 0; j < 9; j++)
                    pv[j] = pack2(fmaf(-ln.x, __uint_as_float(cs[j].x), avq[4 * j + 2 * r]) * ln.y, fmaf(-ln.x, __uint_as_float(cs[j].y), avq[4 * j + 2 * r + 1]) * ln.y);
                sts128(rec + r * 1024 + ((5 ^ rot) << 4), pv[0], pv[1], pv[2], pv[3]);
                sts128(rec + r * 1024 + ((6 ^ rot) << 4), pv[4], pv[5], pv[6], pv[7]);
                sts128(rec + r * 1024 + ((7 ^ rot) << 4), pv[8], 0x00003f80u, 0u, 0u);
            }
            fence_async_smem();
            bar_arrive(8, 512);
            const uint32_t sm2 = __shfl_sync(~0u, sm, 1);
            const uint64_t da2 = mkdesc(sm2 + m * 8192, 16, 1024, 1), db2 = mkdesc(sm2 + KA_B, 16, 1024, 1);
            #pragma unroll
            for (int i = 22; i < 27; i++) mbar_wait(bFull + (i % 9) * 8, 0);
            #pragma unroll
            for (int j = 0; j < 9; j++) cs[j] = lds64(csa + 576 + 32 * j);
            bar_sync(7, 512);
            wg_fence();
            #pragma unroll
            for (int i = 22; i < 27; i++)
                #pragma unroll
                for (int kk = 0; kk < 4; kk++) wgmma_n72<0, 0>(acc, dadv(da2, (i - 22) * 16384 + kk * 32), dadv(db2, (i % 9) * 9216 + kk * 32), 1);
            wg_commit();
            wg_wait<0>();
            reg_fence<36>(acc);
            uint32_t ph[2][18];
            #pragma unroll
            for (int r = 0; r < 2; r++) {
                float a[18];
                const float2 ln = r ? ln1 : ln0;
                #pragma unroll
                for (int j = 0; j < 9; j++) { a[2 * j] = fmaf(-ln.x, __uint_as_float(cs[j].x), acc[4 * j + 2 * r]); a[2 * j + 1] = fmaf(-ln.x, __uint_as_float(cs[j].y), acc[4 * j + 2 * r + 1]); }
                dual_softmax(a, ln.y * LOG2E, ph[r]);
            }
            #pragma unroll
            for (int j = 0; j < 18; j++) asm volatile("" : "+r"(ph[0][j]), "+r"(ph[1][j]));
            bar_sync(13, 256);
            const uint32_t ub = pqs + (w4 * 4 + t) * PQ_UNIT;
            #pragma unroll
            for (int r = 0; r < 2; r++)
                #pragma unroll
                for (int j = 0; j < 4; j++) sts128(ub + r * 512 + (gq * 4 + j) * 16, ph[r][j], ph[r][4 + j], ph[r][8 + j], ph[r][12 + j]);
            sts128(ub + 1024 + gq * 16, ph[0][16], ph[1][16], ph[0][17], ph[1][17]);
            bar_arrive(9 + m, 256);
        }
    }
}

constexpr int K2PRE = 2, K2_B = 73728, K2_PIECE = 27648, K2_X = K2_B + 5 * K2_PIECE, K2_BAR = K2_X + 18432, K2_SMEM = K2_BAR + 128;
__global__ void __cluster_dims__(2, 1, 1) __launch_bounds__(256, 1) k2_attn(const __grid_constant__ CUtensorMap tmX, const bf16* __restrict__ b2) {
    extern __shared__ __align__(1024) char smem[];
    const uint32_t sm = smem_u32(smem);
    const uint32_t bFull = sm + K2_BAR, bX = bFull + 6 * 8;
    const int tid = threadIdx.x, lane = tid & 31, warp = __shfl_sync(~0u, tid >> 5, 0);
    const int ns = blockIdx.x & 3, mt = blockIdx.x >> 2;
    const int wg = warp >> 2, w4 = warp & 3, gq = lane >> 2, t = lane & 3;
    const bf16* wsrc = g_wo + ns * (2 * 72 * 576);
    unsigned short bb0, bb1;
    asm volatile("ld.global.nc.u16 %0, [%1];" : "=h"(bb0) : "l"(b2 + mt * 64 + w4 * 16 + gq));
    asm volatile("ld.global.nc.u16 %0, [%1];" : "=h"(bb1) : "l"(b2 + mt * 64 + w4 * 16 + gq + 8));
    auto load_w = [&](int i) {
        bulk_g2s(sm + K2_B + (i % 5) * K2_PIECE, wsrc + i * (K2_PIECE / 4), K2_PIECE / 2, bFull + i * 8);
        bulk_g2s(sm + K2_B + (i % 5) * K2_PIECE + K2_PIECE / 2, wsrc + 72 * 576 + i * (K2_PIECE / 4), K2_PIECE / 2, bFull + i * 8);
    };
    if (tid == 0) {
        #pragma unroll
        for (int i = 0; i < 7; i++) mbar_init(bFull + i * 8, 1);
        fence_mbar_init();
        #pragma unroll
        for (int i = 0; i < 6; i++) mbar_expect(bFull + i * 8, K2_PIECE + 12288);
        mbar_expect(bX, 18432);
        #pragma unroll
        for (int i = 0; i < K2PRE; i++) load_w(i);
        prefetch_tm(&tmX);
    }
    __syncthreads();
    if (tid == 0) {
        pdl_wait();
        pdl_trigger();
        const bf16* osrc = g_o + mt * (64 * D_);
        #pragma unroll
        for (int i = 0; i < 6; i++) {
            bulk_g2s(sm + i * 12288, osrc + i * 6144, 12288, bFull + i * 8);
            if (i + 1 >= K2PRE && i < 4) load_w(i + 1);
        }
        tma2d(sm + K2_X, &tmX, bX, ns * 144, mt * 64);
        tma2d(sm + K2_X + 9216, &tmX, bX, ns * 144 + 72, mt * 64);
    }
    __syncwarp();
    {
        float acc[36];
        const uint32_t xs = sm + K2_X + wg * 9216;
        uint32_t xr[18];
        const int p = ns * 2 + wg;
        unsigned long long* sb = g_stats + (mt * 4 + w4) * 128 + gq * 2;
        unsigned long long* sw = sb + p * 16;
        const unsigned long long* sr = sb + t * 32;
        bf16* ndst = g_hnT + (mt * D_ + p * 72) * 64;
        asm volatile("" : "+l"(sw), "+l"(sr), "+l"(ndst));
        const uint64_t da0 = mkdesc(sm, 1024, 128, 0), db0 = mkdesc(sm + K2_B + wg * (K2_PIECE / 2), 1152, 128, 0);
        #pragma unroll
        for (int i = 0; i < 6; i++) {
            mbar_wait(bFull + i * 8, 0);
            wg_fence();
            #pragma unroll
            for (int kk = 0; kk < 6; kk++)
                wgmma_n72<0, 0>(acc, dadv(da0, i * 12288 + kk * 2048), dadv(db0, (i % 5) * K2_PIECE + kk * 2304), (i | kk) != 0);
            wg_commit();
            if (i == 1) {
                wg_wait<1>();
                bar_sync(1 + wg, 128);
                if ((tid & 127) == 96) bulk_g2s(sm + K2_B + wg * (K2_PIECE / 2), wsrc + wg * (72 * 576) + 5 * (K2_PIECE / 4), K2_PIECE / 2, bFull + 5 * 8);
                __syncwarp();
            }
            if (i == 5) {
                mbar_wait(bX, 0);
                #pragma unroll
                for (int j = 0; j < 9; j++) {
                    xr[2 * j] = lds32(xs + (w4 * 16 + gq) * 144 + j * 16 + t * 4); xr[2 * j + 1] = lds32(xs + (w4 * 16 + gq + 8) * 144 + j * 16 + t * 4);
                }
            }
        }
        wg_wait<0>();
        reg_fence<36>(acc);
        #pragma unroll
        for (int j = 0; j < 18; j++) { acc[2 * j] += bf_lo(xr[j]); acc[2 * j + 1] += bf_hi(xr[j]); }
        float m0 = 0.f, m1 = 0.f;
        #pragma unroll
        for (int j = 0; j < 9; j++) { m0 += acc[4 * j] + acc[4 * j + 1]; m1 += acc[4 * j + 2] + acc[4 * j + 3]; }
        m0 *= (1.f / 18); m1 *= (1.f / 18);
        float q0 = 0.f, q1 = 0.f, q2 = 0.f, q3 = 0.f;
        #pragma unroll
        for (int j = 0; j < 9; j++) {
            float e;
            e = acc[4 * j] - m0; q0 = fmaf(e, e, q0); e = acc[4 * j + 1] - m0; q2 = fmaf(e, e, q2);
            e = acc[4 * j + 2] - m1; q1 = fmaf(e, e, q1); e = acc[4 * j + 3] - m1; q3 = fmaf(e, e, q3);
        }
        q0 += q2; q1 += q3;
        #pragma unroll
        for (int o = 1; o < 4; o <<= 1) {
            const float a0 = __shfl_xor_sync(~0u, m0, o), a1 = __shfl_xor_sync(~0u, m1, o), b0 = __shfl_xor_sync(~0u, q0, o), b1 = __shfl_xor_sync(~0u, q1, o);
            q0 += b0 + (a0 - m0) * (a0 - m0) * (9.f * o); q1 += b1 + (a1 - m1) * (a1 - m1) * (9.f * o);
            m0 = 0.5f * (m0 + a0); m1 = 0.5f * (m1 + a1);
        }
        if (t == 0) {
            const unsigned long long r0 = ((unsigned long long)(__float_as_uint(q0) | 0x80000000u) << 32) | __float_as_uint(m0);
            const unsigned long long r1 = ((unsigned long long)(__float_as_uint(q1) | 0x80000000u) << 32) | __float_as_uint(m1);
            asm volatile("st.relaxed.gpu.global.v2.u64 [%0], {%1, %2};" :: "l"(sw), "l"(r0), "l"(r1) : "memory");
        }
        bar_sync(1 + wg, 128);
        unsigned long long ra, rb, rc, rd;
        {
            int it = 0;
            while (true) {
                asm volatile("ld.relaxed.gpu.global.v2.u64 {%0, %1}, [%2];" : "=l"(ra), "=l"(rc) : "l"(sr) : "memory");
                asm volatile("ld.relaxed.gpu.global.v2.u64 {%0, %1}, [%2];" : "=l"(rb), "=l"(rd) : "l"(sr + 16) : "memory");
                const bool ok = (long long)(ra & rb & rc & rd) < 0;
                if (__all_sync(~0u, ok)) break;
                if (++it > (1 << 22)) __trap();
            }
        }
        float sc[2], mu[2];
        #pragma unroll
        for (int r = 0; r < 2; r++) {
            const unsigned long long u = r ? rc : ra, v = r ? rd : rb;
            const float ma = __uint_as_float((uint32_t)u), mb = __uint_as_float((uint32_t)v);
            float ms = ma + mb;
            ms += __shfl_xor_sync(~0u, ms, 1); ms += __shfl_xor_sync(~0u, ms, 2);
            const float mean = ms * 0.125f;
            float M2 = fabsf(__uint_as_float((uint32_t)(u >> 32))) + fabsf(__uint_as_float((uint32_t)(v >> 32))) + 72.f * ((ma - mean) * (ma - mean) + (mb - mean) * (mb - mean));
            M2 += __shfl_xor_sync(~0u, M2, 1); M2 += __shfl_xor_sync(~0u, M2, 2);
            const float var = M2 * (1.f / D_);
            const float r1 = rsqrtf(var + LN_EPS);
            const float var2 = var * r1 * r1;
            const float r2 = rsqrtf(var2 + LN_EPS);
            sc[r] = 0.5f * (r1 * r2); mu[r] = mean;
        }
        {
            uint32_t o[18];
            #pragma unroll
            for (int j = 0; j < 9; j++) {
                o[2 * j] = pack2((acc[4 * j] - mu[0]) * sc[0], (acc[4 * j + 1] - mu[0]) * sc[0]);
                o[2 * j + 1] = pack2((acc[4 * j + 2] - mu[1]) * sc[1], (acc[4 * j + 3] - mu[1]) * sc[1]);
            }
            const int ch = 2 * w4 + ((lane >> 3) & 1);
            const uint32_t ad = xs + ((lane >> 4) * 8 + (lane & 7)) * 128 + ((ch ^ (lane & 7)) << 4);
            #pragma unroll
            for (int j = 0; j < 4; j++) stsm4t(ad + j * 2048, o[4 * j], o[4 * j + 1], o[4 * j + 2], o[4 * j + 3]);
            stsm2t(xs + (64 + (lane & 7)) * 128 + ((ch ^ (lane & 7)) << 4), o[16], o[17]);
        }
        fence_async_smem();
        bar_sync(1 + wg, 128);
        if ((tid & 127) == 0) {
            bulk_s2g(ndst, xs, 9216);
            bulk_commit();
        }
        if (p == 1 && t < 2) g_ln[mt * 64 + w4 * 16 + gq + 8 * t] = 0ull;
        if (p == 0 && t < 2) {
            asm volatile("" : "+h"(bb0), "+h"(bb1));
            g_rc[mt * 64 + w4 * 16 + gq + 8 * t] = make_float2(1.f / (t ? sc[1] : sc[0]), (t ? mu[1] : mu[0]) + __uint_as_float((uint32_t)(t ? bb1 : bb0) << 16));
        }
        if ((tid & 127) == 0) bulk_wait_read();
    }
}

constexpr int PFT = 4, W2HEAD = 9;
constexpr int K3_STAGES = 6, K3_STAGE = 36864, K3_STAG = 6, K3_PRE = 2, K3_BAR = K3_STAGES * K3_STAGE, K3_SMEM = K3_BAR + 256;
DEVI uint32_t gelu2(float a0, float a1) {
    const float z0 = a0 * fmaf(a0 * a0, 0.2854192650904f, 1.5957691216057f), z1 = a1 * fmaf(a1 * a1, 0.2854192650904f, 1.5957691216057f);
    return pack2(fmaf(a0, tanh_fast(z0), a0), fmaf(a1, tanh_fast(z1), a1));
}
template<int ROWS, int OFF> DEVI void k3_store(const float* q, uint32_t st, uint32_t lo, int bar) {
    #pragma unroll
    for (int jj = 0; jj < ROWS / 16; jj++)
        stsm4t(st + lo + jj * 2048, gelu2(q[OFF + jj * 8], q[OFF + jj * 8 + 1]), gelu2(q[OFF + jj * 8 + 2], q[OFF + jj * 8 + 3]),
               gelu2(q[OFF + jj * 8 + 4], q[OFF + jj * 8 + 5]), gelu2(q[OFF + jj * 8 + 6], q[OFF + jj * 8 + 7]));
    fence_async_smem();
    bar_arrive(bar, 160);
}
DEVI void k3_typeb(uint32_t sm_, int fc_, uint32_t lo, float bias0, float bias1, const bf16* __restrict__ b1) {
    const uint32_t sm = __shfl_sync(~0u, sm_, 0);
    const int fc = __shfl_sync(~0u, fc_, 0);
    const uint32_t bFull = sm + K3_BAR, bEmpty = bFull + K3_STAGES * 8;
    const int tid = threadIdx.x, lane = tid & 31, warp = __shfl_sync(~0u, tid >> 5, 0);
    const int wg = warp >> 2, w4 = warp & 3, gq = lane >> 2;
    const uint32_t st = sm + wg * 8192;
    const uint64_t da0 = mkdesc(st, 8192, 1024, 1);
    int s = 0, ps = 0; uint32_t ph = 0;
    {
            const int f2 = (fc + 2) * 64 + w4 * 16 + gq;
            const float bias2 = 0.5f * __bfloat162float(b1[f2]), bias3 = 0.5f * __bfloat162float(b1[f2 + 8]);
            float acc[48], acc2[24];
            const uint64_t da2 = mkdesc(sm + 16384, 8192, 1024, 1), db0 = mkdesc(sm + 24576, 16, 1024, 1), db2 = mkdesc(sm + 24576 + wg * 6144, 16, 1024, 1);
            #pragma unroll 1
            for (int i = 0; i < 32 - K3_STAG; i++) {
                mbar_wait(bFull + s * 8, ph);
                const uint32_t so = s * K3_STAGE;
                wg_fence();
                #pragma unroll
                for (int kk = 0; kk < 4; kk++) {
                    wgmma_n96<1, 0>(acc, dadv(da0, so + kk * 2048), dadv(db0, so + kk * 32), (i | kk) != 0);
                    wgmma_n48<1, 0>(acc2, dadv(da2, so + kk * 2048), dadv(db2, so + kk * 32), (i | kk) != 0);
                }
                wg_commit();
                wg_wait<1>();
                if (i > 0 && lane == 0) mbar_arrive(bEmpty + ps * 8);
                ps = s;
                if (++s == K3_STAGES) { s = 0; ph ^= 1; }
            }
            if (wg == 1) {
                wg_wait<0>();
                if (lane == 0) mbar_arrive(bEmpty + ps * 8);
                #pragma unroll
                for (int i = 32 - K3_STAG; i < 32; i++) mbar_wait(bFull + (i % K3_STAGES) * 8, (i / K3_STAGES) & 1);
                bar_sync(3, 256);
            }
            #pragma unroll
            for (int i = 32 - K3_STAG; i < 32; i++) {
                if (wg == 0) mbar_wait(bFull + (i % K3_STAGES) * 8, (i / K3_STAGES) & 1);
                const uint32_t so = (i % K3_STAGES) * K3_STAGE;
                wg_fence();
                #pragma unroll
                for (int kk = 0; kk < 4; kk++) {
                    wgmma_n96<1, 0>(acc, dadv(da0, so + kk * 2048), dadv(db0, so + kk * 32), 1);
                    wgmma_n48<1, 0>(acc2, dadv(da2, so + kk * 2048), dadv(db2, so + kk * 32), 1);
                }
                wg_commit();
                if (i == 32 - K3_STAG && wg == 0) { wg_wait<1>(); if (lane == 0) mbar_arrive(bEmpty + ps * 8); }
            }
            if (wg == 0) bar_arrive(3, 256);
            wg_wait<0>();
            reg_fence<48>(acc); reg_fence<24>(acc2);
            #pragma unroll
            for (int j = 0; j < 48; j++) acc[j] += (j & 2) ? bias1 : bias0;
            #pragma unroll
            for (int j = 0; j < 24; j++) acc2[j] += (j & 2) ? bias3 : bias2;
            bar_sync(1 + wg, 128);
            k3_store<48, 0>(acc, st, lo, 4 + wg * 4);
            k3_store<48, 24>(acc, st + K3_STAGE, lo, 5 + wg * 4);
            k3_store<32, 0>(acc2, st + 2 * K3_STAGE, lo, 6 + wg * 4);
            k3_store<16, 16>(acc2, st + 3 * K3_STAGE, lo, 7 + wg * 4);
    }
}
__global__ void __cluster_dims__(2, 1, 1) __launch_bounds__(352, 1) k3_mix1(const __grid_constant__ CUtensorMap tmW1a, const __grid_constant__ CUtensorMap tmW1b,
                                                                             const bf16* __restrict__ b1, const bf16* __restrict__ w1, const bf16* __restrict__ w2) {
    extern __shared__ __align__(1024) char smem[];
    const uint32_t sm = smem_u32(smem);
    const uint32_t bFull = sm + K3_BAR, bEmpty = bFull + K3_STAGES * 8;
    const int tid = threadIdx.x, lane = tid & 31, warp = __shfl_sync(~0u, tid >> 5, 0);
    const int cl = blockIdx.x >> 1, rank = blockIdx.x & 1;
    bool tb = false; int fc, d0;
    if (cl < 36) { fc = 2 * cl; d0 = 160 * rank; }
    else if (cl < 60) { const int q = (cl - 36) >> 1, e = (cl - 36) & 1; tb = rank; fc = rank ? 6 * q + 3 * e : 6 * q + 4 * e; d0 = rank ? 480 : 320; }
    else { fc = 6 * (2 * (cl - 60) + rank) + 2; d0 = 320; }
    const CUtensorMap* tm = tb ? &tmW1b : &tmW1a;
    const uint32_t abytes = tb ? 24576 : 16384;
    if (tid == 256) {
        #pragma unroll
        for (int i = 0; i < K3_STAGES; i++) { mbar_init(bFull + i * 8, 1); mbar_init(bEmpty + i * 8, 8); }
        fence_mbar_init();
        #pragma unroll
        for (int i = 0; i < K3_STAGES; i++) mbar_expect(bFull + i * 8, K3_STAGE);
        #pragma unroll
        for (int i = 0; i < K3_PRE; i++) tma3d(sm + i * K3_STAGE, tm, bFull + i * 8, 0, i * 64, fc);
    }
    __syncthreads();
    if (warp >= 9) {
        const int wg = warp - 9;
        bf16* dst = g_u + ((fc + wg) * D_ + d0) * 64;
        bf16* dst2 = tb ? g_u + ((fc + 2) * D_ + 480 + wg * 48) * 64 : dst + 96 * 64;
        #pragma unroll
        for (int pc = 0; pc < 4; pc++) {
            bar_sync(4 + wg * 4 + pc, 160);
            if (lane == 0) {
                bulk_s2g(pc < 2 ? dst + pc * (48 * 64) : dst2 + (pc - 2) * (32 * 64), sm + wg * 8192 + pc * K3_STAGE, pc < 2 ? 6144 : (pc == 3 && tb) ? 2048 : 4096);
                bulk_commit();
            }
            __syncwarp();
        }
        if (lane == 0) { bulk_wait_read(); }
    } else if (warp == 8) {
        if (tid == 256) {
            pdl_wait();
            pdl_trigger();
            const bf16* hs = g_hnT + d0 * 64;
            #pragma unroll
            for (int i = 0; i < K3_STAGES; i++) {
                bulk_g2s(sm + i * K3_STAGE + abytes, hs + i * (D_ * 64), K3_STAGE - abytes, bFull + i * 8);
                if (i >= K3_PRE) tma3d(sm + i * K3_STAGE, tm, bFull + i * 8, 0, i * 64, fc);
            }
            int s = 0; uint32_t ph = 0;
            #pragma unroll 1
            for (int i = K3_STAGES; i < 32; i++) {
                mbar_wait(bEmpty + s * 8, ph);
                mbar_expect(bFull + s * 8, K3_STAGE);
                tma3d(sm + s * K3_STAGE, tm, bFull + s * 8, 0, i * 64, fc);
                bulk_g2s(sm + s * K3_STAGE + abytes, hs + i * (D_ * 64), K3_STAGE - abytes, bFull + s * 8);
                if (i == 18 && blockIdx.x < 128) l2_prefetch(w1 + (size_t)(2048 - 64 * PFT) * F_ + blockIdx.x * (2304 * PFT), 4608 * PFT);
                if (++s == K3_STAGES) { s = 0; ph ^= 1; }
            }
            if (blockIdx.x < 128) l2_prefetch(w2 + (size_t)(blockIdx.x & 1) * (2304 * S_) + (blockIdx.x >> 1) * (W2HEAD * 2048), W2HEAD * 4096);
        }
    } else {
        const int wg = warp >> 2, w4 = warp & 3, gq = lane >> 2;
        const int f0 = (fc + wg) * 64 + w4 * 16 + gq;
        const float bias0 = 0.5f * __bfloat162float(b1[f0]), bias1 = 0.5f * __bfloat162float(b1[f0 + 8]);
        const int ch = 2 * w4 + ((lane >> 3) & 1);
        const uint32_t lo = ((lane >> 4) * 8 + (lane & 7)) * 128 + ((ch ^ (lane & 7)) << 4);
        const uint32_t st = sm + wg * 8192;
        const uint64_t da0 = mkdesc(st, 8192, 1024, 1);
        int s = 0, ps = 0; uint32_t ph = 0;
        if (!tb) {
            float acc[80];
            #pragma unroll
            for (int j = 0; j < 80; j++) acc[j] = (j & 2) ? bias1 : bias0;
            reg_fence<80>(acc);
            const uint64_t db0 = mkdesc(sm + 16384, 16, 1024, 1);
            #pragma unroll 1
            for (int i = 0; i < 32 - K3_STAG; i++) {
                mbar_wait(bFull + s * 8, ph);
                const uint64_t da = dadv(da0, s * K3_STAGE), db = dadv(db0, s * K3_STAGE);
                wg_fence();
                #pragma unroll
                for (int kk = 0; kk < 4; kk++)
                    wgmma_n160<1, 0>(acc, dadv(da, kk * 2048), dadv(db, kk * 32), 1);
                wg_commit();
                wg_wait<1>();
                if (i > 0 && lane == 0) mbar_arrive(bEmpty + ps * 8);
                ps = s;
                if (++s == K3_STAGES) { s = 0; ph ^= 1; }
            }
            if (wg == 1) {
                wg_wait<0>();
                if (lane == 0) mbar_arrive(bEmpty + ps * 8);
                #pragma unroll
                for (int i = 32 - K3_STAG; i < 32; i++) mbar_wait(bFull + (i % K3_STAGES) * 8, (i / K3_STAGES) & 1);
                bar_sync(3, 256);
            }
            #pragma unroll
            for (int i = 32 - K3_STAG; i < 32; i++) {
                if (wg == 0) mbar_wait(bFull + (i % K3_STAGES) * 8, (i / K3_STAGES) & 1);
                wg_fence();
                #pragma unroll
                for (int kk = 0; kk < 4; kk++)
                    wgmma_n160<1, 0>(acc, dadv(da0, (i % K3_STAGES) * K3_STAGE + kk * 2048), dadv(db0, (i % K3_STAGES) * K3_STAGE + kk * 32), 1);
                wg_commit();
                if (i == 32 - K3_STAG && wg == 0) { wg_wait<1>(); if (lane == 0) mbar_arrive(bEmpty + ps * 8); }
            }
            if (wg == 0) bar_arrive(3, 256);
            wg_wait<0>();
            reg_fence<80>(acc);
            bar_sync(1 + wg, 128);
            k3_store<48, 0>(acc, st, lo, 4 + wg * 4);
            k3_store<48, 24>(acc, st + K3_STAGE, lo, 5 + wg * 4);
            k3_store<32, 48>(acc, st + 2 * K3_STAGE, lo, 6 + wg * 4);
            k3_store<32, 64>(acc, st + 3 * K3_STAGE, lo, 7 + wg * 4);
        } else {
            k3_typeb(sm, fc, lo, bias0, bias1, b1);
        }
    }
}

constexpr int SLOTC = 700, SLOTP = 578, K4A0 = 1, K4_PD = 4;
constexpr int K4_STAGES = 5, K4_STAGE = 8192 + 36864, K4_STAG = 3, K4_BAR = K4_STAGES * K4_STAGE, K4_SMEM = K4_BAR + 256;
constexpr int K4_XS = (36 - K4_STAG - 1) % K4_STAGES;
__global__ void __cluster_dims__(2, 1, 1) __launch_bounds__(288, 1) k4_mix2(const __grid_constant__ CUtensorMap tmW2, const __grid_constant__ CUtensorMap tmOut) {
    extern __shared__ __align__(1024) char smem[];
    const uint32_t sm = smem_u32(smem);
    const uint32_t bFull = sm + K4_BAR, bEmpty = bFull + K4_STAGES * 8, bP = bEmpty + K4_STAGES * 8, bRdy = bP + 16, bH = bRdy + 8;
    const int tid = threadIdx.x, lane = tid & 31, warp = __shfl_sync(~0u, tid >> 5, 0);
    const int ks = blockIdx.x & 1, tm = (blockIdx.x >> 1) & 31, tn = blockIdx.x >> 6;
    const int k0 = ks * 36;
    if (tid == 256) {
        #pragma unroll
        for (int i = 0; i < K4_STAGES; i++) { mbar_init(bFull + i * 8, 1); mbar_init(bEmpty + i * 8, 8); }
        mbar_init(bP, 1); mbar_init(bP + 8, 1); mbar_init(bRdy, 8); mbar_init(bH, 1);
        fence_mbar_init();
        #pragma unroll
        for (int i = 0; i < K4A0; i++) tma3d(sm + i * K4_STAGE, &tmW2, bFull + i * 8, 0, (k0 + i) * 64, tm);
    }
    __syncthreads();
    cluster_arrive_relaxed();
    if (tid == 0) {
        #pragma unroll
        for (int i = K4A0; i < K4_STAGES; i++) tma3d(sm + i * K4_STAGE, &tmW2, bFull + i * 8, 0, (k0 + i) * 64, tm);
    }
    if (tid == 32) {
        #pragma unroll
        for (int i = 0; i < K4_STAGES; i++) mbar_expect(bFull + i * 8, K4_STAGE);
    }
    if (tid == 128) { mbar_expect(bP, 9216); mbar_expect(bP + 8, 9216); prefetch_tm(&tmOut); }
    __syncwarp();
    if (warp == 8) {
        if (lane == 0) {
            pdl_wait();
            const bf16* us = g_u + ((size_t)k0 * D_ + tn * 288) * 64;
            uint32_t slot = clock() + SLOTC;
            #pragma unroll
            for (int i = 0; i < K4_STAGES; i++) {
                if (i >= 2) { while ((int)(clock() - slot) < 0) {} slot += SLOTP; }
                bulk_g2s(sm + i * K4_STAGE + 8192, us + (size_t)i * (D_ * 64), 36864, bFull + i * 8);
            }
            int s = 0; uint32_t ph = 0;
            #pragma unroll 1
            for (int i = K4_STAGES; i < 36; i++) {
                mbar_wait(bEmpty + s * 8, ph);
                mbar_expect(bFull + s * 8, K4_STAGE);
                tma3d(sm + s * K4_STAGE, &tmW2, bFull + s * 8, 0, (k0 + i) * 64, tm);
                if (i + K4_PD < 36 && ((i ^ tn) & 1)) tma3d_prefetch(&tmW2, 0, (k0 + i + K4_PD) * 64, tm);
                if (i < 32) { while ((int)(clock() - slot) < 0) {} slot += SLOTP; }
                bulk_g2s(sm + s * K4_STAGE + 8192, us + (size_t)i * (D_ * 64), 36864, bFull + s * 8);
                if (++s == K4_STAGES) { s = 0; ph ^= 1; }
            }
            static_assert(K4_STAG <= 3, "stage of step 31 is free");
            mbar_wait(bEmpty + s * 8, ph);
            mbar_expect(bH, 18432);
            bulk_g2s(sm + (31 % K4_STAGES) * K4_STAGE, g_hnT + (tm * D_ + tn * 288 + ks * 144) * 64, 18432, bH);
        }
        __syncwarp();
        cluster_wait();
        #pragma unroll
        for (int hh = 0; hh < 2; hh++) {
            bar_sync(4 + hh, 160);
            if (lane == 0) {
                tma2d_store(&tmOut, sm + K4_XS * K4_STAGE + 24576 + hh * 9216, tn * 288 + ks * 144 + hh * 72, tm * 64);
                bulk_commit();
            }
            __syncwarp();
        }
        if (lane == 0) { bulk_wait_read(); }
    } else {
        const int wg = warp >> 2, w4 = warp & 3, tw = tid & 127;
        const bool keep = wg == ks;
        float acc[72];
        const uint64_t da0 = mkdesc(sm, 8192, 1024, 1), db0 = mkdesc(sm + 8192 + wg * 18432, 16, 1024, 1);
        const uint32_t rdy = mapa(bRdy, ks ^ 1);
        cluster_wait();
        int s = 0, ps = 0; uint32_t ph = 0;
        #pragma unroll 1
        for (int i = 0; i < 36 - K4_STAG; i++) {
            mbar_wait(bFull + s * 8, ph);
            const uint64_t da = dadv(da0, s * K4_STAGE), db = dadv(db0, s * K4_STAGE);
            wg_fence();
            #pragma unroll
            for (int kk = 0; kk < 4; kk++)
                wgmma_n144<1, 0>(acc, dadv(da, kk * 2048), dadv(db, kk * 32), (i | kk) != 0);
            wg_commit();
            wg_wait<1>();
            if (i > 0 && lane == 0) mbar_arrive(bEmpty + ps * 8);
            ps = s;
            if (++s == K4_STAGES) { s = 0; ph ^= 1; }
        }
        const uint32_t xa = sm + K4_XS * K4_STAGE + tw * 16;
        const uint2 rc0 = ldg64(g_rc + tm * 64 + w4 * 16 + (lane >> 2)), rc1 = ldg64(g_rc + tm * 64 + w4 * 16 + (lane >> 2) + 8);
        float res[36];
        const uint32_t ya = sm + (31 % K4_STAGES) * K4_STAGE + 20480 + tw * 16;
        auto residual = [&](int hh) {
            uint32_t hp[20];
            mbar_wait(bH, 0);
            const int ch = 2 * w4 + ((lane >> 3) & 1);
            const uint32_t ha = sm + (31 % K4_STAGES) * K4_STAGE + hh * 9216 + ((lane >> 4) * 8 + (lane & 7)) * 128 + ((ch ^ (lane & 7)) << 4);
            #pragma unroll
            for (int j = 0; j < 5; j++) ldsm4t(ha + j * 2048, hp[4 * j], hp[4 * j + 1], hp[4 * j + 2], hp[4 * j + 3]);
            #pragma unroll
            for (int j = 0; j < 18; j++) {
                const float is = __uint_as_float((j & 1) ? rc1.x : rc0.x), of = __uint_as_float((j & 1) ? rc1.y : rc0.y);
                res[2 * j] = fmaf(bf_lo(hp[j]), is, of); res[2 * j + 1] = fmaf(bf_hi(hp[j]), is, of);
            }
            reg_fence<36>(res);
        };
        auto partial = [&](int hh) {
            mbar_wait(bP + hh * 8, 0);
            uint32_t o[18];
            #pragma unroll
            for (int j = 0; j < 4; j++) { const uint4 v = lds128(xa + hh * 10240 + j * 2048); o[4 * j] = v.x; o[4 * j + 1] = v.y; o[4 * j + 2] = v.z; o[4 * j + 3] = v.w; }
            { const uint2 v = lds64(xa + hh * 10240 + 8192); o[16] = v.x; o[17] = v.y; }
            #pragma unroll
            for (int j = 0; j < 18; j++) { res[2 * j] += bf_lo(o[j]); res[2 * j + 1] += bf_hi(o[j]); }
        };
        if (!keep) {
            #pragma unroll
            for (int i = 36 - K4_STAG; i < 36; i++) {
                mbar_wait(bFull + (i % K4_STAGES) * 8, (i / K4_STAGES) & 1);
                wg_fence();
                #pragma unroll
                for (int kk = 0; kk < 4; kk++)
                    wgmma_n144<1, 0>(acc, dadv(da0, (i % K4_STAGES) * K4_STAGE + kk * 2048), dadv(db0, (i % K4_STAGES) * K4_STAGE + kk * 32), 1);
                wg_commit();
                if (i == 36 - K4_STAG) { wg_wait<1>(); if (lane == 0) mbar_arrive_remote(rdy); }
            }
            bar_arrive(3, 256);
            mbar_wait(bRdy, 0);
            wg_wait<0>();
            reg_fence<72>(acc);
            const uint32_t rd = mapa(xa, ks ^ 1), rb = mapa(bP, ks ^ 1);
            #pragma unroll
            for (int hh = 0; hh < 2; hh++) {
                const float* q = acc + hh * 36;
                #pragma unroll
                for (int j = 0; j < 4; j++)
                    asm volatile("st.async.shared::cluster.mbarrier::complete_tx::bytes.v4.b32 [%0], {%1,%2,%3,%4}, [%5];"
                                 :: "r"(rd + hh * 10240 + j * 2048), "r"(pack2(q[8 * j], q[8 * j + 1])), "r"(pack2(q[8 * j + 2], q[8 * j + 3])),
                                    "r"(pack2(q[8 * j + 4], q[8 * j + 5])), "r"(pack2(q[8 * j + 6], q[8 * j + 7])), "r"(rb + hh * 8) : "memory");
                asm volatile("st.async.shared::cluster.mbarrier::complete_tx::bytes.v2.b32 [%0], {%1,%2}, [%3];"
                             :: "r"(rd + hh * 10240 + 8192), "r"(pack2(q[32], q[33])), "r"(pack2(q[34], q[35])), "r"(rb + hh * 8) : "memory");
            }
            residual(1);
            partial(1);
            reg_fence<36>(res);
            bar_sync(1, 256);
            #pragma unroll
            for (int j = 0; j < 9; j++) {
                const uint4 v = lds128(ya + j * 2048);
                res[4 * j] += __uint_as_float(v.x); res[4 * j + 1] += __uint_as_float(v.y); res[4 * j + 2] += __uint_as_float(v.z); res[4 * j + 3] += __uint_as_float(v.w);
            }
        } else {
            wg_wait<0>();
            if (lane == 0) mbar_arrive_remote(rdy);
            #pragma unroll
            for (int i = 36 - K4_STAG; i < 36; i++) mbar_wait(bFull + (i % K4_STAGES) * 8, (i / K4_STAGES) & 1);
            bar_sync(3, 256);
            wg_fence();
            #pragma unroll
            for (int i = 36 - K4_STAG; i < 36; i++)
                #pragma unroll
                for (int kk = 0; kk < 4; kk++)
                    wgmma_n144<1, 0>(acc, dadv(da0, (i % K4_STAGES) * K4_STAGE + kk * 2048), dadv(db0, (i % K4_STAGES) * K4_STAGE + kk * 32), 1);
            wg_commit();
            residual(0);
            wg_wait<0>();
            reg_fence<72>(acc);
            #pragma unroll
            for (int j = 0; j < 9; j++)
                sts128(ya + j * 2048, __float_as_uint(acc[36 + 4 * j]), __float_as_uint(acc[37 + 4 * j]), __float_as_uint(acc[38 + 4 * j]), __float_as_uint(acc[39 + 4 * j]));
            bar_arrive(1, 256);
            #pragma unroll
            for (int j = 0; j < 36; j++) res[j] += acc[j];
            partial(0);
        }
        const int hh = keep ? 0 : 1;
        uint32_t o[18];
        #pragma unroll
        for (int j = 0; j < 18; j++) o[j] = pack2(res[2 * j], res[2 * j + 1]);
        const uint32_t ad = sm + K4_XS * K4_STAGE + 24576 + hh * 9216 + (w4 * 16 + ((lane >> 3) & 1) * 8 + (lane & 7)) * 144;
        #pragma unroll
        for (int j = 0; j < 4; j++) stsm4(ad + (lane >> 4) * 16 + j * 32, o[4 * j], o[4 * j + 1], o[4 * j + 2], o[4 * j + 3]);
        stsm2(ad + 128, o[16], o[17]);
        fence_async_smem();
        bar_arrive(4 + hh, 160);
    }
}

typedef CUresult (*EncFn)(CUtensorMap*, CUtensorMapDataType, cuuint32_t, void*, const cuuint64_t*, const cuuint64_t*, const cuuint32_t*,
                          const cuuint32_t*, CUtensorMapInterleave, CUtensorMapSwizzle, CUtensorMapL2promotion, CUtensorMapFloatOOBfill);

template <typename... KArgs, typename... Args>
static void launch(void (*kern)(KArgs...), dim3 grid, int block, int smem, bool pdl, Args... args) {
    cudaLaunchConfig_t cfg = {};
    cfg.gridDim = grid; cfg.blockDim = dim3(block); cfg.dynamicSmemBytes = smem; cfg.stream = cudaStreamPerThread;
    cudaLaunchAttribute at[1];
    at[0].id = cudaLaunchAttributeProgrammaticStreamSerialization; at[0].val.programmaticStreamSerializationAllowed = 1;
    cfg.attrs = at; cfg.numAttrs = pdl ? 1 : 0;
    cudaLaunchKernelEx(&cfg, kern, args...);
}

extern "C" void kernel_launch(void* const* d_in, const int* in_sizes, int n_in, void* d_out, int out_size) {
    const bf16* x = (const bf16*)d_in[0];
    const bf16* wqkv = (const bf16*)d_in[1];
    const bf16* wphi = (const bf16*)d_in[2];
    const bf16* wo = (const bf16*)d_in[3];
    const bf16* w1 = (const bf16*)d_in[5];
    const bf16* b1 = (const bf16*)d_in[6];
    const bf16* w2 = (const bf16*)d_in[7];
    const bf16* b2 = (const bf16*)d_in[8];
    static EncFn enc = nullptr;
    if (!enc) {
        void* fn = nullptr; cudaDriverEntryPointQueryResult qr;
        cudaGetDriverEntryPoint("cuTensorMapEncodeTiled", &fn, cudaEnableDefault, &qr);
        enc = (EncFn)fn;
        cudaFuncSetAttribute(ka_front, cudaFuncAttributeMaxDynamicSharedMemorySize, KA_SMEM);
        cudaFuncSetAttribute(k2_attn, cudaFuncAttributeMaxDynamicSharedMemorySize, K2_SMEM);
        cudaFuncSetAttribute(k3_mix1, cudaFuncAttributeMaxDynamicSharedMemorySize, K3_SMEM);
        cudaFuncSetAttribute(k4_mix2, cudaFuncAttributeMaxDynamicSharedMemorySize, K4_SMEM);
    }
    CUtensorMap tmW1, tmW1b, tmW2, tmOut, tmX, tmXA;
    const cuuint32_t es[3] = {1, 1, 1};
    {
        cuuint64_t dims[3] = {64, (cuuint64_t)S_, (cuuint64_t)(F_ / 64)}; cuuint64_t st[2] = {(cuuint64_t)F_ * 2, 128}; cuuint32_t box[3] = {64, 64, 2};
        enc(&tmW1, CU_TENSOR_MAP_DATA_TYPE_BFLOAT16, 3, (void*)w1, dims, st, box, es, CU_TENSOR_MAP_INTERLEAVE_NONE, CU_TENSOR_MAP_SWIZZLE_128B, CU_TENSOR_MAP_L2_PROMOTION_L2_128B, CU_TENSOR_MAP_FLOAT_OOB_FILL_NONE);
        box[2] = 3;
        enc(&tmW1b, CU_TENSOR_MAP_DATA_TYPE_BFLOAT16, 3, (void*)w1, dims, st, box, es, CU_TENSOR_MAP_INTERLEAVE_NONE, CU_TENSOR_MAP_SWIZZLE_128B, CU_TENSOR_MAP_L2_PROMOTION_L2_128B, CU_TENSOR_MAP_FLOAT_OOB_FILL_NONE);
    }
    {
        cuuint64_t dims[3] = {64, (cuuint64_t)F_, (cuuint64_t)(S_ / 64)}; cuuint64_t st[2] = {(cuuint64_t)S_ * 2, 128}; cuuint32_t box[3] = {64, 64, 1};
        enc(&tmW2, CU_TENSOR_MAP_DATA_TYPE_BFLOAT16, 3, (void*)w2, dims, st, box, es, CU_TENSOR_MAP_INTERLEAVE_NONE, CU_TENSOR_MAP_SWIZZLE_128B, CU_TENSOR_MAP_L2_PROMOTION_L2_128B, CU_TENSOR_MAP_FLOAT_OOB_FILL_NONE);
    }
    {
        cuuint64_t dims[2] = {(cuuint64_t)D_, (cuuint64_t)S_}; cuuint64_t st[1] = {(cuuint64_t)D_ * 2}; cuuint32_t box[2] = {72, 64};
        enc(&tmOut, CU_TENSOR_MAP_DATA_TYPE_BFLOAT16, 2, d_out, dims, st, box, es, CU_TENSOR_MAP_INTERLEAVE_NONE, CU_TENSOR_MAP_SWIZZLE_NONE, CU_TENSOR_MAP_L2_PROMOTION_NONE, CU_TENSOR_MAP_FLOAT_OOB_FILL_NONE);
        enc(&tmX, CU_TENSOR_MAP_DATA_TYPE_BFLOAT16, 2, (void*)x, dims, st, box, es, CU_TENSOR_MAP_INTERLEAVE_NONE, CU_TENSOR_MAP_SWIZZLE_NONE, CU_TENSOR_MAP_L2_PROMOTION_NONE, CU_TENSOR_MAP_FLOAT_OOB_FILL_NONE);
    }
    {
        cuuint64_t dims[3] = {64, (cuuint64_t)S_, 9}; cuuint64_t st[2] = {(cuuint64_t)D_ * 2, 128}; cuuint32_t box[3] = {64, 128, 1};
        enc(&tmXA, CU_TENSOR_MAP_DATA_TYPE_BFLOAT16, 3, (void*)x, dims, st, box, es, CU_TENSOR_MAP_INTERLEAVE_NONE, CU_TENSOR_MAP_SWIZZLE_128B, CU_TENSOR_MAP_L2_PROMOTION_L2_128B, CU_TENSOR_MAP_FLOAT_OOB_FILL_NONE);
    }
    launch(k0_prep, dim3(9, 8, 4), 256, 0, false, x, wqkv, wphi);
    launch(ka_front, 132, 640, KA_SMEM, true, tmXA, x, wo, w1, b1);
    launch(k2_attn, 128, 256, K2_SMEM, true, tmX, b2);
    launch(k3_mix1, 132, 352, K3_SMEM, true, tmW1, tmW1b, b1, w1, w2);
    launch(k4_mix2, 128, 288, K4_SMEM, true, tmW2, tmOut);
}
```

```cpp
#include <cuda_runtime.h>
#include <cuda.h>
#include <cuda_bf16.h>
#include <stdint.h>

typedef __nv_bfloat16 bf16;
#define DEVI __device__ __forceinline__

constexpr int S_ = 2048, D_ = 576, F_ = 4608;
constexpr float LN_EPS = 1e-5f;
constexpr float LOG2E = 1.4426950408889634f;

__device__ __align__(1024) bf16 g_o[S_ * D_];
__device__ __align__(1024) bf16 g_wqkv[8 * 27 * 72 * 64];
__device__ __align__(16) float g_cs[8 * 18 * 216];
__device__ __align__(1024) bf16 g_wo[8 * 72 * 72 * 8];
constexpr int KV_H = 960;
constexpr int PQ_UNIT = 1168;
__device__ __align__(1024) float g_kv[32 * KV_H];
__device__ __align__(1024) unsigned long long g_stats[S_ * 8];
__device__ __align__(16) unsigned long long g_ln[S_];
__device__ __align__(16) float2 g_rc[S_];
__device__ __align__(1024) bf16 g_hnT[D_ * S_];
__device__ __align__(1024) bf16 g_u[D_ * F_];
constexpr int CNT_S = 64;
__device__ __align__(256) unsigned int g_cnt[8 * CNT_S];

DEVI uint32_t smem_u32(const void* p) { return (uint32_t)__cvta_generic_to_shared(p); }
DEVI void mbar_init(uint32_t bar, int cnt) { asm volatile("mbarrier.init.shared::cta.b64 [%0], %1;" :: "r"(bar), "r"(cnt) : "memory"); }
DEVI void mbar_expect(uint32_t bar, uint32_t bytes) { asm volatile("mbarrier.arrive.expect_tx.shared::cta.b64 _, [%0], %1;" :: "r"(bar), "r"(bytes) : "memory"); }
DEVI void mbar_wait(uint32_t bar, uint32_t parity) {
    asm volatile("{\n.reg .pred p;\n.reg .u32 it;\n"
                 "mbarrier.try_wait.parity.shared::cta.b64 p, [%0], %1;\n@p bra MW_DONE;\n"
                 "mov.u32 it, 0;\n"
                 "MW_LOOP:\nmbarrier.try_wait.parity.shared::cta.b64 p, [%0], %1;\n@p bra MW_DONE;\n"
                 "add.u32 it, it, 1;\nsetp.lt.u32 p, it, 4194304;\n@p bra MW_LOOP;\ntrap;\n"
                 "MW_DONE:\n}" :: "r"(bar), "r"(parity) : "memory");
}
DEVI void mbar_arrive(uint32_t bar) { asm volatile("mbarrier.arrive.shared::cta.b64 _, [%0];" :: "r"(bar) : "memory"); }
DEVI uint32_t mapa(uint32_t addr, uint32_t cta) { uint32_t r; asm volatile("mapa.shared::cluster.u32 %0, %1, %2;" : "=r"(r) : "r"(addr), "r"(cta)); return r; }
DEVI void mbar_arrive_remote(uint32_t raddr) { asm volatile("mbarrier.arrive.shared::cluster.b64 _, [%0];" :: "r"(raddr) : "memory"); }
DEVI void fence_mbar_init() { asm volatile("fence.mbarrier_init.release.cluster;" ::: "memory"); }
DEVI void fence_async_smem() { asm volatile("fence.proxy.async.shared::cta;" ::: "memory"); }
DEVI void cluster_arrive_relaxed() { asm volatile("barrier.cluster.arrive.relaxed.aligned;" ::: "memory"); }
DEVI void cluster_wait() { asm volatile("barrier.cluster.wait.aligned;" ::: "memory"); }
DEVI void bar_sync(int id, int n) { asm volatile("bar.sync %0, %1;" :: "r"(id), "r"(n) : "memory"); }
DEVI void bar_arrive(int id, int n) { asm volatile("bar.arrive %0, %1;" :: "r"(id), "r"(n) : "memory"); }
DEVI void pdl_wait() { asm volatile("griddepcontrol.wait;" ::: "memory"); }
DEVI void pdl_trigger() { asm volatile("griddepcontrol.launch_dependents;" ::: "memory"); }
DEVI void bulk_g2s(uint32_t dst, const void* src, uint32_t bytes, uint32_t bar) {
    asm volatile("cp.async.bulk.shared::cluster.global.mbarrier::complete_tx::bytes [%0], [%1], %2, [%3];" :: "r"(dst), "l"(src), "r"(bytes), "r"(bar) : "memory");
}
DEVI void bulk_s2g(void* dst, uint32_t src, uint32_t bytes) {
    asm volatile("cp.async.bulk.global.shared::cta.bulk_group [%0], [%1], %2;" :: "l"(dst), "r"(src), "r"(bytes) : "memory");
}
DEVI void l2_prefetch(const void* p, uint32_t bytes) { asm volatile("cp.async.bulk.prefetch.L2.global [%0], %1;" :: "l"(p), "r"(bytes) : "memory"); }
DEVI void bulk_commit() { asm volatile("cp.async.bulk.commit_group;" ::: "memory"); }
DEVI void bulk_wait_read() { asm volatile("cp.async.bulk.wait_group.read 0;" ::: "memory"); }
DEVI void tma2d(uint32_t dst, const CUtensorMap* tm, uint32_t bar, int c0, int c1) {
    asm volatile("cp.async.bulk.tensor.2d.shared::cluster.global.mbarrier::complete_tx::bytes [%0], [%1, {%3, %4}], [%2];" :: "r"(dst), "l"(tm), "r"(bar), "r"(c0), "r"(c1) : "memory");
}
DEVI void tma3d(uint32_t dst, const CUtensorMap* tm, uint32_t bar, int c0, int c1, int c2) {
    asm volatile("cp.async.bulk.tensor.3d.shared::cluster.global.mbarrier::complete_tx::bytes [%0], [%1, {%3, %4, %5}], [%2];" :: "r"(dst), "l"(tm), "r"(bar), "r"(c0), "r"(c1), "r"(c2) : "memory");
}
DEVI void tma3d_prefetch(const CUtensorMap* tm, int c0, int c1, int c2) {
    asm volatile("cp.async.bulk.prefetch.tensor.3d.L2.global [%0, {%1, %2, %3}];" :: "l"(tm), "r"(c0), "r"(c1), "r"(c2) : "memory");
}
DEVI void tma2d_store(const CUtensorMap* tm, uint32_t src, int c0, int c1) {
    asm volatile("cp.async.bulk.tensor.2d.global.shared::cta.bulk_group [%0, {%2, %3}], [%1];" :: "l"(tm), "r"(src), "r"(c0), "r"(c1) : "memory");
}
DEVI void prefetch_tm(const CUtensorMap* tm) { asm volatile("prefetch.tensormap [%0];" :: "l"(tm) : "memory"); }
DEVI uint64_t mkdesc(uint32_t addr, uint32_t lbo, uint32_t sbo, uint64_t swz) {
    return (uint64_t)((addr & 0x3FFFF) >> 4) | ((uint64_t)(lbo >> 4) << 16) | ((uint64_t)(sbo >> 4) << 32) | (swz << 62);
}
DEVI uint64_t dadv(uint64_t d, uint32_t bytes) { return (d & 0xffffffff00000000ull) | (uint64_t)((uint32_t)d + (bytes >> 4)); }
DEVI void wg_fence() { asm volatile("wgmma.fence.sync.aligned;" ::: "memory"); }
DEVI void wg_commit() { asm volatile("wgmma.commit_group.sync.aligned;" ::: "memory"); }
template<int N> DEVI void wg_wait() { asm volatile("wgmma.wait_group.sync.aligned %0;" :: "n"(N) : "memory"); }
template<int N> DEVI void reg_fence(float* d) {
    #pragma unroll
    for (int i = 0; i < N; i++) asm volatile("" : "+f"(d[i]) :: "memory");
}
DEVI uint32_t pack2(float lo, float hi) { uint32_t r; asm("cvt.rn.bf16x2.f32 %0, %1, %2;" : "=r"(r) : "f"(hi), "f"(lo)); return r; }
DEVI float bf_lo(uint32_t v) { return __uint_as_float(v << 16); }
DEVI float bf_hi(uint32_t v) { return __uint_as_float(v & 0xffff0000u); }
DEVI float ex2(float x) { float r; asm("ex2.approx.ftz.f32 %0, %1;" : "=f"(r) : "f"(x)); return r; }
DEVI float rcp(float x) { float r; asm("rcp.approx.ftz.f32 %0, %1;" : "=f"(r) : "f"(x)); return r; }
DEVI float rcp_full(float x) { float r; asm("rcp.approx.f32 %0, %1;" : "=f"(r) : "f"(x)); return r; }
DEVI float tanh_fast(float x) { float r; asm("tanh.approx.f32 %0, %1;" : "=f"(r) : "f"(x)); return r; }
DEVI void mma16816(float* c, uint32_t a0, uint32_t a1, uint32_t a2, uint32_t a3, uint32_t b0, uint32_t b1) {
    asm("mma.sync.aligned.m16n8k16.row.col.f32.bf16.bf16.f32 {%0,%1,%2,%3}, {%4,%5,%6,%7}, {%8,%9}, {%0,%1,%2,%3};"
        : "+f"(c[0]), "+f"(c[1]), "+f"(c[2]), "+f"(c[3]) : "r"(a0), "r"(a1), "r"(a2), "r"(a3), "r"(b0), "r"(b1));
}
DEVI void mma1688(float* c, uint32_t a0, uint32_t a1, uint32_t b0) {
    asm("mma.sync.aligned.m16n8k8.row.col.f32.bf16.bf16.f32 {%0,%1,%2,%3}, {%4,%5}, {%6}, {%0,%1,%2,%3};"
        : "+f"(c[0]), "+f"(c[1]), "+f"(c[2]), "+f"(c[3]) : "r"(a0), "r"(a1), "r"(b0));
}
DEVI void ldsm4t(uint32_t addr, uint32_t& r0, uint32_t& r1, uint32_t& r2, uint32_t& r3) {
    asm volatile("ldmatrix.sync.aligned.m8n8.x4.trans.shared.b16 {%0,%1,%2,%3}, [%4];" : "=r"(r0), "=r"(r1), "=r"(r2), "=r"(r3) : "r"(addr) : "memory");
}
DEVI void stsm4(uint32_t addr, uint32_t r0, uint32_t r1, uint32_t r2, uint32_t r3) {
    asm volatile("stmatrix.sync.aligned.m8n8.x4.shared.b16 [%0], {%1,%2,%3,%4};" :: "r"(addr), "r"(r0), "r"(r1), "r"(r2), "r"(r3) : "memory");
}
DEVI void stsm2(uint32_t addr, uint32_t r0, uint32_t r1) {
    asm volatile("stmatrix.sync.aligned.m8n8.x2.shared.b16 [%0], {%1,%2};" :: "r"(addr), "r"(r0), "r"(r1) : "memory");
}
DEVI void sts128(uint32_t addr, uint32_t r0, uint32_t r1, uint32_t r2, uint32_t r3) {
    asm volatile("st.shared.v4.b32 [%0], {%1,%2,%3,%4};" :: "r"(addr), "r"(r0), "r"(r1), "r"(r2), "r"(r3) : "memory");
}
DEVI uint32_t lds32(uint32_t addr) { uint32_t r; asm volatile("ld.shared.b32 %0, [%1];" : "=r"(r) : "r"(addr) : "memory"); return r; }
template<int TA, int TB> DEVI void wgmma_n40(float* d, uint64_t da, uint64_t db, int sd) {
  asm volatile("{\n.reg .pred p;\nsetp.ne.b32 p, %22, 0;\n"
    "wgmma.mma_async.sync.aligned.m64n40k16.f32.bf16.bf16 {%0, %1, %2, %3, %4, %5, %6, %7, %8, %9, %10, %11, %12, %13, %14, %15, %16, %17, %18, %19}, %20, %21, p, 1, 1, %23, %24;\n}\n"
    : "+f"(d[0]), "+f"(d[1]), "+f"(d[2]), "+f"(d[3]), "+f"(d[4]), "+f"(d[5]), "+f"(d[6]), "+f"(d[7]), "+f"(d[8]), "+f"(d[9]), "+f"(d[10]), "+f"(d[11]), "+f"(d[12]), "+f"(d[13]), "+f"(d[14]), "+f"(d[15]), "+f"(d[16]), "+f"(d[17]), "+f"(d[18]), "+f"(d[19]) : "l"(da), "l"(db), "r"(sd), "n"(TA), "n"(TB));
}
template<int TA, int TB> DEVI void wgmma_n48(float* d, uint64_t da, uint64_t db, int sd) {
  asm volatile("{\n.reg .pred p;\nsetp.ne.b32 p, %26, 0;\n"
    "wgmma.mma_async.sync.aligned.m64n48k16.f32.bf16.bf16 {%0, %1, %2, %3, %4, %5, %6, %7, %8, %9, %10, %11, %12, %13, %14, %15, %16, %17, %18, %19, %20, %21, %22, %23}, %24, %25, p, 1, 1, %27, %28;\n}\n"
    : "+f"(d[0]), "+f"(d[1]), "+f"(d[2]), "+f"(d[3]), "+f"(d[4]), "+f"(d[5]), "+f"(d[6]), "+f"(d[7]), "+f"(d[8]), "+f"(d[9]), "+f"(d[10]), "+f"(d[11]), "+f"(d[12]), "+f"(d[13]), "+f"(d[14]), "+f"(d[15]), "+f"(d[16]), "+f"(d[17]), "+f"(d[18]), "+f"(d[19]), "+f"(d[20]), "+f"(d[21]), "+f"(d[22]), "+f"(d[23]) : "l"(da), "l"(db), "r"(sd), "n"(TA), "n"(TB));
}
template<int TA, int TB> DEVI void wgmma_n72(float* d, uint64_t da, uint64_t db, int sd) {
  asm volatile("{\n.reg .pred p;\nsetp.ne.b32 p, %38, 0;\n"
    "wgmma.mma_async.sync.aligned.m64n72k16.f32.bf16.bf16 {%0, %1, %2, %3, %4, %5, %6, %7, %8, %9, %10, %11, %12, %13, %14, %15, %16, %17, %18, %19, %20, %21, %22, %23, %24, %25, %26, %27, %28, %29, %30, %31, %32, %33, %34, %35}, %36, %37, p, 1, 1, %39, %40;\n}\n"
    : "+f"(d[0]), "+f"(d[1]), "+f"(d[2]), "+f"(d[3]), "+f"(d[4]), "+f"(d[5]), "+f"(d[6]), "+f"(d[7]), "+f"(d[8]), "+f"(d[9]), "+f"(d[10]), "+f"(d[11]), "+f"(d[12]), "+f"(d[13]), "+f"(d[14]), "+f"(d[15]), "+f"(d[16]), "+f"(d[17]), "+f"(d[18]), "+f"(d[19]), "+f"(d[20]), "+f"(d[21]), "+f"(d[22]), "+f"(d[23]), "+f"(d[24]), "+f"(d[25]), "+f"(d[26]), "+f"(d[27]), "+f"(d[28]), "+f"(d[29]), "+f"(d[30]), "+f"(d[31]), "+f"(d[32]), "+f"(d[33]), "+f"(d[34]), "+f"(d[35]) : "l"(da), "l"(db), "r"(sd), "n"(TA), "n"(TB));
}
template<int TA, int TB> DEVI void wgmma_n96(float* d, uint64_t da, uint64_t db, int sd) {
  asm volatile("{\n.reg .pred p;\nsetp.ne.b32 p, %50, 0;\n"
    "wgmma.mma_async.sync.aligned.m64n96k16.f32.bf16.bf16 {%0, %1, %2, %3, %4, %5, %6, %7, %8, %9, %10, %11, %12, %13, %14, %15, %16, %17, %18, %19, %20, %21, %22, %23, %24, %25, %26, %27, %28, %29, %30, %31, %32, %33, %34, %35, %36, %37, %38, %39, %40, %41, %42, %43, %44, %45, %46, %47}, %48, %49, p, 1, 1, %51, %52;\n}\n"
    : "+f"(d[0]), "+f"(d[1]), "+f"(d[2]), "+f"(d[3]), "+f"(d[4]), "+f"(d[5]), "+f"(d[6]), "+f"(d[7]), "+f"(d[8]), "+f"(d[9]), "+f"(d[10]), "+f"(d[11]), "+f"(d[12]), "+f"(d[13]), "+f"(d[14]), "+f"(d[15]), "+f"(d[16]), "+f"(d[17]), "+f"(d[18]), "+f"(d[19]), "+f"(d[20]), "+f"(d[21]), "+f"(d[22]), "+f"(d[23]), "+f"(d[24]), "+f"(d[25]), "+f"(d[26]), "+f"(d[27]), "+f"(d[28]), "+f"(d[29]), "+f"(d[30]), "+f"(d[31]), "+f"(d[32]), "+f"(d[33]), "+f"(d[34]), "+f"(d[35]), "+f"(d[36]), "+f"(d[37]), "+f"(d[38]), "+f"(d[39]), "+f"(d[40]), "+f"(d[41]), "+f"(d[42]), "+f"(d[43]), "+f"(d[44]), "+f"(d[45]), "+f"(d[46]), "+f"(d[47]) : "l"(da), "l"(db), "r"(sd), "n"(TA), "n"(TB));
}
template<int TA, int TB> DEVI void wgmma_n144(float* d, uint64_t da, uint64_t db, int sd) {
  asm volatile("{\n.reg .pred p;\nsetp.ne.b32 p, %74, 0;\n"
    "wgmma.mma_async.sync.aligned.m64n144k16.f32.bf16.bf16 {%0, %1, %2, %3, %4, %5, %6, %7, %8, %9, %10, %11, %12, %13, %14, %15, %16, %17, %18, %19, %20, %21, %22, %23, %24, %25, %26, %27, %28, %29, %30, %31, %32, %33, %34, %35, %36, %37, %38, %39, %40, %41, %42, %43, %44, %45, %46, %47, %48, %49, %50, %51, %52, %53, %54, %55, %56, %57, %58, %59, %60, %61, %62, %63, %64, %65, %66, %67, %68, %69, %70, %71}, %72, %73, p, 1, 1, %75, %76;\n}\n"
    : "+f"(d[0]), "+f"(d[1]), "+f"(d[2]), "+f"(d[3]), "+f"(d[4]), "+f"(d[5]), "+f"(d[6]), "+f"(d[7]), "+f"(d[8]), "+f"(d[9]), "+f"(d[10]), "+f"(d[11]), "+f"(d[12]), "+f"(d[13]), "+f"(d[14]), "+f"(d[15]), "+f"(d[16]), "+f"(d[17]), "+f"(d[18]), "+f"(d[19]), "+f"(d[20]), "+f"(d[21]), "+f"(d[22]), "+f"(d[23]), "+f"(d[24]), "+f"(d[25]), "+f"(d[26]), "+f"(d[27]), "+f"(d[28]), "+f"(d[29]), "+f"(d[30]), "+f"(d[31]), "+f"(d[32]), "+f"(d[33]), "+f"(d[34]), "+f"(d[35]), "+f"(d[36]), "+f"(d[37]), "+f"(d[38]), "+f"(d[39]), "+f"(d[40]), "+f"(d[41]), "+f"(d[42]), "+f"(d[43]), "+f"(d[44]), "+f"(d[45]), "+f"(d[46]), "+f"(d[47]), "+f"(d[48]), "+f"(d[49]), "+f"(d[50]), "+f"(d[51]), "+f"(d[52]), "+f"(d[53]), "+f"(d[54]), "+f"(d[55]), "+f"(d[56]), "+f"(d[57]), "+f"(d[58]), "+f"(d[59]), "+f"(d[60]), "+f"(d[61]), "+f"(d[62]), "+f"(d[63]), "+f"(d[64]), "+f"(d[65]), "+f"(d[66]), "+f"(d[67]), "+f"(d[68]), "+f"(d[69]), "+f"(d[70]), "+f"(d[71]) : "l"(da), "l"(db), "r"(sd), "n"(TA), "n"(TB));
}
template<int TA, int TB> DEVI void wgmma_n160(float* d, uint64_t da, uint64_t db, int sd) {
  asm volatile("{\n.reg .pred p;\nsetp.ne.b32 p, %82, 0;\n"
    "wgmma.mma_async.sync.aligned.m64n160k16.f32.bf16.bf16 {%0, %1, %2, %3, %4, %5, %6, %7, %8, %9, %10, %11, %12, %13, %14, %15, %16, %17, %18, %19, %20, %21, %22, %23, %24, %25, %26, %27, %28, %29, %30, %31, %32, %33, %34, %35, %36, %37, %38, %39, %40, %41, %42, %43, %44, %45, %46, %47, %48, %49, %50, %51, %52, %53, %54, %55, %56, %57, %58, %59, %60, %61, %62, %63, %64, %65, %66, %67, %68, %69, %70, %71, %72, %73, %74, %75, %76, %77, %78, %79}, %80, %81, p, 1, 1, %83, %84;\n}\n"
    : "+f"(d[0]), "+f"(d[1]), "+f"(d[2]), "+f"(d[3]), "+f"(d[4]), "+f"(d[5]), "+f"(d[6]), "+f"(d[7]), "+f"(d[8]), "+f"(d[9]), "+f"(d[10]), "+f"(d[11]), "+f"(d[12]), "+f"(d[13]), "+f"(d[14]), "+f"(d[15]), "+f"(d[16]), "+f"(d[17]), "+f"(d[18]), "+f"(d[19]), "+f"(d[20]), "+f"(d[21]), "+f"(d[22]), "+f"(d[23]), "+f"(d[24]), "+f"(d[25]), "+f"(d[26]), "+f"(d[27]), "+f"(d[28]), "+f"(d[29]), "+f"(d[30]), "+f"(d[31]), "+f"(d[32]), "+f"(d[33]), "+f"(d[34]), "+f"(d[35]), "+f"(d[36]), "+f"(d[37]), "+f"(d[38]), "+f"(d[39]), "+f"(d[40]), "+f"(d[41]), "+f"(d[42]), "+f"(d[43]), "+f"(d[44]), "+f"(d[45]), "+f"(d[46]), "+f"(d[47]), "+f"(d[48]), "+f"(d[49]), "+f"(d[50]), "+f"(d[51]), "+f"(d[52]), "+f"(d[53]), "+f"(d[54]), "+f"(d[55]), "+f"(d[56]), "+f"(d[57]), "+f"(d[58]), "+f"(d[59]), "+f"(d[60]), "+f"(d[61]), "+f"(d[62]), "+f"(d[63]), "+f"(d[64]), "+f"(d[65]), "+f"(d[66]), "+f"(d[67]), "+f"(d[68]), "+f"(d[69]), "+f"(d[70]), "+f"(d[71]), "+f"(d[72]), "+f"(d[73]), "+f"(d[74]), "+f"(d[75]), "+f"(d[76]), "+f"(d[77]), "+f"(d[78]), "+f"(d[79]) : "l"(da), "l"(db), "r"(sd), "n"(TA), "n"(TB));
}

__host__ __device__ constexpr int ka_seq(int p, int c) { return p == 0 ? c : c >= 5 ? 2 * c - 2 + p : p == 1 ? 17 + c : 22 + c; }
__global__ void __launch_bounds__(256, 3) k0_prep(const bf16* __restrict__ x, const bf16* __restrict__ wqkv, const bf16* __restrict__ wphi,
                                                  const bf16* __restrict__ wo) {
    __shared__ __align__(16) uint32_t s_in[64 * 36 + 64];
    pdl_trigger();
    const int tid = threadIdx.x, lane = tid & 31, warp = __shfl_sync(~0u, tid >> 5, 0);
    const int c = blockIdx.x, g = blockIdx.y, p = blockIdx.z;
    const bool fold = p == 0 || p == 2;
    const int b = (p * 8 + g) * 9 + c;
    if (p == 3) {
        const int j = b - 216;
        const uint4 z = make_uint4(0u, 0u, 0u, 0u);
        if (j < 32) reinterpret_cast<uint4*>(g_stats)[j * 256 + tid] = z;
        else if (j < 62) reinterpret_cast<uint4*>(g_kv)[(j - 32) * 256 + tid] = z;
        else if (j == 66 && tid < 8) g_cnt[tid * CNT_S] = 0u;
        return;
    }
    constexpr int ld = 1728;
    const bf16* src = wqkv + ((p == 2 ? 0 : p + 1) * 576 + c * 64 * ld + g * 72);
    const uint32_t si = smem_u32(s_in);
    #pragma unroll
    for (int j = 0; j < 3; j++) {
        const int i = tid + j * 256, r = (i * 7282) >> 16;
        if (j < 2 || tid < 64) asm volatile("cp.async.cg.shared.global [%0], [%1], 16;" :: "r"(si + i * 16 + (r >> 3) * 32), "l"(src + (r * (ld - 72) + i * 8)) : "memory");
    }
    const int t = warp & 3, half = warp >> 2, g8 = lane >> 2, c4 = lane & 3;
    uint32_t af[3][3];
    if (fold) {
        const unsigned short* ph = reinterpret_cast<const unsigned short*>(wphi) + (g * 4 + t) * 324;
        unsigned short lo[3][3], hi[3][3];
        #pragma unroll
        for (int fb = 0; fb < 3; fb++)
            #pragma unroll
            for (int db = 0; db < 3; db++) {
                const int o = min(2 * c4 + 8 * db, 16) * 18 + min(g8 + 8 * fb, 17);
                lo[fb][db] = __ldg(ph + o); hi[fb][db] = __ldg(ph + o + 18);
            }
        #pragma unroll
        for (int fb = 0; fb < 3; fb++)
            #pragma unroll
            for (int db = 0; db < 3; db++) af[fb][db] = (uint32_t)lo[fb][db] | ((uint32_t)hi[fb][db] << 16);
    } else {
        const uint32_t v = (g8 == 2 * c4 ? 0x3f80u : 0u) | (g8 == 2 * c4 + 1 ? 0x3f800000u : 0u);
        #pragma unroll
        for (int fb = 0; fb < 3; fb++)
            #pragma unroll
            for (int db = 0; db < 3; db++) af[fb][db] = fb == db ? v : 0u;
    }
    bf16* dst = g_wqkv + (g * 27 + ka_seq(p, c)) * 4608;
    float* csd = g_cs + (g * 18 + c * 2 + half) * 216 + p * 72 + 2 * t;
    asm volatile("cp.async.wait_all;" ::: "memory");
    __syncthreads();
    if (tid < 96 && b < 192) asm volatile("prefetch.global.L2 [%0];" :: "l"(x + b * 6144 + tid * 64));
    if (tid >= 96 && tid < 120) asm volatile("prefetch.global.L2 [%0];" :: "l"(wo + b * 1536 + (tid - 96) * 64));
    uint32_t ov[3][4];
    const uint32_t* wr = &s_in[(half * 32 + (g8 >> 1) * 8 + (g8 & 1)) * 36 + (half * 4 + (g8 >> 1)) * 8 + t * 9 + c4];
    #pragma unroll
    for (int j = 0; j < 4; j++) {
        const uint32_t b0 = wr[j * 72], b1 = wr[j * 72 + 4], b2 = c4 == 0 ? wr[j * 72 + 8] : 0u;
        float c0[4] = {0.f, 0.f, 0.f, 0.f}, c1[4] = {0.f, 0.f, 0.f, 0.f};
        mma16816(c0, af[0][0], af[1][0], af[0][1], af[1][1], b0, b1);
        mma1688(c0, af[0][2], af[1][2], b2);
        mma16816(c1, af[2][0], 0u, af[2][1], 0u, b0, b1);
        mma1688(c1, af[2][2], 0u, b2);
        ov[0][j] = pack2(c0[0], c0[1]); ov[1][j] = pack2(c0[2], c0[3]); ov[2][j] = pack2(c1[0], c1[1]);
    }
    {
        const int nl = 2 * t + (g8 & 1);
        uint4* o = reinterpret_cast<uint4*>(dst) + ((g8 >> 1) * 8 + nl) * 8 + ((half * 4 + c4) ^ nl);
        o[0] = make_uint4(ov[0][0], ov[0][1], ov[0][2], ov[0][3]);
        o[256] = make_uint4(ov[1][0], ov[1][1], ov[1][2], ov[1][3]);
        if (g8 < 2) o[512] = make_uint4(ov[2][0], ov[2][1], ov[2][2], ov[2][3]);
    }
    {
        float cs0[4] = {0.f, 0.f, 0.f, 0.f}, cs1[4] = {0.f, 0.f, 0.f, 0.f};
        mma16816(cs0, ov[0][0], ov[1][0], ov[0][1], ov[1][1], 0x3f803f80u, 0x3f803f80u);
        mma16816(cs1, ov[2][0], 0u, ov[2][1], 0u, 0x3f803f80u, 0x3f803f80u);
        mma16816(cs0, ov[0][2], ov[1][2], ov[0][3], ov[1][3], 0x3f803f80u, 0x3f803f80u);
        mma16816(cs1, ov[2][2], 0u, ov[2][3], 0u, 0x3f803f80u, 0x3f803f80u);
        const int f = g8 + 8 * c4;
        if (f < 18) csd[8 * (f >> 1) + (f & 1)] = c4 == 0 ? cs0[0] : c4 == 1 ? cs0[2] : cs1[0];
    }
}

DEVI void dual_softmax(const float* a, float scale, uint32_t* o) {
    float mx = a[0], mn = a[0];
    #pragma unroll
    for (int j = 1; j < 18; j++) { mx = fmaxf(mx, a[j]); mn = fminf(mn, a[j]); }
    const float mxs = -mx * scale, mns = mn * scale;
    float ep[18], en[18], sp = 0.f, sn = 0.f;
    #pragma unroll
    for (int j = 0; j < 18; j++) {
        ep[j] = ex2(fmaf(a[j], scale, mxs)); sp += ep[j];
        en[j] = ex2(fmaf(a[j], -scale, mns)); sn += en[j];
    }
    const float rp = rcp(sp), rn = rcp(sn);
    #pragma unroll
    for (int j = 0; j < 9; j++) {
        o[j] = pack2(ep[2 * j] * rp, ep[2 * j + 1] * rp);
        o[9 + j] = pack2(en[2 * j] * rn, en[2 * j + 1] * rn);
    }
}

DEVI uint4 ldg128(const void* p) { uint4 v; asm volatile("ld.global.cg.v4.u32 {%0,%1,%2,%3}, [%4];" : "=r"(v.x), "=r"(v.y), "=r"(v.z), "=r"(v.w) : "l"(p)); return v; }
DEVI uint2 ldg64(const void* p) { uint2 v; asm volatile("ld.global.cg.v2.u32 {%0,%1}, [%2];" : "=r"(v.x), "=r"(v.y) : "l"(p)); return v; }
DEVI uint4 lds128(uint32_t a) { uint4 v; asm volatile("ld.shared.v4.u32 {%0,%1,%2,%3}, [%4];" : "=r"(v.x), "=r"(v.y), "=r"(v.z), "=r"(v.w) : "r"(a) : "memory"); return v; }
DEVI uint2 lds64(uint32_t a) { uint2 v; asm volatile("ld.shared.v2.u32 {%0,%1}, [%2];" : "=r"(v.x), "=r"(v.y) : "r"(a) : "memory"); return v; }
DEVI uint32_t packu(uint32_t lo, uint32_t hi) { return pack2(__uint_as_float(lo), __uint_as_float(hi)); }
DEVI void spin_ge(const unsigned int* p, unsigned int n) {
    uint32_t f; int it = 0;
    do {
        asm volatile("ld.acquire.gpu.global.u32 %0, [%1];" : "=r"(f) : "l"(p) : "memory");
        if (++it > (1 << 22)) __trap();
    } while (f < n);
}
constexpr int KA_PRE = 3, KA_REC = 5 * 16384, KA_B = 147456, KA_CS = KA_B + 9 * 9216, KA_LN = KA_CS + 864, KA_BAR = KA_LN + 1024, KA_SMEM = KA_BAR + 160;
static_assert(KA_SMEM <= 232448, "smem");
DEVI int gpc_pos() {
    unsigned smid, nsm;
    asm volatile("mov.u32 %0, %%smid;" : "=r"(smid));
    asm volatile("mov.u32 %0, %%nsmid;" : "=r"(nsm));
    if (nsm != 132) return blockIdx.x;
    const int tpc = smid >> 1, o = smid & 1;
    if (smid == 13 || smid == 15) return 124 + tpc;
    if (tpc < 32) return (tpc & 7) * 16 + (tpc >> 3) * 2 + o;
    if (tpc < 60) { const int j = tpc - 32, r = j / 7; return (1 + j - r * 7) * 16 + 8 + r * 2 + o; }
    if (tpc < 62) return o ? 68 + tpc : (tpc - 54) * 16 + 1;
    return 8 + (tpc - 62) * 2 + o;
}
__global__ void __launch_bounds__(640, 1) ka_front(const __grid_constant__ CUtensorMap tmXA, const bf16* __restrict__ x, const bf16* __restrict__ wo, const bf16* __restrict__ w1, const bf16* __restrict__ b1) {
    extern __shared__ __align__(1024) char smem[];
    const uint32_t sm = smem_u32(smem);
    const uint32_t bFull = sm + KA_BAR, bEmpty = bFull + 9 * 8, bLn = bEmpty + 9 * 8;
    const int tid = threadIdx.x, lane = tid & 31, warp = __shfl_sync(~0u, tid >> 5, 0);
    const int pos = gpc_pos();
    if (pos >= 128) {
        const int ns = pos - 128;
        if (tid == 0) {
            #pragma unroll
            for (int q = 0; q < 6; q++) mbar_init(bFull + q * 8, 1);
            fence_mbar_init();
            #pragma unroll
            for (int q = 0; q < 6; q++) mbar_expect(bFull + q * 8, 96 * 288);
        }
        __syncthreads();
        if (tid < 576) {
            const int h = tid / 18, d = tid - h * 18, r = (h >> 2) * 72 + (d < 16 ? 16 * (h & 3) + d : 48 + 2 * (h & 3) + d);
            bulk_g2s(sm + r * 304, wo + tid * 576 + ns * 144, 288, bFull + (r / 96) * 8);
        }
        #pragma unroll 1
        for (int q = 0; q < 6; q++) {
            const uint32_t ob = sm + 175104 + (q & 1) * 27648;
            mbar_wait(bFull + q * 8, 0);
            if (tid == 0) asm volatile("cp.async.bulk.wait_group.read 1;" ::: "memory");
            __syncthreads();
            if (warp < 18) {
                #pragma unroll
                for (int rb = 0; rb < 3; rb++) {
                    uint32_t r0, r1, r2, r3;
                    ldsm4t(sm + (q * 96 + rb * 32 + lane) * 304 + warp * 16, r0, r1, r2, r3);
                    stsm4(ob + (warp / 9) * 13824 + ((rb * 4 + (lane >> 3)) * 72 + (warp % 9) * 8 + (lane & 7)) * 16, r0, r1, r2, r3);
                }
            }
            fence_async_smem();
            __syncthreads();
            if (tid == 0) {
                bulk_s2g(g_wo + (ns * 2) * (72 * 576) + q * 6912, ob, 13824);
                bulk_s2g(g_wo + (ns * 2 + 1) * (72 * 576) + q * 6912, ob + 13824, 13824);
                bulk_commit();
            }
        }
        if (tid == 0) {
            asm volatile("cp.async.bulk.wait_group 0;\nfence.proxy.async.global;\nfence.acq_rel.gpu;" ::: "memory");
            pdl_wait();
            pdl_trigger();
        }
        return;
    }
    const int g = ((pos >> 4) & 1) * 4 + (pos & 3), mt = (pos >> 5) * 4 + ((pos >> 2) & 3);
    if (warp >= 16) {
        asm volatile("setmaxnreg.dec.sync.aligned.u32 32;");
        if (warp == 16) {
            if (lane == 0) {
                #pragma unroll
                for (int c = 0; c < 9; c++) { mbar_init(bFull + c * 8, 1); mbar_init(bEmpty + c * 8, 8); }
                mbar_init(bLn, 64);
                fence_mbar_init();
            }
            __syncwarp();
            bar_arrive(0, 640);
        } else {
            bar_sync(0, 640);
            if (tid == 544) {
                #pragma unroll
                for (int c = 0; c < 9; c++) mbar_expect(bFull + c * 8, 16384 + 9216);
            }
            __syncwarp();
        }
        if (tid == 512) {
            #pragma unroll
            for (int c = 0; c < KA_PRE; c++) tma3d(sm + c * 16384, &tmXA, bFull + c * 8, 0, mt * 128, c);
            pdl_wait();
            const bf16* wsrc = g_wqkv + g * (27 * 4608);
            const uint32_t sb = sm + KA_B;
            #pragma unroll
            for (int c = 0; c < 9; c++) {
                bulk_g2s(sb + c * 9216, wsrc + c * 4608, 9216, bFull + c * 8);
                const int xc = c + KA_PRE - 2;
                if (c >= 2 && xc < 9) tma3d(sm + xc * 16384, &tmXA, bFull + xc * 8, 0, mt * 128, xc);
            }
            pdl_trigger();
            #pragma unroll 1
            for (int p = 1; p < 3; p++) {
                #pragma unroll
                for (int c = 0; c < 9; c++) {
                    mbar_wait(bEmpty + c * 8, p - 1); mbar_expect(bFull + c * 8, 9216);
                    bulk_g2s(sb + c * 9216, wsrc + (p * 9 + c) * 4608, 9216, bFull + c * 8);
                }
            }
            l2_prefetch(w1 + pos * 13824, 27648);
            if (pos == 0) l2_prefetch(b1, 9216);
        } else if (warp == 17) {
            bar_sync(2, 160);
            if (lane == 0) spin_ge(g_cnt + g * CNT_S, 64);
            __syncwarp();
            bar_arrive(1, 288);
        } else if (warp >= 18) {
            const int m = warp - 18;
            {
                const unsigned long long* lp = g_ln + mt * 128 + m * 64 + (lane >> 3) * 16 + (lane & 7);
                unsigned long long r0, r1; int it = 0;
                __nanosleep(700);
                while (true) {
                    asm volatile("ld.relaxed.gpu.global.u64 %0, [%1];" : "=l"(r0) : "l"(lp) : "memory");
                    asm volatile("ld.relaxed.gpu.global.u64 %0, [%1];" : "=l"(r1) : "l"(lp + 8) : "memory");
                    if (__all_sync(~0u, (long long)(r0 & r1) < 0)) break;
                    if (++it > (1 << 22)) __trap();
                }
                sts128(sm + KA_LN + (m * 32 + lane) * 16, (uint32_t)r0, (uint32_t)(r0 >> 32), (uint32_t)r1, (uint32_t)(r1 >> 32));
                mbar_arrive(bLn);
            }
        }
    } else {
        const int xrow = mt * 128 + g * 16 + warp;
        uint4 xv[3];
        {
            const uint4* xr = reinterpret_cast<const uint4*>(x + xrow * D_);
            xv[0] = ldg128(xr + lane); xv[1] = ldg128(xr + lane + 32); xv[2] = ldg128(xr + 64 + (lane & 7));
        }
        asm volatile("setmaxnreg.inc.sync.aligned.u32 112;");
        bar_sync(0, 640);
        const int wg = warp >> 2, m = wg & 1, w4 = warp & 3, gq = lane >> 2, t = lane & 3;
        {
            const uint32_t w[12] = {xv[0].x, xv[0].y, xv[0].z, xv[0].w, xv[1].x, xv[1].y, xv[1].z, xv[1].w, xv[2].x, xv[2].y, xv[2].z, xv[2].w};
            float s = 0.f, s2 = 0.f;
            #pragma unroll
            for (int i = 0; i < 12; i++) { if (i < 8) s += bf_lo(w[i]) + bf_hi(w[i]); else s2 += bf_lo(w[i]) + bf_hi(w[i]); }
            if (lane < 8) s += s2;
            #pragma unroll
            for (int o = 16; o; o >>= 1) s += __shfl_xor_sync(~0u, s, o);
            const float mean = s * (1.f / D_);
            float q = 0.f, q2 = 0.f;
            #pragma unroll
            for (int i = 0; i < 12; i++) {
                const float e0 = bf_lo(w[i]) - mean, e1 = bf_hi(w[i]) - mean;
                if (i < 8) q += e0 * e0 + e1 * e1; else q2 += e0 * e0 + e1 * e1;
            }
            if (lane < 8) q += q2;
            #pragma unroll
            for (int o = 16; o; o >>= 1) q += __shfl_xor_sync(~0u, q, o);
            const unsigned long long lrec = ((unsigned long long)(__float_as_uint(rsqrtf(q * (1.f / D_) + LN_EPS)) | 0x80000000u) << 32) | __float_as_uint(mean);
            if (lane == 0) asm volatile("st.relaxed.gpu.global.u64 [%0], %1;" :: "l"(g_ln + xrow), "l"(lrec) : "memory");
        }
        float2 ln0, ln1;
        auto ln_get = [&]() {
            mbar_wait(bLn, 0);
            const uint4 v = lds128(sm + KA_LN + (m * 32 + w4 * 8 + gq) * 16);
            ln0 = make_float2(__uint_as_float(v.x), fabsf(__uint_as_float(v.y))); ln1 = make_float2(__uint_as_float(v.z), fabsf(__uint_as_float(v.w)));
        };
        const uint64_t da = mkdesc(sm + m * 8192, 16, 1024, 1), db = mkdesc(sm + KA_B, 16, 1024, 1);
        const uint32_t csa = sm + KA_CS + 8 * t;
        const int rot = (gq + 2 * t) & 7;
        const uint32_t rec = sm + KA_REC + t * 16384 + m * 8192 + (w4 * 16 + rot) * 128;
        const uint32_t pqs = sm + KA_B + m * (16 * PQ_UNIT);
        if (wg < 2) {
            float acc[36]; uint2 cs[9];
            #pragma unroll
            for (int c = 0; c < 9; c++) {
                mbar_wait(bFull + c * 8, 0);
                wg_fence();
                #pragma unroll
                for (int kk = 0; kk < 4; kk++) wgmma_n72<0, 0>(acc, dadv(da, c * 16384 + kk * 32), dadv(db, c * 9216 + kk * 32), (c | kk) != 0);
                wg_commit();
                if (c > 0) { wg_wait<1>(); if (lane == 0) mbar_arrive(bEmpty + (c - 1) * 8); }
            }
            wg_wait<0>();
            reg_fence<36>(acc);
            bar_arrive(5, 512);
            if (lane == 0) mbar_arrive(bEmpty + 8 * 8);
            bar_sync(6, 384);
            #pragma unroll
            for (int j = 0; j < 9; j++) cs[j] = lds64(csa + 32 * j);
            ln_get();
            uint32_t ph[2][18];
            #pragma unroll
            for (int r = 0; r < 2; r++) {
                float a[18];
                const float2 ln = r ? ln1 : ln0;
                #pragma unroll
                for (int j = 0; j < 9; j++) { a[2 * j] = fmaf(-ln.x, __uint_as_float(cs[j].x), acc[4 * j + 2 * r]); a[2 * j + 1] = fmaf(-ln.x, __uint_as_float(cs[j].y), acc[4 * j + 2 * r + 1]); }
                dual_softmax(a, ln.y * LOG2E, ph[r]);
            }
            #pragma unroll
            for (int j = 0; j < 18; j++) asm volatile("" : "+r"(ph[0][j]), "+r"(ph[1][j]));
            bar_sync(3 + m, 256);
            #pragma unroll
            for (int r = 0; r < 2; r++) {
                #pragma unroll
                for (int j = 0; j < 4; j++) sts128(rec + r * 1024 + ((j ^ rot) << 4), ph[r][4 * j], ph[r][4 * j + 1], ph[r][4 * j + 2], ph[r][4 * j + 3]);
                sts128(rec + r * 1024 + ((4 ^ rot) << 4), ph[r][16], ph[r][17], 0u, 0u);
            }
            fence_async_smem();
            bar_sync(8, 512);
            float ck[2][20];
            wg_fence();
            const uint64_t dr = mkdesc(sm + KA_REC + m * 32768, 8192, 1024, 1);
            #pragma unroll
            for (int ks = 0; ks < 8; ks++)
                #pragma unroll
                for (int hh = 0; hh < 2; hh++)
                    wgmma_n40<1, 1>(ck[hh], dadv(dr, hh * 16384 + ks * 2048), dadv(dr, hh * 16384 + ks * 2048), ks != 0);
            wg_commit();
            if (w4 < 2) bar_arrive(7, 512);
            wg_wait<0>();
            reg_fence<20>(ck[0]); reg_fence<20>(ck[1]);
            if (w4 >= 2) {
                #pragma unroll
                for (int hh = 0; hh < 2; hh++) {
                    float* kvh = g_kv + (g * 4 + m * 2 + hh) * KV_H;
                    #pragma unroll
                    for (int e = 0; e < 2; e++) {
                        const int nt = 2 * w4 + e - 5;
                        if (nt >= 0 && (nt < 2 || gq < 3)) {
                            float* p = kvh + nt * 320;
                            const float* q = ck[hh] + 2 * e;
                            asm volatile("red.global.add.v4.f32 [%0], {%1, %2, %3, %4};" :: "l"(p + lane * 4), "f"(q[0]), "f"(q[1]), "f"(q[4]), "f"(q[5]) : "memory");
                            asm volatile("red.global.add.v4.f32 [%0], {%1, %2, %3, %4};" :: "l"(p + 128 + lane * 4), "f"(q[8]), "f"(q[9]), "f"(q[12]), "f"(q[13]) : "memory");
                            if (t < 2) asm volatile("red.global.add.v2.f32 [%0], {%1, %2};" :: "l"(p + 256 + lane * 2), "f"(q[16]), "f"(q[17]) : "memory");
                        }
                    }
                }
                __syncwarp();
                bar_arrive(7, 512);
                if (lane == 0) asm volatile("red.release.gpu.global.add.u32 [%0], 1;" :: "l"(g_cnt + g * CNT_S) : "memory");
                __syncwarp();
                bar_arrive(2, 160);
            }
            const float* kp = g_kv + (g * 4 + w4) * KV_H + lane * 2;
            uint32_t* og = reinterpret_cast<uint32_t*>(g_o + (mt * 2 + m) * (64 * D_) + g * 4608);
            uint32_t* og2 = og + 8 * 256 + gq * 4 + w4;
            og += w4 * 512 + lane;
            asm volatile("" : "+l"(og), "+l"(og2));
            bar_sync(1, 288);
            uint4 u0[3], u1[3]; uint2 u2[3];
            #pragma unroll
            for (int n = 2; n >= 0; n--) { u0[n] = ldg128(kp + n * 320 + lane * 2); u1[n] = ldg128(kp + n * 320 + 128 + lane * 2); u2[n] = ldg64(kp + n * 320 + 256); }
            bar_sync(9 + m, 256);
            uint4 a0[4], a1[4]; uint2 at[4];
            #pragma unroll
            for (int mm = 0; mm < 4; mm++) {
                const uint32_t ub = pqs + (mm * 4 + w4) * PQ_UNIT;
                a0[mm] = lds128(ub + lane * 16); a1[mm] = lds128(ub + 512 + lane * 16); at[mm] = lds64(ub + 1024 + gq * 16 + (t & 1) * 8);
            }
            uint32_t bq[3][5];
            #pragma unroll
            for (int n = 0; n < 3; n++) {
                bq[n][0] = packu(u0[n].x, u0[n].y); bq[n][1] = packu(u0[n].z, u0[n].w);
                bq[n][2] = packu(u1[n].x, u1[n].y); bq[n][3] = packu(u1[n].z, u1[n].w);
                bq[n][4] = packu(u2[n].x, u2[n].y);
            }
            #pragma unroll
            for (int mp = 0; mp < 2; mp++) {
                float c[2][3][4];
                #pragma unroll
                for (int e = 0; e < 2; e++)
                    #pragma unroll
                    for (int n = 2; n >= 0; n--) {
                        c[e][n][0] = c[e][n][1] = c[e][n][2] = c[e][n][3] = 0.f;
                        mma16816(c[e][n], a0[2 * mp + e].x, a1[2 * mp + e].x, a0[2 * mp + e].y, a1[2 * mp + e].y, bq[n][0], bq[n][1]);
                    }
                #pragma unroll
                for (int e = 0; e < 2; e++)
                    #pragma unroll
                    for (int n = 2; n >= 0; n--) mma16816(c[e][n], a0[2 * mp + e].z, a1[2 * mp + e].z, a0[2 * mp + e].w, a1[2 * mp + e].w, bq[n][2], bq[n][3]);
                #pragma unroll
                for (int e = 0; e < 2; e++)
                    #pragma unroll
                    for (int n = 2; n >= 0; n--) mma1688(c[e][n], at[2 * mp + e].x, at[2 * mp + e].y, bq[n][4]);
                float rr[2][2];
                #pragma unroll
                for (int e = 0; e < 2; e++) {
                    rr[e][0] = __shfl_sync(~0u, c[e][2][0], (lane & 28) | 1); rr[e][1] = __shfl_sync(~0u, c[e][2][2], (lane & 28) | 1);
                }
                #pragma unroll
                for (int e = 0; e < 2; e++) {
                    const float r0 = rcp_full(rr[e][0] + 1e-6f), r1 = rcp_full(rr[e][1] + 1e-6f);
                    #pragma unroll
                    for (int n = 0; n < 3; n++) {
                        const uint32_t v0 = pack2(c[e][n][0] * r0, c[e][n][1] * r0), v1 = pack2(c[e][n][2] * r1, c[e][n][3] * r1);
                        uint32_t* op = (n < 2 ? og + n * 256 : og2) + (2 * mp + e) * 64;
                        if (n < 2 || t == 0) { op[0] = v0; op[32] = v1; }
                    }
                }
            }
        } else {
            float avq[36], acc[36]; uint2 cs[9];
            if (m == 1) {
                pdl_wait();
                if (tid < 384 + 108) {
                    uint2 pc[18];
                    #pragma unroll
                    for (int j = 0; j < 18; j++) pc[j] = ldg64(g_cs + (g * 18 + j) * 216 + (tid - 384) * 2);
                    float a = 0.f, c = 0.f;
                    #pragma unroll
                    for (int j = 0; j < 18; j++) { a += __uint_as_float(pc[j].x); c += __uint_as_float(pc[j].y); }
                    asm volatile("st.shared.v2.f32 [%0], {%1, %2};" :: "r"(sm + KA_CS + (tid - 384) * 8), "f"(a), "f"(c) : "memory");
                }
                bar_arrive(6, 384);
            }
            bar_sync(5, 512);
            #pragma unroll
            for (int i = 9; i < 22; i++) {
                const int c = i < 17 ? (i + 1) / 2 : i - 17;
                mbar_wait(bFull + (i % 9) * 8, (i / 9) & 1);
                wg_fence();
                #pragma unroll
                for (int kk = 0; kk < 4; kk++)
                    wgmma_n72<0, 0>((i < 17 && !(i & 1)) ? acc : avq, dadv(da, c * 16384 + kk * 32), dadv(db, (i % 9) * 9216 + kk * 32), i > 10 || kk != 0);
                wg_commit();
                if (i > 9 && i <= 18) { wg_wait<1>(); if (lane == 0) mbar_arrive(bEmpty + ((i - 1) % 9) * 8); }
                if (i == 17) bar_arrive(3 + m, 256);
                if (i == 18) bar_sync(14 + m, 128);
            }
            #pragma unroll
            for (int j = 0; j < 9; j++) cs[j] = lds64(csa + 288 + 32 * j);
            ln_get();
            wg_wait<0>();
            reg_fence<36>(avq);
            #pragma unroll
            for (int r = 0; r < 2; r++) {
                uint32_t pv[9];
                const float2 ln = r ? ln1 : ln0;
                #pragma unroll
                for (int j = 0; j < 9; j++)
                    pv[j] = pack2(fmaf(-ln.x, __uint_as_float(cs[j].x), avq[4 * j + 2 * r]) * ln.y, fmaf(-ln.x, __uint_as_float(cs[j].y), avq[4 * j + 2 * r + 1]) * ln.y);
                sts128(rec + r * 1024 + ((5 ^ rot) << 4), pv[0], pv[1], pv[2], pv[3]);
                sts128(rec + r * 1024 + ((6 ^ rot) << 4), pv[4], pv[5], pv[6], pv[7]);
                sts128(rec + r * 1024 + ((7 ^ rot) << 4), pv[8], 0x00003f80u, 0u, 0u);
            }
            fence_async_smem();
            bar_arrive(8, 512);
            const uint32_t sm2 = __shfl_sync(~0u, sm, 1);
            const uint64_t da2 = mkdesc(sm2 + m * 8192, 16, 1024, 1), db2 = mkdesc(sm2 + KA_B, 16, 1024, 1);
            #pragma unroll
            for (int i = 22; i < 27; i++) mbar_wait(bFull + (i % 9) * 8, 0);
            #pragma unroll
            for (int j = 0; j < 9; j++) cs[j] = lds64(csa + 576 + 32 * j);
            bar_sync(7, 512);
            wg_fence();
            #pragma unroll
            for (int i = 22; i < 27; i++)
                #pragma unroll
                for (int kk = 0; kk < 4; kk++) wgmma_n72<0, 0>(acc, dadv(da2, (i - 22) * 16384 + kk * 32), dadv(db2, (i % 9) * 9216 + kk * 32), 1);
            wg_commit();
            wg_wait<0>();
            reg_fence<36>(acc);
            uint32_t ph[2][18];
            #pragma unroll
            for (int r = 0; r < 2; r++) {
                float a[18];
                const float2 ln = r ? ln1 : ln0;
                #pragma unroll
                for (int j = 0; j < 9; j++) { a[2 * j] = fmaf(-ln.x, __uint_as_float(cs[j].x), acc[4 * j + 2 * r]); a[2 * j + 1] = fmaf(-ln.x, __uint_as_float(cs[j].y), acc[4 * j + 2 * r + 1]); }
                dual_softmax(a, ln.y * LOG2E, ph[r]);
            }
            #pragma unroll
            for (int j = 0; j < 18; j++) asm volatile("" : "+r"(ph[0][j]), "+r"(ph[1][j]));
            bar_sync(13, 256);
            const uint32_t ub = pqs + (w4 * 4 + t) * PQ_UNIT;
            #pragma unroll
            for (int r = 0; r < 2; r++)
                #pragma unroll
                for (int j = 0; j < 4; j++) sts128(ub + r * 512 + (gq * 4 + j) * 16, ph[r][j], ph[r][4 + j], ph[r][8 + j], ph[r][12 + j]);
            sts128(ub + 1024 + gq * 16, ph[0][16], ph[1][16], ph[0][17], ph[1][17]);
            bar_arrive(9 + m, 256);
        }
    }
}

constexpr int K2PRE = 2, K2_B = 73728, K2_PIECE = 27648, K2_X = K2_B + 5 * K2_PIECE, K2_BAR = K2_X + 18432, K2_SMEM = K2_BAR + 128;
__global__ void __cluster_dims__(2, 1, 1) __launch_bounds__(256, 1) k2_attn(const __grid_constant__ CUtensorMap tmX, const bf16* __restrict__ b2) {
    extern __shared__ __align__(1024) char smem[];
    const uint32_t sm = smem_u32(smem);
    const uint32_t bFull = sm + K2_BAR, bX = bFull + 6 * 8;
    const int tid = threadIdx.x, lane = tid & 31, warp = __shfl_sync(~0u, tid >> 5, 0);
    const int ns = blockIdx.x & 3, mt = blockIdx.x >> 2;
    const int wg = warp >> 2, w4 = warp & 3, gq = lane >> 2, t = lane & 3;
    const bf16* wsrc = g_wo + ns * (2 * 72 * 576);
    unsigned short bb0, bb1;
    asm volatile("ld.global.nc.u16 %0, [%1];" : "=h"(bb0) : "l"(b2 + mt * 64 + w4 * 16 + gq));
    asm volatile("ld.global.nc.u16 %0, [%1];" : "=h"(bb1) : "l"(b2 + mt * 64 + w4 * 16 + gq + 8));
    auto load_w = [&](int i) {
        bulk_g2s(sm + K2_B + (i % 5) * K2_PIECE, wsrc + i * (K2_PIECE / 4), K2_PIECE / 2, bFull + i * 8);
        bulk_g2s(sm + K2_B + (i % 5) * K2_PIECE + K2_PIECE / 2, wsrc + 72 * 576 + i * (K2_PIECE / 4), K2_PIECE / 2, bFull + i * 8);
    };
    if (tid == 0) {
        #pragma unroll
        for (int i = 0; i < 7; i++) mbar_init(bFull + i * 8, 1);
        fence_mbar_init();
        #pragma unroll
        for (int i = 0; i < 6; i++) mbar_expect(bFull + i * 8, K2_PIECE + 12288);
        mbar_expect(bX, 18432);
        #pragma unroll
        for (int i = 0; i < K2PRE; i++) load_w(i);
        prefetch_tm(&tmX);
    }
    __syncthreads();
    if (tid == 0) {
        pdl_wait();
        pdl_trigger();
        const bf16* osrc = g_o + mt * (64 * D_);
        #pragma unroll
        for (int i = 0; i < 6; i++) {
            bulk_g2s(sm + i * 12288, osrc + i * 6144, 12288, bFull + i * 8);
            if (i + 1 >= K2PRE && i < 4) load_w(i + 1);
        }
        tma2d(sm + K2_X, &tmX, bX, ns * 144, mt * 64);
        tma2d(sm + K2_X + 9216, &tmX, bX, ns * 144 + 72, mt * 64);
    }
    __syncwarp();
    {
        float acc[36];
        const uint32_t xs = sm + K2_X + wg * 9216;
        uint32_t xr[18];
        const int p = ns * 2 + wg;
        unsigned long long* sb = g_stats + (mt * 4 + w4) * 128 + gq * 2;
        unsigned long long* sw = sb + p * 16;
        const unsigned long long* sr = sb + t * 32;
        uint32_t* ndst = reinterpret_cast<uint32_t*>(g_hnT + (mt * D_ + p * 72) * 64) + w4 * 64 + lane;
        asm volatile("" : "+l"(sw), "+l"(sr), "+l"(ndst));
        const uint64_t da0 = mkdesc(sm, 1024, 128, 0), db0 = mkdesc(sm + K2_B + wg * (K2_PIECE / 2), 1152, 128, 0);
        #pragma unroll
        for (int i = 0; i < 6; i++) {
            mbar_wait(bFull + i * 8, 0);
            wg_fence();
            #pragma unroll
            for (int kk = 0; kk < 6; kk++)
                wgmma_n72<0, 0>(acc, dadv(da0, i * 12288 + kk * 2048), dadv(db0, (i % 5) * K2_PIECE + kk * 2304), (i | kk) != 0);
            wg_commit();
            if (i == 1) {
                wg_wait<1>();
                bar_sync(1 + wg, 128);
                if ((tid & 127) == 96) bulk_g2s(sm + K2_B + wg * (K2_PIECE / 2), wsrc + wg * (72 * 576) + 5 * (K2_PIECE / 4), K2_PIECE / 2, bFull + 5 * 8);
                __syncwarp();
            }
            if (i == 5) {
                mbar_wait(bX, 0);
                #pragma unroll
                for (int j = 0; j < 9; j++) {
                    xr[2 * j] = lds32(xs + (w4 * 16 + gq) * 144 + j * 16 + t * 4); xr[2 * j + 1] = lds32(xs + (w4 * 16 + gq + 8) * 144 + j * 16 + t * 4);
                }
            }
        }
        wg_wait<0>();
        reg_fence<36>(acc);
        #pragma unroll
        for (int j = 0; j < 18; j++) { acc[2 * j] += bf_lo(xr[j]); acc[2 * j + 1] += bf_hi(xr[j]); }
        float m0 = 0.f, m1 = 0.f;
        #pragma unroll
        for (int j = 0; j < 9; j++) { m0 += acc[4 * j] + acc[4 * j + 1]; m1 += acc[4 * j + 2] + acc[4 * j + 3]; }
        m0 *= (1.f / 18); m1 *= (1.f / 18);
        float q0 = 0.f, q1 = 0.f, q2 = 0.f, q3 = 0.f;
        #pragma unroll
        for (int j = 0; j < 9; j++) {
            float e;
            e = acc[4 * j] - m0; q0 = fmaf(e, e, q0); e = acc[4 * j + 1] - m0; q2 = fmaf(e, e, q2);
            e = acc[4 * j + 2] - m1; q1 = fmaf(e, e, q1); e = acc[4 * j + 3] - m1; q3 = fmaf(e, e, q3);
        }
        q0 += q2; q1 += q3;
        #pragma unroll
        for (int o = 1; o < 4; o <<= 1) {
            const float a0 = __shfl_xor_sync(~0u, m0, o), a1 = __shfl_xor_sync(~0u, m1, o), b0 = __shfl_xor_sync(~0u, q0, o), b1 = __shfl_xor_sync(~0u, q1, o);
            q0 += b0 + (a0 - m0) * (a0 - m0) * (9.f * o); q1 += b1 + (a1 - m1) * (a1 - m1) * (9.f * o);
            m0 = 0.5f * (m0 + a0); m1 = 0.5f * (m1 + a1);
        }
        if (t == 0) {
            const unsigned long long r0 = ((unsigned long long)(__float_as_uint(q0) | 0x80000000u) << 32) | __float_as_uint(m0);
            const unsigned long long r1 = ((unsigned long long)(__float_as_uint(q1) | 0x80000000u) << 32) | __float_as_uint(m1);
            asm volatile("st.relaxed.gpu.global.v2.u64 [%0], {%1, %2};" :: "l"(sw), "l"(r0), "l"(r1) : "memory");
        }
        unsigned long long ra, rb, rc, rd;
        {
            int it = 0;
            while (true) {
                asm volatile("ld.relaxed.gpu.global.v2.u64 {%0, %1}, [%2];" : "=l"(ra), "=l"(rc) : "l"(sr) : "memory");
                asm volatile("ld.relaxed.gpu.global.v2.u64 {%0, %1}, [%2];" : "=l"(rb), "=l"(rd) : "l"(sr + 16) : "memory");
                const bool ok = (long long)(ra & rb & rc & rd) < 0;
                if (__all_sync(~0u, ok)) break;
                if (++it > (1 << 22)) __trap();
            }
        }
        float sc[2], mu[2];
        #pragma unroll
        for (int r = 0; r < 2; r++) {
            const unsigned long long u = r ? rc : ra, v = r ? rd : rb;
            const float ma = __uint_as_float((uint32_t)u), mb = __uint_as_float((uint32_t)v);
            float ms = ma + mb;
            ms += __shfl_xor_sync(~0u, ms, 1); ms += __shfl_xor_sync(~0u, ms, 2);
            const float mean = ms * 0.125f;
            float M2 = fabsf(__uint_as_float((uint32_t)(u >> 32))) + fabsf(__uint_as_float((uint32_t)(v >> 32))) + 72.f * ((ma - mean) * (ma - mean) + (mb - mean) * (mb - mean));
            M2 += __shfl_xor_sync(~0u, M2, 1); M2 += __shfl_xor_sync(~0u, M2, 2);
            const float var = M2 * (1.f / D_);
            const float r1 = rsqrtf(var + LN_EPS);
            const float var2 = var * r1 * r1;
            const float r2 = rsqrtf(var2 + LN_EPS);
            sc[r] = 0.5f * (r1 * r2); mu[r] = mean;
        }
        #pragma unroll
        for (int j = 0; j < 9; j++) {
            ndst[j * 256] = pack2((acc[4 * j] - mu[0]) * sc[0], (acc[4 * j + 1] - mu[0]) * sc[0]);
            ndst[j * 256 + 32] = pack2((acc[4 * j + 2] - mu[1]) * sc[1], (acc[4 * j + 3] - mu[1]) * sc[1]);
        }
        if (p == 1 && t < 2) g_ln[mt * 64 + w4 * 16 + gq + 8 * t] = 0ull;
        if (p == 0 && t < 2) {
            asm volatile("" : "+h"(bb0), "+h"(bb1));
            g_rc[mt * 64 + w4 * 16 + gq + 8 * t] = make_float2(1.f / (t ? sc[1] : sc[0]), (t ? mu[1] : mu[0]) + __uint_as_float((uint32_t)(t ? bb1 : bb0) << 16));
        }
    }
}

constexpr int PFT = 4, W2HEAD = 9;
constexpr int K3_STAGES = 6, K3_STAGE = 36864, K3_STAG = 6, K3_PRE = 2, K3_BAR = K3_STAGES * K3_STAGE, K3_SMEM = K3_BAR + 256;
DEVI uint32_t gelu2(float a0, float a1) {
    const float z0 = a0 * fmaf(a0 * a0, 0.2854192650904f, 1.5957691216057f), z1 = a1 * fmaf(a1 * a1, 0.2854192650904f, 1.5957691216057f);
    return pack2(fmaf(a0, tanh_fast(z0), a0), fmaf(a1, tanh_fast(z1), a1));
}
template<int NB> DEVI void k3_store(const float* q, uint32_t* dst) {
    #pragma unroll
    for (int j = 0; j < NB; j++) { dst[j * 256] = gelu2(q[4 * j], q[4 * j + 1]); dst[j * 256 + 32] = gelu2(q[4 * j + 2], q[4 * j + 3]); }
}
DEVI void k3_typeb(uint32_t sm_, int fc_, float bias0, float bias1, const bf16* __restrict__ b1) {
    const uint32_t sm = __shfl_sync(~0u, sm_, 0);
    const int fc = __shfl_sync(~0u, fc_, 0);
    const uint32_t bFull = sm + K3_BAR, bEmpty = bFull + K3_STAGES * 8;
    const int tid = threadIdx.x, lane = tid & 31, warp = __shfl_sync(~0u, tid >> 5, 0);
    const int wg = warp >> 2, w4 = warp & 3, gq = lane >> 2;
    const uint32_t st = sm + wg * 8192;
    const uint64_t da0 = mkdesc(st, 8192, 1024, 1);
    int s = 0, ps = 0; uint32_t ph = 0;
    {
            const int f2 = (fc + 2) * 64 + w4 * 16 + gq;
            const float bias2 = 0.5f * __bfloat162float(b1[f2]), bias3 = 0.5f * __bfloat162float(b1[f2 + 8]);
            float acc[48], acc2[24];
            const uint64_t da2 = mkdesc(sm + 16384, 8192, 1024, 1), db0 = mkdesc(sm + 24576, 128, 1024, 0), db2 = mkdesc(sm + 24576 + wg * 6144, 128, 1024, 0);
            #pragma unroll 1
            for (int i = 0; i < 32 - K3_STAG; i++) {
                mbar_wait(bFull + s * 8, ph);
                const uint32_t so = s * K3_STAGE;
                wg_fence();
                #pragma unroll
                for (int kk = 0; kk < 4; kk++) {
                    wgmma_n96<1, 1>(acc, dadv(da0, so + kk * 2048), dadv(db0, so + kk * 256), (i | kk) != 0);
                    wgmma_n48<1, 1>(acc2, dadv(da2, so + kk * 2048), dadv(db2, so + kk * 256), (i | kk) != 0);
                }
                wg_commit();
                wg_wait<1>();
                if (i > 0 && lane == 0) mbar_arrive(bEmpty + ps * 8);
                ps = s;
                if (++s == K3_STAGES) { s = 0; ph ^= 1; }
            }
            if (wg == 1) {
                wg_wait<0>();
                if (lane == 0) mbar_arrive(bEmpty + ps * 8);
                #pragma unroll
                for (int i = 32 - K3_STAG; i < 32; i++) mbar_wait(bFull + (i % K3_STAGES) * 8, (i / K3_STAGES) & 1);
                bar_sync(3, 256);
            }
            #pragma unroll
            for (int i = 32 - K3_STAG; i < 32; i++) {
                if (wg == 0) mbar_wait(bFull + (i % K3_STAGES) * 8, (i / K3_STAGES) & 1);
                const uint32_t so = (i % K3_STAGES) * K3_STAGE;
                wg_fence();
                #pragma unroll
                for (int kk = 0; kk < 4; kk++) {
                    wgmma_n96<1, 1>(acc, dadv(da0, so + kk * 2048), dadv(db0, so + kk * 256), 1);
                    wgmma_n48<1, 1>(acc2, dadv(da2, so + kk * 2048), dadv(db2, so + kk * 256), 1);
                }
                wg_commit();
                if (i == 32 - K3_STAG && wg == 0) { wg_wait<1>(); if (lane == 0) mbar_arrive(bEmpty + ps * 8); }
            }
            if (wg == 0) bar_arrive(3, 256);
            wg_wait<0>();
            reg_fence<48>(acc); reg_fence<24>(acc2);
            #pragma unroll
            for (int j = 0; j < 48; j++) acc[j] += (j & 2) ? bias1 : bias0;
            #pragma unroll
            for (int j = 0; j < 24; j++) acc2[j] += (j & 2) ? bias3 : bias2;
            k3_store<12>(acc, reinterpret_cast<uint32_t*>(g_u + ((fc + wg) * D_ + 480) * 64) + w4 * 64 + lane);
            k3_store<6>(acc2, reinterpret_cast<uint32_t*>(g_u + ((fc + 2) * D_ + 480 + wg * 48) * 64) + w4 * 64 + lane);
    }
}
__global__ void __cluster_dims__(2, 1, 1) __launch_bounds__(288, 1) k3_mix1(const __grid_constant__ CUtensorMap tmW1a, const __grid_constant__ CUtensorMap tmW1b,
                                                                             const bf16* __restrict__ b1, const bf16* __restrict__ w1, const bf16* __restrict__ w2) {
    extern __shared__ __align__(1024) char smem[];
    const uint32_t sm = smem_u32(smem);
    const uint32_t bFull = sm + K3_BAR, bEmpty = bFull + K3_STAGES * 8;
    const int tid = threadIdx.x, lane = tid & 31, warp = __shfl_sync(~0u, tid >> 5, 0);
    const int cl = blockIdx.x >> 1, rank = blockIdx.x & 1;
    bool tb = false; int fc, d0;
    if (cl < 36) { fc = 2 * cl; d0 = 160 * rank; }
    else if (cl < 60) { const int q = (cl - 36) >> 1, e = (cl - 36) & 1; tb = rank; fc = rank ? 6 * q + 3 * e : 6 * q + 4 * e; d0 = rank ? 480 : 320; }
    else { fc = 6 * (2 * (cl - 60) + rank) + 2; d0 = 320; }
    const CUtensorMap* tm = tb ? &tmW1b : &tmW1a;
    const uint32_t abytes = tb ? 24576 : 16384;
    if (tid == 256) {
        #pragma unroll
        for (int i = 0; i < K3_STAGES; i++) { mbar_init(bFull + i * 8, 1); mbar_init(bEmpty + i * 8, 8); }
        fence_mbar_init();
        #pragma unroll
        for (int i = 0; i < K3_STAGES; i++) mbar_expect(bFull + i * 8, K3_STAGE);
        #pragma unroll
        for (int i = 0; i < K3_PRE; i++) tma3d(sm + i * K3_STAGE, tm, bFull + i * 8, 0, i * 64, fc);
    }
    __syncthreads();
    if (warp == 8) {
        if (tid == 256) {
            pdl_wait();
            pdl_trigger();
            const bf16* hs = g_hnT + d0 * 64;
            #pragma unroll
            for (int i = 0; i < K3_STAGES; i++) {
                bulk_g2s(sm + i * K3_STAGE + abytes, hs + i * (D_ * 64), K3_STAGE - abytes, bFull + i * 8);
                if (i >= K3_PRE) tma3d(sm + i * K3_STAGE, tm, bFull + i * 8, 0, i * 64, fc);
            }
            int s = 0; uint32_t ph = 0;
            #pragma unroll 1
            for (int i = K3_STAGES; i < 32; i++) {
                mbar_wait(bEmpty + s * 8, ph);
                mbar_expect(bFull + s * 8, K3_STAGE);
                tma3d(sm + s * K3_STAGE, tm, bFull + s * 8, 0, i * 64, fc);
                bulk_g2s(sm + s * K3_STAGE + abytes, hs + i * (D_ * 64), K3_STAGE - abytes, bFull + s * 8);
                if (i == 18 && blockIdx.x < 128) l2_prefetch(w1 + (size_t)(2048 - 64 * PFT) * F_ + blockIdx.x * (2304 * PFT), 4608 * PFT);
                if (++s == K3_STAGES) { s = 0; ph ^= 1; }
            }
            if (blockIdx.x < 128) l2_prefetch(w2 + (size_t)(blockIdx.x & 1) * (2304 * S_) + (blockIdx.x >> 1) * (W2HEAD * 2048), W2HEAD * 4096);
        }
    } else {
        const int wg = warp >> 2, w4 = warp & 3, gq = lane >> 2;
        const int f0 = (fc + wg) * 64 + w4 * 16 + gq;
        const float bias0 = 0.5f * __bfloat162float(b1[f0]), bias1 = 0.5f * __bfloat162float(b1[f0 + 8]);
        uint32_t* dst = reinterpret_cast<uint32_t*>(g_u + ((fc + wg) * D_ + d0) * 64) + w4 * 64 + lane;
        const uint32_t st = sm + wg * 8192;
        const uint64_t da0 = mkdesc(st, 8192, 1024, 1);
        int s = 0, ps = 0; uint32_t ph = 0;
        if (!tb) {
            float acc[80];
            #pragma unroll
            for (int j = 0; j < 80; j++) acc[j] = (j & 2) ? bias1 : bias0;
            reg_fence<80>(acc);
            const uint64_t db0 = mkdesc(sm + 16384, 128, 1024, 0);
            #pragma unroll 1
            for (int i = 0; i < 32 - K3_STAG; i++) {
                mbar_wait(bFull + s * 8, ph);
                const uint64_t da = dadv(da0, s * K3_STAGE), db = dadv(db0, s * K3_STAGE);
                wg_fence();
                #pragma unroll
                for (int kk = 0; kk < 4; kk++)
                    wgmma_n160<1, 1>(acc, dadv(da, kk * 2048), dadv(db, kk * 256), 1);
                wg_commit();
                wg_wait<1>();
                if (i > 0 && lane == 0) mbar_arrive(bEmpty + ps * 8);
                ps = s;
                if (++s == K3_STAGES) { s = 0; ph ^= 1; }
            }
            if (wg == 1) {
                wg_wait<0>();
                if (lane == 0) mbar_arrive(bEmpty + ps * 8);
                #pragma unroll
                for (int i = 32 - K3_STAG; i < 32; i++) mbar_wait(bFull + (i % K3_STAGES) * 8, (i / K3_STAGES) & 1);
                bar_sync(3, 256);
            }
            #pragma unroll
            for (int i = 32 - K3_STAG; i < 32; i++) {
                if (wg == 0) mbar_wait(bFull + (i % K3_STAGES) * 8, (i / K3_STAGES) & 1);
                wg_fence();
                #pragma unroll
                for (int kk = 0; kk < 4; kk++)
                    wgmma_n160<1, 1>(acc, dadv(da0, (i % K3_STAGES) * K3_STAGE + kk * 2048), dadv(db0, (i % K3_STAGES) * K3_STAGE + kk * 256), 1);
                wg_commit();
                if (i == 32 - K3_STAG && wg == 0) { wg_wait<1>(); if (lane == 0) mbar_arrive(bEmpty + ps * 8); }
            }
            if (wg == 0) bar_arrive(3, 256);
            wg_wait<0>();
            reg_fence<80>(acc);
            k3_store<20>(acc, dst);
        } else {
            k3_typeb(sm, fc, bias0, bias1, b1);
        }
    }
}

constexpr int SLOTC = 700, SLOTP = 578, K4A0 = 1, K4_PD = 4;
constexpr int K4_STAGES = 5, K4_STAGE = 8192 + 36864, K4_STAG = 3, K4_BAR = K4_STAGES * K4_STAGE, K4_SMEM = K4_BAR + 256;
constexpr int K4_XS = (36 - K4_STAG - 1) % K4_STAGES;
__global__ void __cluster_dims__(2, 1, 1) __launch_bounds__(288, 1) k4_mix2(const __grid_constant__ CUtensorMap tmW2, const __grid_constant__ CUtensorMap tmOut) {
    extern __shared__ __align__(1024) char smem[];
    const uint32_t sm = smem_u32(smem);
    const uint32_t bFull = sm + K4_BAR, bEmpty = bFull + K4_STAGES * 8, bP = bEmpty + K4_STAGES * 8, bRdy = bP + 16, bH = bRdy + 8;
    const int tid = threadIdx.x, lane = tid & 31, warp = __shfl_sync(~0u, tid >> 5, 0);
    const int ks = blockIdx.x & 1, tm = (blockIdx.x >> 1) & 31, tn = blockIdx.x >> 6;
    const int k0 = ks * 36;
    if (tid == 256) {
        #pragma unroll
        for (int i = 0; i < K4_STAGES; i++) { mbar_init(bFull + i * 8, 1); mbar_init(bEmpty + i * 8, 8); }
        mbar_init(bP, 1); mbar_init(bP + 8, 1); mbar_init(bRdy, 8); mbar_init(bH, 1);
        fence_mbar_init();
        #pragma unroll
        for (int i = 0; i < K4A0; i++) tma3d(sm + i * K4_STAGE, &tmW2, bFull + i * 8, 0, (k0 + i) * 64, tm);
    }
    __syncthreads();
    cluster_arrive_relaxed();
    if (tid == 0) {
        #pragma unroll
        for (int i = K4A0; i < 2; i++) tma3d(sm + i * K4_STAGE, &tmW2, bFull + i * 8, 0, (k0 + i) * 64, tm);
    }
    if (tid == 32) {
        #pragma unroll
        for (int i = 0; i < K4_STAGES; i++) mbar_expect(bFull + i * 8, K4_STAGE);
    }
    if (tid == 128) { mbar_expect(bP, 9216); mbar_expect(bP + 8, 9216); prefetch_tm(&tmOut); }
    __syncwarp();
    if (warp == 8) {
        if (lane == 0) {
            pdl_wait();
            const bf16* us = g_u + ((size_t)k0 * D_ + tn * 288) * 64;
            uint32_t slot = clock() + SLOTC;
            #pragma unroll
            for (int i = 0; i < K4_STAGES; i++) {
                if (i >= 2) { tma3d(sm + i * K4_STAGE, &tmW2, bFull + i * 8, 0, (k0 + i) * 64, tm); while ((int)(clock() - slot) < 0) {} slot += SLOTP; }
                bulk_g2s(sm + i * K4_STAGE + 8192, us + (size_t)i * (D_ * 64), 36864, bFull + i * 8);
            }
            int s = 0; uint32_t ph = 0;
            #pragma unroll 1
            for (int i = K4_STAGES; i < 36; i++) {
                mbar_wait(bEmpty + s * 8, ph);
                mbar_expect(bFull + s * 8, K4_STAGE);
                tma3d(sm + s * K4_STAGE, &tmW2, bFull + s * 8, 0, (k0 + i) * 64, tm);
                if (i + K4_PD < 36 && ((i ^ tn) & 1)) tma3d_prefetch(&tmW2, 0, (k0 + i + K4_PD) * 64, tm);
                if (i < 32) { while ((int)(clock() - slot) < 0) {} slot += SLOTP; }
                bulk_g2s(sm + s * K4_STAGE + 8192, us + (size_t)i * (D_ * 64), 36864, bFull + s * 8);
                if (++s == K4_STAGES) { s = 0; ph ^= 1; }
            }
            static_assert(K4_STAG <= 3, "stage of step 31 is free");
            mbar_wait(bEmpty + s * 8, ph);
            mbar_expect(bH, 18432);
            bulk_g2s(sm + (31 % K4_STAGES) * K4_STAGE, g_hnT + (tm * D_ + tn * 288 + ks * 144) * 64, 18432, bH);
        }
        __syncwarp();
        cluster_wait();
        #pragma unroll
        for (int hh = 0; hh < 2; hh++) {
            bar_sync(4 + hh, 160);
            if (lane == 0) {
                tma2d_store(&tmOut, sm + K4_XS * K4_STAGE + 24576 + hh * 9216, tn * 288 + ks * 144 + hh * 72, tm * 64);
                bulk_commit();
            }
            __syncwarp();
        }
        if (lane == 0) { bulk_wait_read(); }
    } else {
        const int wg = warp >> 2, w4 = warp & 3, tw = tid & 127;
        const bool keep = wg == ks;
        float acc[72];
        const uint64_t da0 = mkdesc(sm, 8192, 1024, 1), db0 = mkdesc(sm + 8192 + wg * 18432, 128, 1024, 0);
        const uint32_t rdy = mapa(bRdy, ks ^ 1);
        cluster_wait();
        int s = 0, ps = 0; uint32_t ph = 0;
        #pragma unroll 1
        for (int i = 0; i < 36 - K4_STAG; i++) {
            mbar_wait(bFull + s * 8, ph);
            const uint64_t da = dadv(da0, s * K4_STAGE), db = dadv(db0, s * K4_STAGE);
            wg_fence();
            #pragma unroll
            for (int kk = 0; kk < 4; kk++)
                wgmma_n144<1, 1>(acc, dadv(da, kk * 2048), dadv(db, kk * 256), (i | kk) != 0);
            wg_commit();
            wg_wait<1>();
            if (i > 0 && lane == 0) mbar_arrive(bEmpty + ps * 8);
            ps = s;
            if (++s == K4_STAGES) { s = 0; ph ^= 1; }
        }
        const uint32_t xa = sm + K4_XS * K4_STAGE + tw * 16;
        const uint2 rc0 = ldg64(g_rc + tm * 64 + w4 * 16 + (lane >> 2)), rc1 = ldg64(g_rc + tm * 64 + w4 * 16 + (lane >> 2) + 8);
        float res[36];
        const uint32_t ya = sm + (31 % K4_STAGES) * K4_STAGE + 20480 + tw * 16;
        auto residual = [&](int hh) {
            uint32_t hp[20];
            mbar_wait(bH, 0);
            const uint32_t ha = sm + (31 % K4_STAGES) * K4_STAGE + hh * 9216 + (lane >> 4) * 1024 + w4 * 256 + (lane & 15) * 16;
            #pragma unroll
            for (int j = 0; j < 5; j++)
                asm volatile("ldmatrix.sync.aligned.m8n8.x4.shared.b16 {%0,%1,%2,%3}, [%4];" : "=r"(hp[4 * j]), "=r"(hp[4 * j + 1]), "=r"(hp[4 * j + 2]), "=r"(hp[4 * j + 3]) : "r"(ha + j * 2048) : "memory");
            #pragma unroll
            for (int j = 0; j < 18; j++) {
                const float is = __uint_as_float((j & 1) ? rc1.x : rc0.x), of = __uint_as_float((j & 1) ? rc1.y : rc0.y);
                res[2 * j] = fmaf(bf_lo(hp[j]), is, of); res[2 * j + 1] = fmaf(bf_hi(hp[j]), is, of);
            }
            reg_fence<36>(res);
        };
        auto partial = [&](int hh) {
            mbar_wait(bP + hh * 8, 0);
            uint32_t o[18];
            #pragma unroll
            for (int j = 0; j < 4; j++) { const uint4 v = lds128(xa + hh * 10240 + j * 2048); o[4 * j] = v.x; o[4 * j + 1] = v.y; o[4 * j + 2] = v.z; o[4 * j + 3] = v.w; }
            { const uint2 v = lds64(xa + hh * 10240 + 8192); o[16] = v.x; o[17] = v.y; }
            #pragma unroll
            for (int j = 0; j < 18; j++) { res[2 * j] += bf_lo(o[j]); res[2 * j + 1] += bf_hi(o[j]); }
        };
        if (!keep) {
            #pragma unroll
            for (int i = 36 - K4_STAG; i < 36; i++) {
                mbar_wait(bFull + (i % K4_STAGES) * 8, (i / K4_STAGES) & 1);
                wg_fence();
                #pragma unroll
                for (int kk = 0; kk < 4; kk++)
                    wgmma_n144<1, 1>(acc, dadv(da0, (i % K4_STAGES) * K4_STAGE + kk * 2048), dadv(db0, (i % K4_STAGES) * K4_STAGE + kk * 256), 1);
                wg_commit();
                if (i == 36 - K4_STAG) { wg_wait<1>(); if (lane == 0) mbar_arrive_remote(rdy); }
            }
            bar_arrive(3, 256);
            mbar_wait(bRdy, 0);
            wg_wait<0>();
            reg_fence<72>(acc);
            const uint32_t rd = mapa(xa, ks ^ 1), rb = mapa(bP, ks ^ 1);
            #pragma unroll
            for (int hh = 0; hh < 2; hh++) {
                const float* q = acc + hh * 36;
                #pragma unroll
                for (int j = 0; j < 4; j++)
                    asm volatile("st.async.shared::cluster.mbarrier::complete_tx::bytes.v4.b32 [%0], {%1,%2,%3,%4}, [%5];"
                                 :: "r"(rd + hh * 10240 + j * 2048), "r"(pack2(q[8 * j], q[8 * j + 1])), "r"(pack2(q[8 * j + 2], q[8 * j + 3])),
                                    "r"(pack2(q[8 * j + 4], q[8 * j + 5])), "r"(pack2(q[8 * j + 6], q[8 * j + 7])), "r"(rb + hh * 8) : "memory");
                asm volatile("st.async.shared::cluster.mbarrier::complete_tx::bytes.v2.b32 [%0], {%1,%2}, [%3];"
                             :: "r"(rd + hh * 10240 + 8192), "r"(pack2(q[32], q[33])), "r"(pack2(q[34], q[35])), "r"(rb + hh * 8) : "memory");
            }
            residual(1);
            partial(1);
            reg_fence<36>(res);
            bar_sync(1, 256);
            #pragma unroll
            for (int j = 0; j < 9; j++) {
                const uint4 v = lds128(ya + j * 2048);
                res[4 * j] += __uint_as_float(v.x); res[4 * j + 1] += __uint_as_float(v.y); res[4 * j + 2] += __uint_as_float(v.z); res[4 * j + 3] += __uint_as_float(v.w);
            }
        } else {
            wg_wait<0>();
            if (lane == 0) mbar_arrive_remote(rdy);
            #pragma unroll
            for (int i = 36 - K4_STAG; i < 36; i++) mbar_wait(bFull + (i % K4_STAGES) * 8, (i / K4_STAGES) & 1);
            bar_sync(3, 256);
            wg_fence();
            #pragma unroll
            for (int i = 36 - K4_STAG; i < 36; i++)
                #pragma unroll
                for (int kk = 0; kk < 4; kk++)
                    wgmma_n144<1, 1>(acc, dadv(da0, (i % K4_STAGES) * K4_STAGE + kk * 2048), dadv(db0, (i % K4_STAGES) * K4_STAGE + kk * 256), 1);
            wg_commit();
            residual(0);
            wg_wait<0>();
            reg_fence<72>(acc);
            #pragma unroll
            for (int j = 0; j < 9; j++)
                sts128(ya + j * 2048, __float_as_uint(acc[36 + 4 * j]), __float_as_uint(acc[37 + 4 * j]), __float_as_uint(acc[38 + 4 * j]), __float_as_uint(acc[39 + 4 * j]));
            bar_arrive(1, 256);
            #pragma unroll
            for (int j = 0; j < 36; j++) res[j] += acc[j];
            partial(0);
        }
        const int hh = keep ? 0 : 1;
        uint32_t o[18];
        #pragma unroll
        for (int j = 0; j < 18; j++) o[j] = pack2(res[2 * j], res[2 * j + 1]);
        const uint32_t ad = sm + K4_XS * K4_STAGE + 24576 + hh * 9216 + (w4 * 16 + ((lane >> 3) & 1) * 8 + (lane & 7)) * 144;
        #pragma unroll
        for (int j = 0; j < 4; j++) stsm4(ad + (lane >> 4) * 16 + j * 32, o[4 * j], o[4 * j + 1], o[4 * j + 2], o[4 * j + 3]);
        stsm2(ad + 128, o[16], o[17]);
        fence_async_smem();
        bar_arrive(4 + hh, 160);
    }
}

typedef CUresult (*EncFn)(CUtensorMap*, CUtensorMapDataType, cuuint32_t, void*, const cuuint64_t*, const cuuint64_t*, const cuuint32_t*,
                          const cuuint32_t*, CUtensorMapInterleave, CUtensorMapSwizzle, CUtensorMapL2promotion, CUtensorMapFloatOOBfill);

template <typename... KArgs, typename... Args>
static void launch(void (*kern)(KArgs...), dim3 grid, int block, int smem, bool pdl, Args... args) {
    cudaLaunchConfig_t cfg = {};
    cfg.gridDim = grid; cfg.blockDim = dim3(block); cfg.dynamicSmemBytes = smem; cfg.stream = cudaStreamPerThread;
    cudaLaunchAttribute at[1];
    at[0].id = cudaLaunchAttributeProgrammaticStreamSerialization; at[0].val.programmaticStreamSerializationAllowed = 1;
    cfg.attrs = at; cfg.numAttrs = pdl ? 1 : 0;
    cudaLaunchKernelEx(&cfg, kern, args...);
}

extern "C" void kernel_launch(void* const* d_in, const int* in_sizes, int n_in, void* d_out, int out_size) {
    const bf16* x = (const bf16*)d_in[0];
    const bf16* wqkv = (const bf16*)d_in[1];
    const bf16* wphi = (const bf16*)d_in[2];
    const bf16* wo = (const bf16*)d_in[3];
    const bf16* w1 = (const bf16*)d_in[5];
    const bf16* b1 = (const bf16*)d_in[6];
    const bf16* w2 = (const bf16*)d_in[7];
    const bf16* b2 = (const bf16*)d_in[8];
    static EncFn enc = nullptr;
    if (!enc) {
        void* fn = nullptr; cudaDriverEntryPointQueryResult qr;
        cudaGetDriverEntryPoint("cuTensorMapEncodeTiled", &fn, cudaEnableDefault, &qr);
        enc = (EncFn)fn;
        cudaFuncSetAttribute(ka_front, cudaFuncAttributeMaxDynamicSharedMemorySize, KA_SMEM);
        cudaFuncSetAttribute(k2_attn, cudaFuncAttributeMaxDynamicSharedMemorySize, K2_SMEM);
        cudaFuncSetAttribute(k3_mix1, cudaFuncAttributeMaxDynamicSharedMemorySize, K3_SMEM);
        cudaFuncSetAttribute(k4_mix2, cudaFuncAttributeMaxDynamicSharedMemorySize, K4_SMEM);
    }
    CUtensorMap tmW1, tmW1b, tmW2, tmOut, tmX, tmXA;
    const cuuint32_t es[3] = {1, 1, 1};
    {
        cuuint64_t dims[3] = {64, (cuuint64_t)S_, (cuuint64_t)(F_ / 64)}; cuuint64_t st[2] = {(cuuint64_t)F_ * 2, 128}; cuuint32_t box[3] = {64, 64, 2};
        enc(&tmW1, CU_TENSOR_MAP_DATA_TYPE_BFLOAT16, 3, (void*)w1, dims, st, box, es, CU_TENSOR_MAP_INTERLEAVE_NONE, CU_TENSOR_MAP_SWIZZLE_128B, CU_TENSOR_MAP_L2_PROMOTION_L2_128B, CU_TENSOR_MAP_FLOAT_OOB_FILL_NONE);
        box[2] = 3;
        enc(&tmW1b, CU_TENSOR_MAP_DATA_TYPE_BFLOAT16, 3, (void*)w1, dims, st, box, es, CU_TENSOR_MAP_INTERLEAVE_NONE, CU_TENSOR_MAP_SWIZZLE_128B, CU_TENSOR_MAP_L2_PROMOTION_L2_128B, CU_TENSOR_MAP_FLOAT_OOB_FILL_NONE);
    }
    {
        cuuint64_t dims[3] = {64, (cuuint64_t)F_, (cuuint64_t)(S_ / 64)}; cuuint64_t st[2] = {(cuuint64_t)S_ * 2, 128}; cuuint32_t box[3] = {64, 64, 1};
        enc(&tmW2, CU_TENSOR_MAP_DATA_TYPE_BFLOAT16, 3, (void*)w2, dims, st, box, es, CU_TENSOR_MAP_INTERLEAVE_NONE, CU_TENSOR_MAP_SWIZZLE_128B, CU_TENSOR_MAP_L2_PROMOTION_L2_128B, CU_TENSOR_MAP_FLOAT_OOB_FILL_NONE);
    }
    {
        cuuint64_t dims[2] = {(cuuint64_t)D_, (cuuint64_t)S_}; cuuint64_t st[1] = {(cuuint64_t)D_ * 2}; cuuint32_t box[2] = {72, 64};
        enc(&tmOut, CU_TENSOR_MAP_DATA_TYPE_BFLOAT16, 2, d_out, dims, st, box, es, CU_TENSOR_MAP_INTERLEAVE_NONE, CU_TENSOR_MAP_SWIZZLE_NONE, CU_TENSOR_MAP_L2_PROMOTION_NONE, CU_TENSOR_MAP_FLOAT_OOB_FILL_NONE);
        enc(&tmX, CU_TENSOR_MAP_DATA_TYPE_BFLOAT16, 2, (void*)x, dims, st, box, es, CU_TENSOR_MAP_INTERLEAVE_NONE, CU_TENSOR_MAP_SWIZZLE_NONE, CU_TENSOR_MAP_L2_PROMOTION_NONE, CU_TENSOR_MAP_FLOAT_OOB_FILL_NONE);
    }
    {
        cuuint64_t dims[3] = {64, (cuuint64_t)S_, 9}; cuuint64_t st[2] = {(cuuint64_t)D_ * 2, 128}; cuuint32_t box[3] = {64, 128, 1};
        enc(&tmXA, CU_TENSOR_MAP_DATA_TYPE_BFLOAT16, 3, (void*)x, dims, st, box, es, CU_TENSOR_MAP_INTERLEAVE_NONE, CU_TENSOR_MAP_SWIZZLE_128B, CU_TENSOR_MAP_L2_PROMOTION_L2_128B, CU_TENSOR_MAP_FLOAT_OOB_FILL_NONE);
    }
    launch(k0_prep, dim3(9, 8, 4), 256, 0, false, x, wqkv, wphi, wo);
    launch(ka_front, 132, 640, KA_SMEM, true, tmXA, x, wo, w1, b1);
    launch(k2_attn, 128, 256, K2_SMEM, true, tmX, b2);
    launch(k3_mix1, 132, 288, K3_SMEM, true, tmW1, tmW1b, b1, w1, w2);
    launch(k4_mix2, 128, 288, K4_SMEM, true, tmW2, tmOut);
}
```

```cpp
#include <cuda_runtime.h>
#include <cuda.h>
#include <cuda_bf16.h>
#include <stdint.h>

typedef __nv_bfloat16 bf16;
#define DEVI __device__ __forceinline__

constexpr int S_ = 2048, D_ = 576, F_ = 4608;
constexpr float LN_EPS = 1e-5f;
constexpr float LOG2E = 1.4426950408889634f;

__device__ __align__(1024) bf16 g_o[S_ * D_];
__device__ __align__(1024) bf16 g_wqkv[8 * 27 * 72 * 64];
__device__ __align__(16) float g_cs[8 * 18 * 216];
__device__ __align__(1024) bf16 g_wo[8 * 72 * 72 * 8];
constexpr int KV_H = 960;
__device__ __align__(1024) float g_kv[32 * KV_H];
__device__ __align__(1024) unsigned long long g_stats[S_ * 8];
__device__ __align__(16) unsigned long long g_ln[S_];
__device__ __align__(16) float2 g_rc[S_];
__device__ __align__(1024) bf16 g_hnT[D_ * S_];
__device__ __align__(1024) bf16 g_u[D_ * F_];
constexpr int CNT_S = 64;
__device__ __align__(256) unsigned int g_cnt[8 * CNT_S];

DEVI uint32_t smem_u32(const void* p) { return (uint32_t)__cvta_generic_to_shared(p); }
DEVI void mbar_init(uint32_t bar, int cnt) { asm volatile("mbarrier.init.shared::cta.b64 [%0], %1;" :: "r"(bar), "r"(cnt) : "memory"); }
DEVI void mbar_expect(uint32_t bar, uint32_t bytes) { asm volatile("mbarrier.arrive.expect_tx.shared::cta.b64 _, [%0], %1;" :: "r"(bar), "r"(bytes) : "memory"); }
DEVI void mbar_wait(uint32_t bar, uint32_t parity) {
    asm volatile("{\n.reg .pred p;\n.reg .u32 it;\n"
                 "mbarrier.try_wait.parity.shared::cta.b64 p, [%0], %1;\n@p bra MW_DONE;\n"
                 "mov.u32 it, 0;\n"
                 "MW_LOOP:\nmbarrier.try_wait.parity.shared::cta.b64 p, [%0], %1;\n@p bra MW_DONE;\n"
                 "add.u32 it, it, 1;\nsetp.lt.u32 p, it, 4194304;\n@p bra MW_LOOP;\ntrap;\n"
                 "MW_DONE:\n}" :: "r"(bar), "r"(parity) : "memory");
}
DEVI void mbar_arrive(uint32_t bar) { asm volatile("mbarrier.arrive.shared::cta.b64 _, [%0];" :: "r"(bar) : "memory"); }
DEVI uint32_t mapa(uint32_t addr, uint32_t cta) { uint32_t r; asm volatile("mapa.shared::cluster.u32 %0, %1, %2;" : "=r"(r) : "r"(addr), "r"(cta)); return r; }
DEVI void mbar_arrive_remote(uint32_t raddr) { asm volatile("mbarrier.arrive.shared::cluster.b64 _, [%0];" :: "r"(raddr) : "memory"); }
DEVI void fence_mbar_init() { asm volatile("fence.mbarrier_init.release.cluster;" ::: "memory"); }
DEVI void fence_async_smem() { asm volatile("fence.proxy.async.shared::cta;" ::: "memory"); }
DEVI void cluster_arrive_relaxed() { asm volatile("barrier.cluster.arrive.relaxed.aligned;" ::: "memory"); }
DEVI void cluster_wait() { asm volatile("barrier.cluster.wait.aligned;" ::: "memory"); }
DEVI void bar_sync(int id, int n) { asm volatile("bar.sync %0, %1;" :: "r"(id), "r"(n) : "memory"); }
DEVI void bar_arrive(int id, int n) { asm volatile("bar.arrive %0, %1;" :: "r"(id), "r"(n) : "memory"); }
DEVI void pdl_wait() { asm volatile("griddepcontrol.wait;" ::: "memory"); }
DEVI void pdl_trigger() { asm volatile("griddepcontrol.launch_dependents;" ::: "memory"); }
DEVI void bulk_g2s(uint32_t dst, const void* src, uint32_t bytes, uint32_t bar) {
    asm volatile("cp.async.bulk.shared::cluster.global.mbarrier::complete_tx::bytes [%0], [%1], %2, [%3];" :: "r"(dst), "l"(src), "r"(bytes), "r"(bar) : "memory");
}
DEVI void bulk_s2g(void* dst, uint32_t src, uint32_t bytes) {
    asm volatile("cp.async.bulk.global.shared::cta.bulk_group [%0], [%1], %2;" :: "l"(dst), "r"(src), "r"(bytes) : "memory");
}
DEVI void l2_prefetch(const void* p, uint32_t bytes) { asm volatile("cp.async.bulk.prefetch.L2.global [%0], %1;" :: "l"(p), "r"(bytes) : "memory"); }
DEVI void bulk_commit() { asm volatile("cp.async.bulk.commit_group;" ::: "memory"); }
DEVI void bulk_wait_read() { asm volatile("cp.async.bulk.wait_group.read 0;" ::: "memory"); }
DEVI void tma2d(uint32_t dst, const CUtensorMap* tm, uint32_t bar, int c0, int c1) {
    asm volatile("cp.async.bulk.tensor.2d.shared::cluster.global.mbarrier::complete_tx::bytes [%0], [%1, {%3, %4}], [%2];" :: "r"(dst), "l"(tm), "r"(bar), "r"(c0), "r"(c1) : "memory");
}
DEVI void tma3d(uint32_t dst, const CUtensorMap* tm, uint32_t bar, int c0, int c1, int c2) {
    asm volatile("cp.async.bulk.tensor.3d.shared::cluster.global.mbarrier::complete_tx::bytes [%0], [%1, {%3, %4, %5}], [%2];" :: "r"(dst), "l"(tm), "r"(bar), "r"(c0), "r"(c1), "r"(c2) : "memory");
}
DEVI void tma3d_prefetch(const CUtensorMap* tm, int c0, int c1, int c2) {
    asm volatile("cp.async.bulk.prefetch.tensor.3d.L2.global [%0, {%1, %2, %3}];" :: "l"(tm), "r"(c0), "r"(c1), "r"(c2) : "memory");
}
DEVI void tma2d_store(const CUtensorMap* tm, uint32_t src, int c0, int c1) {
    asm volatile("cp.async.bulk.tensor.2d.global.shared::cta.bulk_group [%0, {%2, %3}], [%1];" :: "l"(tm), "r"(src), "r"(c0), "r"(c1) : "memory");
}
DEVI void prefetch_tm(const CUtensorMap* tm) { asm volatile("prefetch.tensormap [%0];" :: "l"(tm) : "memory"); }
DEVI uint64_t mkdesc(uint32_t addr, uint32_t lbo, uint32_t sbo, uint64_t swz) {
    return (uint64_t)((addr & 0x3FFFF) >> 4) | ((uint64_t)(lbo >> 4) << 16) | ((uint64_t)(sbo >> 4) << 32) | (swz << 62);
}
DEVI uint64_t dadv(uint64_t d, uint32_t bytes) { return (d & 0xffffffff00000000ull) | (uint64_t)((uint32_t)d + (bytes >> 4)); }
DEVI void wg_fence() { asm volatile("wgmma.fence.sync.aligned;" ::: "memory"); }
DEVI void wg_commit() { asm volatile("wgmma.commit_group.sync.aligned;" ::: "memory"); }
template<int N> DEVI void wg_wait() { asm volatile("wgmma.wait_group.sync.aligned %0;" :: "n"(N) : "memory"); }
template<int N> DEVI void reg_fence(float* d) {
    #pragma unroll
    for (int i = 0; i < N; i++) asm volatile("" : "+f"(d[i]) :: "memory");
}
DEVI uint32_t pack2(float lo, float hi) { uint32_t r; asm("cvt.rn.bf16x2.f32 %0, %1, %2;" : "=r"(r) : "f"(hi), "f"(lo)); return r; }
DEVI float bf_lo(uint32_t v) { return __uint_as_float(v << 16); }
DEVI float bf_hi(uint32_t v) { return __uint_as_float(v & 0xffff0000u); }
DEVI float ex2(float x) { float r; asm("ex2.approx.ftz.f32 %0, %1;" : "=f"(r) : "f"(x)); return r; }
DEVI float rcp(float x) { float r; asm("rcp.approx.ftz.f32 %0, %1;" : "=f"(r) : "f"(x)); return r; }
DEVI float rcp_full(float x) { float r; asm("rcp.approx.f32 %0, %1;" : "=f"(r) : "f"(x)); return r; }
DEVI float tanh_fast(float x) { float r; asm("tanh.approx.f32 %0, %1;" : "=f"(r) : "f"(x)); return r; }
DEVI void mma16816(float* c, uint32_t a0, uint32_t a1, uint32_t a2, uint32_t a3, uint32_t b0, uint32_t b1) {
    asm("mma.sync.aligned.m16n8k16.row.col.f32.bf16.bf16.f32 {%0,%1,%2,%3}, {%4,%5,%6,%7}, {%8,%9}, {%0,%1,%2,%3};"
        : "+f"(c[0]), "+f"(c[1]), "+f"(c[2]), "+f"(c[3]) : "r"(a0), "r"(a1), "r"(a2), "r"(a3), "r"(b0), "r"(b1));
}
DEVI void mma1688(float* c, uint32_t a0, uint32_t a1, uint32_t b0) {
    asm("mma.sync.aligned.m16n8k8.row.col.f32.bf16.bf16.f32 {%0,%1,%2,%3}, {%4,%5}, {%6}, {%0,%1,%2,%3};"
        : "+f"(c[0]), "+f"(c[1]), "+f"(c[2]), "+f"(c[3]) : "r"(a0), "r"(a1), "r"(b0));
}
DEVI void ldsm4t(uint32_t addr, uint32_t& r0, uint32_t& r1, uint32_t& r2, uint32_t& r3) {
    asm volatile("ldmatrix.sync.aligned.m8n8.x4.trans.shared.b16 {%0,%1,%2,%3}, [%4];" : "=r"(r0), "=r"(r1), "=r"(r2), "=r"(r3) : "r"(addr) : "memory");
}
DEVI void stsm4(uint32_t addr, uint32_t r0, uint32_t r1, uint32_t r2, uint32_t r3) {
    asm volatile("stmatrix.sync.aligned.m8n8.x4.shared.b16 [%0], {%1,%2,%3,%4};" :: "r"(addr), "r"(r0), "r"(r1), "r"(r2), "r"(r3) : "memory");
}
DEVI void stsm2(uint32_t addr, uint32_t r0, uint32_t r1) {
    asm volatile("stmatrix.sync.aligned.m8n8.x2.shared.b16 [%0], {%1,%2};" :: "r"(addr), "r"(r0), "r"(r1) : "memory");
}
DEVI void sts128(uint32_t addr, uint32_t r0, uint32_t r1, uint32_t r2, uint32_t r3) {
    asm volatile("st.shared.v4.b32 [%0], {%1,%2,%3,%4};" :: "r"(addr), "r"(r0), "r"(r1), "r"(r2), "r"(r3) : "memory");
}
DEVI void sts32(uint32_t addr, uint32_t r0) { asm volatile("st.shared.b32 [%0], %1;" :: "r"(addr), "r"(r0) : "memory"); }
DEVI uint32_t lds32(uint32_t addr) { uint32_t r; asm volatile("ld.shared.b32 %0, [%1];" : "=r"(r) : "r"(addr) : "memory"); return r; }
DEVI void wgmma_rs_n80(float* d, uint32_t a0, uint32_t a1, uint32_t a2, uint32_t a3, uint64_t db, int sd) {
  asm volatile("{\n.reg .pred p;\nsetp.ne.b32 p, %45, 0;\n"
    "wgmma.mma_async.sync.aligned.m64n80k16.f32.bf16.bf16 {%0, %1, %2, %3, %4, %5, %6, %7, %8, %9, %10, %11, %12, %13, %14, %15, %16, %17, %18, %19, %20, %21, %22, %23, %24, %25, %26, %27, %28, %29, %30, %31, %32, %33, %34, %35, %36, %37, %38, %39}, {%40, %41, %42, %43}, %44, p, 1, 1, 0;\n}\n"
    : "+f"(d[0]), "+f"(d[1]), "+f"(d[2]), "+f"(d[3]), "+f"(d[4]), "+f"(d[5]), "+f"(d[6]), "+f"(d[7]), "+f"(d[8]), "+f"(d[9]), "+f"(d[10]), "+f"(d[11]), "+f"(d[12]), "+f"(d[13]), "+f"(d[14]), "+f"(d[15]), "+f"(d[16]), "+f"(d[17]), "+f"(d[18]), "+f"(d[19]), "+f"(d[20]), "+f"(d[21]), "+f"(d[22]), "+f"(d[23]), "+f"(d[24]), "+f"(d[25]), "+f"(d[26]), "+f"(d[27]), "+f"(d[28]), "+f"(d[29]), "+f"(d[30]), "+f"(d[31]), "+f"(d[32]), "+f"(d[33]), "+f"(d[34]), "+f"(d[35]), "+f"(d[36]), "+f"(d[37]), "+f"(d[38]), "+f"(d[39]) : "r"(a0), "r"(a1), "r"(a2), "r"(a3), "l"(db), "r"(sd));
}
template<int TA, int TB> DEVI void wgmma_n40(float* d, uint64_t da, uint64_t db, int sd) {
  asm volatile("{\n.reg .pred p;\nsetp.ne.b32 p, %22, 0;\n"
    "wgmma.mma_async.sync.aligned.m64n40k16.f32.bf16.bf16 {%0, %1, %2, %3, %4, %5, %6, %7, %8, %9, %10, %11, %12, %13, %14, %15, %16, %17, %18, %19}, %20, %21, p, 1, 1, %23, %24;\n}\n"
    : "+f"(d[0]), "+f"(d[1]), "+f"(d[2]), "+f"(d[3]), "+f"(d[4]), "+f"(d[5]), "+f"(d[6]), "+f"(d[7]), "+f"(d[8]), "+f"(d[9]), "+f"(d[10]), "+f"(d[11]), "+f"(d[12]), "+f"(d[13]), "+f"(d[14]), "+f"(d[15]), "+f"(d[16]), "+f"(d[17]), "+f"(d[18]), "+f"(d[19]) : "l"(da), "l"(db), "r"(sd), "n"(TA), "n"(TB));
}
template<int TA, int TB> DEVI void wgmma_n48(float* d, uint64_t da, uint64_t db, int sd) {
  asm volatile("{\n.reg .pred p;\nsetp.ne.b32 p, %26, 0;\n"
    "wgmma.mma_async.sync.aligned.m64n48k16.f32.bf16.bf16 {%0, %1, %2, %3, %4, %5, %6, %7, %8, %9, %10, %11, %12, %13, %14, %15, %16, %17, %18, %19, %20, %21, %22, %23}, %24, %25, p, 1, 1, %27, %28;\n}\n"
    : "+f"(d[0]), "+f"(d[1]), "+f"(d[2]), "+f"(d[3]), "+f"(d[4]), "+f"(d[5]), "+f"(d[6]), "+f"(d[7]), "+f"(d[8]), "+f"(d[9]), "+f"(d[10]), "+f"(d[11]), "+f"(d[12]), "+f"(d[13]), "+f"(d[14]), "+f"(d[15]), "+f"(d[16]), "+f"(d[17]), "+f"(d[18]), "+f"(d[19]), "+f"(d[20]), "+f"(d[21]), "+f"(d[22]), "+f"(d[23]) : "l"(da), "l"(db), "r"(sd), "n"(TA), "n"(TB));
}
template<int TA, int TB> DEVI void wgmma_n72(float* d, uint64_t da, uint64_t db, int sd) {
  asm volatile("{\n.reg .pred p;\nsetp.ne.b32 p, %38, 0;\n"
    "wgmma.mma_async.sync.aligned.m64n72k16.f32.bf16.bf16 {%0, %1, %2, %3, %4, %5, %6, %7, %8, %9, %10, %11, %12, %13, %14, %15, %16, %17, %18, %19, %20, %21, %22, %23, %24, %25, %26, %27, %28, %29, %30, %31, %32, %33, %34, %35}, %36, %37, p, 1, 1, %39, %40;\n}\n"
    : "+f"(d[0]), "+f"(d[1]), "+f"(d[2]), "+f"(d[3]), "+f"(d[4]), "+f"(d[5]), "+f"(d[6]), "+f"(d[7]), "+f"(d[8]), "+f"(d[9]), "+f"(d[10]), "+f"(d[11]), "+f"(d[12]), "+f"(d[13]), "+f"(d[14]), "+f"(d[15]), "+f"(d[16]), "+f"(d[17]), "+f"(d[18]), "+f"(d[19]), "+f"(d[20]), "+f"(d[21]), "+f"(d[22]), "+f"(d[23]), "+f"(d[24]), "+f"(d[25]), "+f"(d[26]), "+f"(d[27]), "+f"(d[28]), "+f"(d[29]), "+f"(d[30]), "+f"(d[31]), "+f"(d[32]), "+f"(d[33]), "+f"(d[34]), "+f"(d[35]) : "l"(da), "l"(db), "r"(sd), "n"(TA), "n"(TB));
}
template<int TA, int TB> DEVI void wgmma_n96(float* d, uint64_t da, uint64_t db, int sd) {
  asm volatile("{\n.reg .pred p;\nsetp.ne.b32 p, %50, 0;\n"
    "wgmma.mma_async.sync.aligned.m64n96k16.f32.bf16.bf16 {%0, %1, %2, %3, %4, %5, %6, %7, %8, %9, %10, %11, %12, %13, %14, %15, %16, %17, %18, %19, %20, %21, %22, %23, %24, %25, %26, %27, %28, %29, %30, %31, %32, %33, %34, %35, %36, %37, %38, %39, %40, %41, %42, %43, %44, %45, %46, %47}, %48, %49, p, 1, 1, %51, %52;\n}\n"
    : "+f"(d[0]), "+f"(d[1]), "+f"(d[2]), "+f"(d[3]), "+f"(d[4]), "+f"(d[5]), "+f"(d[6]), "+f"(d[7]), "+f"(d[8]), "+f"(d[9]), "+f"(d[10]), "+f"(d[11]), "+f"(d[12]), "+f"(d[13]), "+f"(d[14]), "+f"(d[15]), "+f"(d[16]), "+f"(d[17]), "+f"(d[18]), "+f"(d[19]), "+f"(d[20]), "+f"(d[21]), "+f"(d[22]), "+f"(d[23]), "+f"(d[24]), "+f"(d[25]), "+f"(d[26]), "+f"(d[27]), "+f"(d[28]), "+f"(d[29]), "+f"(d[30]), "+f"(d[31]), "+f"(d[32]), "+f"(d[33]), "+f"(d[34]), "+f"(d[35]), "+f"(d[36]), "+f"(d[37]), "+f"(d[38]), "+f"(d[39]), "+f"(d[40]), "+f"(d[41]), "+f"(d[42]), "+f"(d[43]), "+f"(d[44]), "+f"(d[45]), "+f"(d[46]), "+f"(d[47]) : "l"(da), "l"(db), "r"(sd), "n"(TA), "n"(TB));
}
template<int TA, int TB> DEVI void wgmma_n144(float* d, uint64_t da, uint64_t db, int sd) {
  asm volatile("{\n.reg .pred p;\nsetp.ne.b32 p, %74, 0;\n"
    "wgmma.mma_async.sync.aligned.m64n144k16.f32.bf16.bf16 {%0, %1, %2, %3, %4, %5, %6, %7, %8, %9, %10, %11, %12, %13, %14, %15, %16, %17, %18, %19, %20, %21, %22, %23, %24, %25, %26, %27, %28, %29, %30, %31, %32, %33, %34, %35, %36, %37, %38, %39, %40, %41, %42, %43, %44, %45, %46, %47, %48, %49, %50, %51, %52, %53, %54, %55, %56, %57, %58, %59, %60, %61, %62, %63, %64, %65, %66, %67, %68, %69, %70, %71}, %72, %73, p, 1, 1, %75, %76;\n}\n"
    : "+f"(d[0]), "+f"(d[1]), "+f"(d[2]), "+f"(d[3]), "+f"(d[4]), "+f"(d[5]), "+f"(d[6]), "+f"(d[7]), "+f"(d[8]), "+f"(d[9]), "+f"(d[10]), "+f"(d[11]), "+f"(d[12]), "+f"(d[13]), "+f"(d[14]), "+f"(d[15]), "+f"(d[16]), "+f"(d[17]), "+f"(d[18]), "+f"(d[19]), "+f"(d[20]), "+f"(d[21]), "+f"(d[22]), "+f"(d[23]), "+f"(d[24]), "+f"(d[25]), "+f"(d[26]), "+f"(d[27]), "+f"(d[28]), "+f"(d[29]), "+f"(d[30]), "+f"(d[31]), "+f"(d[32]), "+f"(d[33]), "+f"(d[34]), "+f"(d[35]), "+f"(d[36]), "+f"(d[37]), "+f"(d[38]), "+f"(d[39]), "+f"(d[40]), "+f"(d[41]), "+f"(d[42]), "+f"(d[43]), "+f"(d[44]), "+f"(d[45]), "+f"(d[46]), "+f"(d[47]), "+f"(d[48]), "+f"(d[49]), "+f"(d[50]), "+f"(d[51]), "+f"(d[52]), "+f"(d[53]), "+f"(d[54]), "+f"(d[55]), "+f"(d[56]), "+f"(d[57]), "+f"(d[58]), "+f"(d[59]), "+f"(d[60]), "+f"(d[61]), "+f"(d[62]), "+f"(d[63]), "+f"(d[64]), "+f"(d[65]), "+f"(d[66]), "+f"(d[67]), "+f"(d[68]), "+f"(d[69]), "+f"(d[70]), "+f"(d[71]) : "l"(da), "l"(db), "r"(sd), "n"(TA), "n"(TB));
}
template<int TA, int TB> DEVI void wgmma_n160(float* d, uint64_t da, uint64_t db, int sd) {
  asm volatile("{\n.reg .pred p;\nsetp.ne.b32 p, %82, 0;\n"
    "wgmma.mma_async.sync.aligned.m64n160k16.f32.bf16.bf16 {%0, %1, %2, %3, %4, %5, %6, %7, %8, %9, %10, %11, %12, %13, %14, %15, %16, %17, %18, %19, %20, %21, %22, %23, %24, %25, %26, %27, %28, %29, %30, %31, %32, %33, %34, %35, %36, %37, %38, %39, %40, %41, %42, %43, %44, %45, %46, %47, %48, %49, %50, %51, %52, %53, %54, %55, %56, %57, %58, %59, %60, %61, %62, %63, %64, %65, %66, %67, %68, %69, %70, %71, %72, %73, %74, %75, %76, %77, %78, %79}, %80, %81, p, 1, 1, %83, %84;\n}\n"
    : "+f"(d[0]), "+f"(d[1]), "+f"(d[2]), "+f"(d[3]), "+f"(d[4]), "+f"(d[5]), "+f"(d[6]), "+f"(d[7]), "+f"(d[8]), "+f"(d[9]), "+f"(d[10]), "+f"(d[11]), "+f"(d[12]), "+f"(d[13]), "+f"(d[14]), "+f"(d[15]), "+f"(d[16]), "+f"(d[17]), "+f"(d[18]), "+f"(d[19]), "+f"(d[20]), "+f"(d[21]), "+f"(d[22]), "+f"(d[23]), "+f"(d[24]), "+f"(d[25]), "+f"(d[26]), "+f"(d[27]), "+f"(d[28]), "+f"(d[29]), "+f"(d[30]), "+f"(d[31]), "+f"(d[32]), "+f"(d[33]), "+f"(d[34]), "+f"(d[35]), "+f"(d[36]), "+f"(d[37]), "+f"(d[38]), "+f"(d[39]), "+f"(d[40]), "+f"(d[41]), "+f"(d[42]), "+f"(d[43]), "+f"(d[44]), "+f"(d[45]), "+f"(d[46]), "+f"(d[47]), "+f"(d[48]), "+f"(d[49]), "+f"(d[50]), "+f"(d[51]), "+f"(d[52]), "+f"(d[53]), "+f"(d[54]), "+f"(d[55]), "+f"(d[56]), "+f"(d[57]), "+f"(d[58]), "+f"(d[59]), "+f"(d[60]), "+f"(d[61]), "+f"(d[62]), "+f"(d[63]), "+f"(d[64]), "+f"(d[65]), "+f"(d[66]), "+f"(d[67]), "+f"(d[68]), "+f"(d[69]), "+f"(d[70]), "+f"(d[71]), "+f"(d[72]), "+f"(d[73]), "+f"(d[74]), "+f"(d[75]), "+f"(d[76]), "+f"(d[77]), "+f"(d[78]), "+f"(d[79]) : "l"(da), "l"(db), "r"(sd), "n"(TA), "n"(TB));
}

__host__ __device__ constexpr int ka_seq(int p, int c) { return p == 0 ? c : c >= 5 ? 2 * c - 2 + p : p == 1 ? 17 + c : 22 + c; }
__global__ void __launch_bounds__(256, 3) k0_prep(const bf16* __restrict__ x, const bf16* __restrict__ wqkv, const bf16* __restrict__ wphi,
                                                  const bf16* __restrict__ wo) {
    __shared__ __align__(16) uint32_t s_in[64 * 36 + 64];
    pdl_trigger();
    const int tid = threadIdx.x, lane = tid & 31, warp = __shfl_sync(~0u, tid >> 5, 0);
    const int c = blockIdx.x, g = blockIdx.y, p = blockIdx.z;
    const bool fold = p == 0 || p == 2;
    const int b = (p * 8 + g) * 9 + c;
    if (p == 3) {
        const int j = b - 216;
        const uint4 z = make_uint4(0u, 0u, 0u, 0u);
        if (j < 32) reinterpret_cast<uint4*>(g_stats)[j * 256 + tid] = z;
        else if (j < 62) reinterpret_cast<uint4*>(g_kv)[(j - 32) * 256 + tid] = z;
        else if (j == 66 && tid < 8) g_cnt[tid * CNT_S] = 0u;
        return;
    }
    constexpr int ld = 1728;
    const bf16* src = wqkv + ((p == 2 ? 0 : p + 1) * 576 + c * 64 * ld + g * 72);
    const uint32_t si = smem_u32(s_in);
    #pragma unroll
    for (int j = 0; j < 3; j++) {
        const int i = tid + j * 256, r = (i * 7282) >> 16;
        if (j < 2 || tid < 64) asm volatile("cp.async.cg.shared.global [%0], [%1], 16;" :: "r"(si + i * 16 + (r >> 3) * 32), "l"(src + (r * (ld - 72) + i * 8)) : "memory");
    }
    const int t = warp & 3, half = warp >> 2, g8 = lane >> 2, c4 = lane & 3;
    uint32_t af[3][3];
    if (fold) {
        const unsigned short* ph = reinterpret_cast<const unsigned short*>(wphi) + (g * 4 + t) * 324;
        unsigned short lo[3][3], hi[3][3];
        #pragma unroll
        for (int fb = 0; fb < 3; fb++)
            #pragma unroll
            for (int db = 0; db < 3; db++) {
                const int o = min(2 * c4 + 8 * db, 16) * 18 + min(g8 + 8 * fb, 17);
                lo[fb][db] = __ldg(ph + o); hi[fb][db] = __ldg(ph + o + 18);
            }
        #pragma unroll
        for (int fb = 0; fb < 3; fb++)
            #pragma unroll
            for (int db = 0; db < 3; db++) af[fb][db] = (uint32_t)lo[fb][db] | ((uint32_t)hi[fb][db] << 16);
    } else {
        const uint32_t v = (g8 == 2 * c4 ? 0x3f80u : 0u) | (g8 == 2 * c4 + 1 ? 0x3f800000u : 0u);
        #pragma unroll
        for (int fb = 0; fb < 3; fb++)
            #pragma unroll
            for (int db = 0; db < 3; db++) af[fb][db] = fb == db ? v : 0u;
    }
    bf16* dst = g_wqkv + (g * 27 + ka_seq(p, c)) * 4608;
    float* csd = g_cs + (g * 18 + c * 2 + half) * 216 + p * 72 + 2 * t;
    asm volatile("cp.async.wait_all;" ::: "memory");
    __syncthreads();
    if (tid < 96 && b < 192) asm volatile("prefetch.global.L2 [%0];" :: "l"(x + b * 6144 + tid * 64));
    if (tid >= 96 && tid < 120) asm volatile("prefetch.global.L2 [%0];" :: "l"(wo + b * 1536 + (tid - 96) * 64));
    uint32_t ov[3][4];
    const uint32_t* wr = &s_in[(half * 32 + (g8 >> 1) * 8 + (g8 & 1)) * 36 + (half * 4 + (g8 >> 1)) * 8 + t * 9 + c4];
    #pragma unroll
    for (int j = 0; j < 4; j++) {
        const uint32_t b0 = wr[j * 72], b1 = wr[j * 72 + 4], b2 = c4 == 0 ? wr[j * 72 + 8] : 0u;
        float c0[4] = {0.f, 0.f, 0.f, 0.f}, c1[4] = {0.f, 0.f, 0.f, 0.f};
        mma16816(c0, af[0][0], af[1][0], af[0][1], af[1][1], b0, b1);
        mma1688(c0, af[0][2], af[1][2], b2);
        mma16816(c1, af[2][0], 0u, af[2][1], 0u, b0, b1);
        mma1688(c1, af[2][2], 0u, b2);
        ov[0][j] = pack2(c0[0], c0[1]); ov[1][j] = pack2(c0[2], c0[3]); ov[2][j] = pack2(c1[0], c1[1]);
    }
    {
        const int nl = 2 * t + (g8 & 1);
        uint4* o = reinterpret_cast<uint4*>(dst) + ((g8 >> 1) * 8 + nl) * 8 + ((half * 4 + c4) ^ nl);
        o[0] = make_uint4(ov[0][0], ov[0][1], ov[0][2], ov[0][3]);
        o[256] = make_uint4(ov[1][0], ov[1][1], ov[1][2], ov[1][3]);
        if (g8 < 2) o[512] = make_uint4(ov[2][0], ov[2][1], ov[2][2], ov[2][3]);
    }
    {
        float cs0[4] = {0.f, 0.f, 0.f, 0.f}, cs1[4] = {0.f, 0.f, 0.f, 0.f};
        mma16816(cs0, ov[0][0], ov[1][0], ov[0][1], ov[1][1], 0x3f803f80u, 0x3f803f80u);
        mma16816(cs1, ov[2][0], 0u, ov[2][1], 0u, 0x3f803f80u, 0x3f803f80u);
        mma16816(cs0, ov[0][2], ov[1][2], ov[0][3], ov[1][3], 0x3f803f80u, 0x3f803f80u);
        mma16816(cs1, ov[2][2], 0u, ov[2][3], 0u, 0x3f803f80u, 0x3f803f80u);
        const int f = g8 + 8 * c4;
        if (f < 18) csd[8 * (f >> 1) + (f & 1)] = c4 == 0 ? cs0[0] : c4 == 1 ? cs0[2] : cs1[0];
    }
}

DEVI void dual_softmax(const float* a, float scale, uint32_t* o) {
    float mx = a[0], mn = a[0];
    #pragma unroll
    for (int j = 1; j < 18; j++) { mx = fmaxf(mx, a[j]); mn = fminf(mn, a[j]); }
    const float mxs = -mx * scale, mns = mn * scale;
    float ep[18], en[18], sp = 0.f, sn = 0.f;
    #pragma unroll
    for (int j = 0; j < 18; j++) {
        ep[j] = ex2(fmaf(a[j], scale, mxs)); sp += ep[j];
        en[j] = ex2(fmaf(a[j], -scale, mns)); sn += en[j];
    }
    const float rp = rcp(sp), rn = rcp(sn);
    #pragma unroll
    for (int j = 0; j < 9; j++) {
        o[j] = pack2(ep[2 * j] * rp, ep[2 * j + 1] * rp);
        o[9 + j] = pack2(en[2 * j] * rn, en[2 * j + 1] * rn);
    }
}

DEVI uint4 ldg128(const void* p) { uint4 v; asm volatile("ld.global.cg.v4.u32 {%0,%1,%2,%3}, [%4];" : "=r"(v.x), "=r"(v.y), "=r"(v.z), "=r"(v.w) : "l"(p)); return v; }
DEVI uint2 ldg64(const void* p) { uint2 v; asm volatile("ld.global.cg.v2.u32 {%0,%1}, [%2];" : "=r"(v.x), "=r"(v.y) : "l"(p)); return v; }
DEVI uint4 lds128(uint32_t a) { uint4 v; asm volatile("ld.shared.v4.u32 {%0,%1,%2,%3}, [%4];" : "=r"(v.x), "=r"(v.y), "=r"(v.z), "=r"(v.w) : "r"(a) : "memory"); return v; }
DEVI uint2 lds64(uint32_t a) { uint2 v; asm volatile("ld.shared.v2.u32 {%0,%1}, [%2];" : "=r"(v.x), "=r"(v.y) : "r"(a) : "memory"); return v; }
DEVI uint32_t packu(uint32_t lo, uint32_t hi) { return pack2(__uint_as_float(lo), __uint_as_float(hi)); }
DEVI void spin_ge(const unsigned int* p, unsigned int n) {
    uint32_t f; int it = 0;
    do {
        asm volatile("ld.acquire.gpu.global.u32 %0, [%1];" : "=r"(f) : "l"(p) : "memory");
        if (++it > (1 << 22)) __trap();
    } while (f < n);
}
constexpr int KA_PRE = 3, KA_REC = 5 * 16384, KA_B = 147456, KA_CS = KA_B + 9 * 9216, KA_LN = KA_CS + 864, KA_BAR = KA_LN + 1024, KA_SMEM = KA_BAR + 160;
static_assert(KA_SMEM <= 232448, "smem");
DEVI void ka_kv(uint32_t recs, float* kvh, int w4, int lane) {
    float ck[2][20];
    const uint64_t dr = mkdesc(recs, 8192, 1024, 1);
    wg_fence();
    #pragma unroll
    for (int ks = 0; ks < 4; ks++)
        #pragma unroll
        for (int hh = 0; hh < 2; hh++) wgmma_n40<1, 1>(ck[hh], dadv(dr, hh * 8192 + ks * 2048), dadv(dr, hh * 8192 + ks * 2048), ks != 0);
    wg_commit();
    wg_wait<0>();
    reg_fence<20>(ck[0]); reg_fence<20>(ck[1]);
    if (w4 >= 2) {
        #pragma unroll
        for (int e = 1; e >= 0; e--) {
            const int nt = 2 * w4 + e - 5;
            if (nt >= 0 && (nt < 2 || lane < 12)) {
                float* p = kvh + nt * 320;
                float q[10];
                #pragma unroll
                for (int j = 0; j < 10; j++) q[j] = ck[0][(j >> 1) * 4 + 2 * e + (j & 1)] + ck[1][(j >> 1) * 4 + 2 * e + (j & 1)];
                asm volatile("red.global.add.v4.f32 [%0], {%1, %2, %3, %4};" :: "l"(p + lane * 4), "f"(q[0]), "f"(q[1]), "f"(q[2]), "f"(q[3]) : "memory");
                asm volatile("red.global.add.v4.f32 [%0], {%1, %2, %3, %4};" :: "l"(p + 128 + lane * 4), "f"(q[4]), "f"(q[5]), "f"(q[6]), "f"(q[7]) : "memory");
                if ((lane & 3) < 2) asm volatile("red.global.add.v2.f32 [%0], {%1, %2};" :: "l"(p + 256 + lane * 2), "f"(q[8]), "f"(q[9]) : "memory");
            }
        }
        __syncwarp();
        bar_arrive(2, 288);
    }
}
DEVI int gpc_pos() {
    unsigned smid, nsm;
    asm volatile("mov.u32 %0, %%smid;" : "=r"(smid));
    asm volatile("mov.u32 %0, %%nsmid;" : "=r"(nsm));
    if (nsm != 132) return blockIdx.x;
    const int tpc = smid >> 1, o = smid & 1;
    if (smid == 13 || smid == 15) return 124 + tpc;
    if (tpc < 32) return (tpc & 7) * 16 + (tpc >> 3) * 2 + o;
    if (tpc < 60) { const int j = tpc - 32, r = j / 7; return (1 + j - r * 7) * 16 + 8 + r * 2 + o; }
    if (tpc < 62) return o ? 68 + tpc : (tpc - 54) * 16 + 1;
    return 8 + (tpc - 62) * 2 + o;
}
__global__ void __launch_bounds__(640, 1) ka_front(const __grid_constant__ CUtensorMap tmXA, const bf16* __restrict__ x, const bf16* __restrict__ wo, const bf16* __restrict__ w1, const bf16* __restrict__ b1) {
    extern __shared__ __align__(1024) char smem[];
    const uint32_t sm = smem_u32(smem);
    const uint32_t bFull = sm + KA_BAR, bEmpty = bFull + 9 * 8, bLn = bEmpty + 9 * 8;
    const int tid = threadIdx.x, lane = tid & 31, warp = __shfl_sync(~0u, tid >> 5, 0);
    const int pos = gpc_pos();
    if (pos >= 128) {
        const int ns = pos - 128;
        if (tid == 0) {
            #pragma unroll
            for (int q = 0; q < 6; q++) mbar_init(bFull + q * 8, 1);
            fence_mbar_init();
            #pragma unroll
            for (int q = 0; q < 6; q++) mbar_expect(bFull + q * 8, 96 * 288);
        }
        __syncthreads();
        if (tid < 576) {
            const int h = tid / 18, d = tid - h * 18, r = (h >> 2) * 72 + (d >> 1) * 8 + 2 * (h & 3) + (d & 1);
            bulk_g2s(sm + r * 304, wo + tid * 576 + ns * 144, 288, bFull + (r / 96) * 8);
        }
        #pragma unroll 1
        for (int q = 0; q < 6; q++) {
            const uint32_t ob = sm + 175104 + (q & 1) * 27648;
            mbar_wait(bFull + q * 8, 0);
            if (tid == 0) asm volatile("cp.async.bulk.wait_group.read 1;" ::: "memory");
            __syncthreads();
            if (warp < 18) {
                #pragma unroll
                for (int rb = 0; rb < 3; rb++) {
                    uint32_t r0, r1, r2, r3;
                    ldsm4t(sm + (q * 96 + rb * 32 + lane) * 304 + warp * 16, r0, r1, r2, r3);
                    stsm4(ob + (warp / 9) * 13824 + ((rb * 4 + (lane >> 3)) * 72 + (warp % 9) * 8 + (lane & 7)) * 16, r0, r1, r2, r3);
                }
            }
            fence_async_smem();
            __syncthreads();
            if (tid == 0) {
                bulk_s2g(g_wo + (ns * 2) * (72 * 576) + q * 6912, ob, 13824);
                bulk_s2g(g_wo + (ns * 2 + 1) * (72 * 576) + q * 6912, ob + 13824, 13824);
                bulk_commit();
            }
        }
        if (tid == 0) {
            asm volatile("cp.async.bulk.wait_group 0;\nfence.proxy.async.global;\nfence.acq_rel.gpu;" ::: "memory");
            pdl_wait();
            pdl_trigger();
        }
        return;
    }
    const int g = ((pos >> 4) & 1) * 4 + (pos & 3), mt = (pos >> 5) * 4 + ((pos >> 2) & 3);
    if (warp >= 16) {
        asm volatile("setmaxnreg.dec.sync.aligned.u32 32;");
        if (warp == 16) {
            if (lane == 0) {
                #pragma unroll
                for (int c = 0; c < 9; c++) { mbar_init(bFull + c * 8, 1); mbar_init(bEmpty + c * 8, 8); }
                mbar_init(bLn, 64);
                fence_mbar_init();
            }
            __syncwarp();
            bar_arrive(0, 640);
        } else {
            bar_sync(0, 640);
            if (tid == 544) {
                #pragma unroll
                for (int c = 0; c < 9; c++) mbar_expect(bFull + c * 8, 16384 + 9216);
            }
            __syncwarp();
        }
        if (tid == 512) {
            #pragma unroll
            for (int c = 0; c < KA_PRE; c++) tma3d(sm + c * 16384, &tmXA, bFull + c * 8, 0, mt * 128, c);
            pdl_wait();
            const bf16* wsrc = g_wqkv + g * (27 * 4608);
            const uint32_t sb = sm + KA_B;
            #pragma unroll
            for (int c = 0; c < 9; c++) {
                bulk_g2s(sb + c * 9216, wsrc + c * 4608, 9216, bFull + c * 8);
                const int xc = c + KA_PRE - 2;
                if (c >= 2 && xc < 9) tma3d(sm + xc * 16384, &tmXA, bFull + xc * 8, 0, mt * 128, xc);
            }
            pdl_trigger();
            #pragma unroll 1
            for (int p = 1; p < 3; p++) {
                #pragma unroll
                for (int c = 0; c < 9; c++) {
                    mbar_wait(bEmpty + c * 8, p - 1); mbar_expect(bFull + c * 8, 9216);
                    bulk_g2s(sb + c * 9216, wsrc + (p * 9 + c) * 4608, 9216, bFull + c * 8);
                }
            }
            l2_prefetch(w1 + pos * 13824, 27648);
            if (pos == 0) l2_prefetch(b1, 9216);
        } else if (warp == 17) {
            bar_sync(2, 288);
            if (lane == 0) {
                asm volatile("red.release.gpu.global.add.u32 [%0], 1;" :: "l"(g_cnt + g * CNT_S) : "memory");
                spin_ge(g_cnt + g * CNT_S, 16);
            }
            __syncwarp();
            bar_arrive(1, 288);
        } else if (warp >= 18) {
            const int m = warp - 18;
            {
                const unsigned long long* lp = g_ln + mt * 128 + m * 64 + (lane >> 3) * 16 + (lane & 7);
                unsigned long long r0, r1; int it = 0;
                __nanosleep(700);
                while (true) {
                    asm volatile("ld.relaxed.gpu.global.u64 %0, [%1];" : "=l"(r0) : "l"(lp) : "memory");
                    asm volatile("ld.relaxed.gpu.global.u64 %0, [%1];" : "=l"(r1) : "l"(lp + 8) : "memory");
                    if (__all_sync(~0u, (long long)(r0 & r1) < 0)) break;
                    if (++it > (1 << 22)) __trap();
                }
                sts128(sm + KA_LN + (m * 32 + lane) * 16, (uint32_t)r0, (uint32_t)(r0 >> 32), (uint32_t)r1, (uint32_t)(r1 >> 32));
                mbar_arrive(bLn);
            }
        }
    } else {
        const int xrow = mt * 128 + g * 16 + warp;
        uint4 xv[3];
        {
            const uint4* xr = reinterpret_cast<const uint4*>(x + xrow * D_);
            xv[0] = ldg128(xr + lane); xv[1] = ldg128(xr + lane + 32); xv[2] = ldg128(xr + 64 + (lane & 7));
        }
        asm volatile("setmaxnreg.inc.sync.aligned.u32 112;");
        bar_sync(0, 640);
        const int wg = warp >> 2, m = wg & 1, w4 = warp & 3, gq = lane >> 2, t = lane & 3;
        {
            const uint32_t w[12] = {xv[0].x, xv[0].y, xv[0].z, xv[0].w, xv[1].x, xv[1].y, xv[1].z, xv[1].w, xv[2].x, xv[2].y, xv[2].z, xv[2].w};
            float s = 0.f, s2 = 0.f;
            #pragma unroll
            for (int i = 0; i < 12; i++) { if (i < 8) s += bf_lo(w[i]) + bf_hi(w[i]); else s2 += bf_lo(w[i]) + bf_hi(w[i]); }
            if (lane < 8) s += s2;
            #pragma unroll
            for (int o = 16; o; o >>= 1) s += __shfl_xor_sync(~0u, s, o);
            const float mean = s * (1.f / D_);
            float q = 0.f, q2 = 0.f;
            #pragma unroll
            for (int i = 0; i < 12; i++) {
                const float e0 = bf_lo(w[i]) - mean, e1 = bf_hi(w[i]) - mean;
                if (i < 8) q += e0 * e0 + e1 * e1; else q2 += e0 * e0 + e1 * e1;
            }
            if (lane < 8) q += q2;
            #pragma unroll
            for (int o = 16; o; o >>= 1) q += __shfl_xor_sync(~0u, q, o);
            const unsigned long long lrec = ((unsigned long long)(__float_as_uint(rsqrtf(q * (1.f / D_) + LN_EPS)) | 0x80000000u) << 32) | __float_as_uint(mean);
            if (lane == 0) asm volatile("st.relaxed.gpu.global.u64 [%0], %1;" :: "l"(g_ln + xrow), "l"(lrec) : "memory");
        }
        float2 ln0, ln1;
        auto ln_get = [&]() {
            mbar_wait(bLn, 0);
            const uint4 v = lds128(sm + KA_LN + (m * 32 + w4 * 8 + gq) * 16);
            ln0 = make_float2(__uint_as_float(v.x), fabsf(__uint_as_float(v.y))); ln1 = make_float2(__uint_as_float(v.z), fabsf(__uint_as_float(v.w)));
        };
        const uint64_t da = mkdesc(sm + m * 8192, 16, 1024, 1), db = mkdesc(sm + KA_B, 16, 1024, 1);
        const uint32_t csa = sm + KA_CS + 8 * t;
        const int rot = (gq + 2 * t) & 7;
        const uint32_t rec = sm + KA_REC + t * 16384 + m * 8192 + (w4 * 16 + rot) * 128;
        const uint32_t kvb = sm + KA_REC;
        if (wg < 2) {
            float acc[36]; uint2 cs[9];
            #pragma unroll
            for (int c = 0; c < 9; c++) {
                mbar_wait(bFull + c * 8, 0);
                wg_fence();
                #pragma unroll
                for (int kk = 0; kk < 4; kk++) wgmma_n72<0, 0>(acc, dadv(da, c * 16384 + kk * 32), dadv(db, c * 9216 + kk * 32), (c | kk) != 0);
                wg_commit();
                if (c > 0) { wg_wait<1>(); if (lane == 0) mbar_arrive(bEmpty + (c - 1) * 8); }
            }
            wg_wait<0>();
            reg_fence<36>(acc);
            bar_arrive(5, 512);
            if (lane == 0) mbar_arrive(bEmpty + 8 * 8);
            bar_sync(6, 384);
            #pragma unroll
            for (int j = 0; j < 9; j++) cs[j] = lds64(csa + 32 * j);
            ln_get();
            uint32_t ph[2][18];
            #pragma unroll
            for (int r = 0; r < 2; r++) {
                float a[18];
                const float2 ln = r ? ln1 : ln0;
                #pragma unroll
                for (int j = 0; j < 9; j++) { a[2 * j] = fmaf(-ln.x, __uint_as_float(cs[j].x), acc[4 * j + 2 * r]); a[2 * j + 1] = fmaf(-ln.x, __uint_as_float(cs[j].y), acc[4 * j + 2 * r + 1]); }
                dual_softmax(a, ln.y * LOG2E, ph[r]);
            }
            #pragma unroll
            for (int j = 0; j < 18; j++) asm volatile("" : "+r"(ph[0][j]), "+r"(ph[1][j]));
            bar_sync(3 + m, 256);
            #pragma unroll
            for (int r = 0; r < 2; r++) {
                #pragma unroll
                for (int j = 0; j < 4; j++) sts128(rec + r * 1024 + ((j ^ rot) << 4), ph[r][4 * j], ph[r][4 * j + 1], ph[r][4 * j + 2], ph[r][4 * j + 3]);
                sts128(rec + r * 1024 + ((4 ^ rot) << 4), ph[r][16], ph[r][17], 0u, 0u);
            }
            fence_async_smem();
            bar_sync(8, 512);
            ka_kv(sm + KA_REC + wg * 16384, g_kv + (g * 4 + wg) * KV_H, w4, lane);
            bar_arrive(7, 512);
            bar_sync(11, 256);
            #pragma unroll
            for (int j = 0; j < 6; j++) if (j < 5 || tid < 196) sts128(kvb + (j * 256 + tid) * 16, 0u, 0u, 0u, 0u);
            const float* kp = g_kv + (g * 4 + w4) * KV_H + lane * 2;
            const uint32_t kd = kvb + t * 1312 + ((gq >> 1) * 8 + 2 * w4 + (gq & 1)) * 16 + w4 * 4;
            bar_sync(1, 288);
            if (m == 0) {
                const uint4 u0 = ldg128(kp + lane * 2), u1 = ldg128(kp + 128 + lane * 2); const uint2 u2 = ldg64(kp + 256);
                const uint4 v0 = ldg128(kp + 640 + lane * 2), v1 = ldg128(kp + 768 + lane * 2); const uint2 v2 = ldg64(kp + 896);
                sts32(kd, packu(u0.x, u0.y)); sts32(kd + 5248, packu(u0.z, u0.w)); sts32(kd + 10496, packu(u1.x, u1.y)); sts32(kd + 15744, packu(u1.z, u1.w));
                if (t < 2) sts32(kd + 20992, packu(u2.x, u2.y));
                if (gq < 3) {
                    sts32(kd + 1024, packu(v0.x, v0.y)); sts32(kd + 6272, packu(v0.z, v0.w)); sts32(kd + 11520, packu(v1.x, v1.y)); sts32(kd + 16768, packu(v1.z, v1.w));
                    if (t < 2) sts32(kd + 22016, packu(v2.x, v2.y));
                }
            } else {
                const uint4 u0 = ldg128(kp + 320 + lane * 2), u1 = ldg128(kp + 448 + lane * 2); const uint2 u2 = ldg64(kp + 576);
                sts32(kd + 512, packu(u0.x, u0.y)); sts32(kd + 5760, packu(u0.z, u0.w)); sts32(kd + 11008, packu(u1.x, u1.y)); sts32(kd + 16256, packu(u1.z, u1.w));
                if (t < 2) sts32(kd + 21504, packu(u2.x, u2.y));
            }
            fence_async_smem();
            bar_arrive(9, 512);
        } else {
            float avq[36], acc[36]; uint2 cs[9];
            if (m == 1) {
                pdl_wait();
                if (tid < 384 + 108) {
                    uint2 pc[18];
                    #pragma unroll
                    for (int j = 0; j < 18; j++) pc[j] = ldg64(g_cs + (g * 18 + j) * 216 + (tid - 384) * 2);
                    float a = 0.f, c = 0.f;
                    #pragma unroll
                    for (int j = 0; j < 18; j++) { a += __uint_as_float(pc[j].x); c += __uint_as_float(pc[j].y); }
                    asm volatile("st.shared.v2.f32 [%0], {%1, %2};" :: "r"(sm + KA_CS + (tid - 384) * 8), "f"(a), "f"(c) : "memory");
                }
                bar_arrive(6, 384);
            }
            bar_sync(5, 512);
            #pragma unroll
            for (int i = 9; i < 22; i++) {
                const int c = i < 17 ? (i + 1) / 2 : i - 17;
                mbar_wait(bFull + (i % 9) * 8, (i / 9) & 1);
                wg_fence();
                #pragma unroll
                for (int kk = 0; kk < 4; kk++)
                    wgmma_n72<0, 0>((i < 17 && !(i & 1)) ? acc : avq, dadv(da, c * 16384 + kk * 32), dadv(db, (i % 9) * 9216 + kk * 32), i > 10 || kk != 0);
                wg_commit();
                if (i > 9 && i <= 18) { wg_wait<1>(); if (lane == 0) mbar_arrive(bEmpty + ((i - 1) % 9) * 8); }
                if (i == 17) bar_arrive(3 + m, 256);
                if (i == 18) bar_sync(14 + m, 128);
            }
            #pragma unroll
            for (int j = 0; j < 9; j++) cs[j] = lds64(csa + 288 + 32 * j);
            ln_get();
            wg_wait<0>();
            reg_fence<36>(avq);
            #pragma unroll
            for (int r = 0; r < 2; r++) {
                uint32_t pv[9];
                const float2 ln = r ? ln1 : ln0;
                #pragma unroll
                for (int j = 0; j < 9; j++)
                    pv[j] = pack2(fmaf(-ln.x, __uint_as_float(cs[j].x), avq[4 * j + 2 * r]) * ln.y, fmaf(-ln.x, __uint_as_float(cs[j].y), avq[4 * j + 2 * r + 1]) * ln.y);
                sts128(rec + r * 1024 + ((5 ^ rot) << 4), pv[0], pv[1], pv[2], pv[3]);
                sts128(rec + r * 1024 + ((6 ^ rot) << 4), pv[4], pv[5], pv[6], pv[7]);
                sts128(rec + r * 1024 + ((7 ^ rot) << 4), pv[8], 0x00003f80u, 0u, 0u);
            }
            fence_async_smem();
            bar_sync(8, 512);
            ka_kv(sm + KA_REC + wg * 16384, g_kv + (g * 4 + wg) * KV_H, w4, lane);
            const uint32_t sm2 = __shfl_sync(~0u, sm, 1);
            const uint64_t da2 = mkdesc(sm2 + m * 8192, 16, 1024, 1), db2 = mkdesc(sm2 + KA_B, 16, 1024, 1);
            #pragma unroll
            for (int i = 22; i < 27; i++) mbar_wait(bFull + (i % 9) * 8, 0);
            #pragma unroll
            for (int j = 0; j < 9; j++) cs[j] = lds64(csa + 576 + 32 * j);
            bar_sync(7, 512);
            wg_fence();
            #pragma unroll
            for (int i = 22; i < 27; i++)
                #pragma unroll
                for (int kk = 0; kk < 4; kk++) wgmma_n72<0, 0>(acc, dadv(da2, (i - 22) * 16384 + kk * 32), dadv(db2, (i % 9) * 9216 + kk * 32), 1);
            wg_commit();
            wg_wait<0>();
            reg_fence<36>(acc);
            uint32_t ph[2][18];
            #pragma unroll
            for (int r = 0; r < 2; r++) {
                float a[18];
                const float2 ln = r ? ln1 : ln0;
                #pragma unroll
                for (int j = 0; j < 9; j++) { a[2 * j] = fmaf(-ln.x, __uint_as_float(cs[j].x), acc[4 * j + 2 * r]); a[2 * j + 1] = fmaf(-ln.x, __uint_as_float(cs[j].y), acc[4 * j + 2 * r + 1]); }
                dual_softmax(a, ln.y * LOG2E, ph[r]);
            }
            #pragma unroll
            for (int j = 0; j < 18; j++) asm volatile("" : "+r"(ph[0][j]), "+r"(ph[1][j]));
            uint32_t* og = reinterpret_cast<uint32_t*>(g_o + (mt * 2 + m) * (64 * D_) + g * 4608) + w4 * 64 + lane;
            asm volatile("" : "+l"(og));
            const uint64_t dk = mkdesc(sm2 + KA_REC, 1312, 128, 0);
            float oc[40];
            bar_sync(9, 512);
            wg_fence();
            #pragma unroll
            for (int j = 0; j < 9; j++) wgmma_rs_n80(oc, ph[0][2 * j], ph[1][2 * j], ph[0][2 * j + 1], ph[1][2 * j + 1], dadv(dk, j * 2624), j != 0);
            wg_commit();
            wg_wait<0>();
            reg_fence<40>(oc);
            const float r0 = rcp_full(oc[36] + 1e-6f), r1 = rcp_full(oc[38] + 1e-6f);
            #pragma unroll
            for (int j = 0; j < 9; j++) { og[j * 256] = pack2(oc[4 * j] * r0, oc[4 * j + 1] * r0); og[j * 256 + 32] = pack2(oc[4 * j + 2] * r1, oc[4 * j + 3] * r1); }
        }
    }
}

constexpr int K2PRE = 2, K2_B = 73728, K2_PIECE = 27648, K2_X = K2_B + 5 * K2_PIECE, K2_BAR = K2_X + 18432, K2_SMEM = K2_BAR + 128;
__global__ void __cluster_dims__(2, 1, 1) __launch_bounds__(256, 1) k2_attn(const __grid_constant__ CUtensorMap tmX, const bf16* __restrict__ b2) {
    extern __shared__ __align__(1024) char smem[];
    const uint32_t sm = smem_u32(smem);
    const uint32_t bFull = sm + K2_BAR, bX = bFull + 6 * 8;
    const int tid = threadIdx.x, lane = tid & 31, warp = __shfl_sync(~0u, tid >> 5, 0);
    const int ns = blockIdx.x & 3, mt = blockIdx.x >> 2;
    const int wg = warp >> 2, w4 = warp & 3, gq = lane >> 2, t = lane & 3;
    const bf16* wsrc = g_wo + ns * (2 * 72 * 576);
    unsigned short bb0, bb1;
    asm volatile("ld.global.nc.u16 %0, [%1];" : "=h"(bb0) : "l"(b2 + mt * 64 + w4 * 16 + gq));
    asm volatile("ld.global.nc.u16 %0, [%1];" : "=h"(bb1) : "l"(b2 + mt * 64 + w4 * 16 + gq + 8));
    auto load_w = [&](int i) {
        bulk_g2s(sm + K2_B + (i % 5) * K2_PIECE, wsrc + i * (K2_PIECE / 4), K2_PIECE / 2, bFull + i * 8);
        bulk_g2s(sm + K2_B + (i % 5) * K2_PIECE + K2_PIECE / 2, wsrc + 72 * 576 + i * (K2_PIECE / 4), K2_PIECE / 2, bFull + i * 8);
    };
    if (tid == 0) {
        #pragma unroll
        for (int i = 0; i < 7; i++) mbar_init(bFull + i * 8, 1);
        fence_mbar_init();
        #pragma unroll
        for (int i = 0; i < 6; i++) mbar_expect(bFull + i * 8, K2_PIECE + 12288);
        mbar_expect(bX, 18432);
        #pragma unroll
        for (int i = 0; i < K2PRE; i++) load_w(i);
        prefetch_tm(&tmX);
    }
    __syncthreads();
    if (tid == 0) {
        pdl_wait();
        pdl_trigger();
        const bf16* osrc = g_o + mt * (64 * D_);
        #pragma unroll
        for (int i = 0; i < 6; i++) {
            bulk_g2s(sm + i * 12288, osrc + i * 6144, 12288, bFull + i * 8);
            if (i + 1 >= K2PRE && i < 4) load_w(i + 1);
        }
        tma2d(sm + K2_X, &tmX, bX, ns * 144, mt * 64);
        tma2d(sm + K2_X + 9216, &tmX, bX, ns * 144 + 72, mt * 64);
    }
    __syncwarp();
    {
        float acc[36];
        const uint32_t xs = sm + K2_X + wg * 9216;
        uint32_t xr[18];
        const int p = ns * 2 + wg;
        unsigned long long* sb = g_stats + (mt * 4 + w4) * 128 + gq * 2;
        unsigned long long* sw = sb + p * 16;
        const unsigned long long* sr = sb + t * 32;
        uint32_t* ndst = reinterpret_cast<uint32_t*>(g_hnT + (mt * D_ + p * 72) * 64) + w4 * 64 + lane;
        asm volatile("" : "+l"(sw), "+l"(sr), "+l"(ndst));
        const uint64_t da0 = mkdesc(sm, 1024, 128, 0), db0 = mkdesc(sm + K2_B + wg * (K2_PIECE / 2), 1152, 128, 0);
        #pragma unroll
        for (int i = 0; i < 6; i++) {
            mbar_wait(bFull + i * 8, 0);
            wg_fence();
            #pragma unroll
            for (int kk = 0; kk < 6; kk++)
                wgmma_n72<0, 0>(acc, dadv(da0, i * 12288 + kk * 2048), dadv(db0, (i % 5) * K2_PIECE + kk * 2304), (i | kk) != 0);
            wg_commit();
            if (i == 1) {
                wg_wait<1>();
                bar_sync(1 + wg, 128);
                if ((tid & 127) == 96) bulk_g2s(sm + K2_B + wg * (K2_PIECE / 2), wsrc + wg * (72 * 576) + 5 * (K2_PIECE / 4), K2_PIECE / 2, bFull + 5 * 8);
                __syncwarp();
            }
            if (i == 5) {
                mbar_wait(bX, 0);
                #pragma unroll
                for (int j = 0; j < 9; j++) {
                    xr[2 * j] = lds32(xs + (w4 * 16 + gq) * 144 + j * 16 + t * 4); xr[2 * j + 1] = lds32(xs + (w4 * 16 + gq + 8) * 144 + j * 16 + t * 4);
                }
            }
        }
        wg_wait<0>();
        reg_fence<36>(acc);
        #pragma unroll
        for (int j = 0; j < 18; j++) { acc[2 * j] += bf_lo(xr[j]); acc[2 * j + 1] += bf_hi(xr[j]); }
        float m0 = 0.f, m1 = 0.f;
        #pragma unroll
        for (int j = 0; j < 9; j++) { m0 += acc[4 * j] + acc[4 * j + 1]; m1 += acc[4 * j + 2] + acc[4 * j + 3]; }
        m0 *= (1.f / 18); m1 *= (1.f / 18);
        float q0 = 0.f, q1 = 0.f, q2 = 0.f, q3 = 0.f;
        #pragma unroll
        for (int j = 0; j < 9; j++) {
            float e;
            e = acc[4 * j] - m0; q0 = fmaf(e, e, q0); e = acc[4 * j + 1] - m0; q2 = fmaf(e, e, q2);
            e = acc[4 * j + 2] - m1; q1 = fmaf(e, e, q1); e = acc[4 * j + 3] - m1; q3 = fmaf(e, e, q3);
        }
        q0 += q2; q1 += q3;
        #pragma unroll
        for (int o = 1; o < 4; o <<= 1) {
            const float a0 = __shfl_xor_sync(~0u, m0, o), a1 = __shfl_xor_sync(~0u, m1, o), b0 = __shfl_xor_sync(~0u, q0, o), b1 = __shfl_xor_sync(~0u, q1, o);
            q0 += b0 + (a0 - m0) * (a0 - m0) * (9.f * o); q1 += b1 + (a1 - m1) * (a1 - m1) * (9.f * o);
            m0 = 0.5f * (m0 + a0); m1 = 0.5f * (m1 + a1);
        }
        if (t == 0) {
            const unsigned long long r0 = ((unsigned long long)(__float_as_uint(q0) | 0x80000000u) << 32) | __float_as_uint(m0);
            const unsigned long long r1 = ((unsigned long long)(__float_as_uint(q1) | 0x80000000u) << 32) | __float_as_uint(m1);
            asm volatile("st.relaxed.gpu.global.v2.u64 [%0], {%1, %2};" :: "l"(sw), "l"(r0), "l"(r1) : "memory");
        }
        unsigned long long ra, rb, rc, rd;
        {
            int it = 0;
            while (true) {
                asm volatile("ld.relaxed.gpu.global.v2.u64 {%0, %1}, [%2];" : "=l"(ra), "=l"(rc) : "l"(sr) : "memory");
                asm volatile("ld.relaxed.gpu.global.v2.u64 {%0, %1}, [%2];" : "=l"(rb), "=l"(rd) : "l"(sr + 16) : "memory");
                const bool ok = (long long)(ra & rb & rc & rd) < 0;
                if (__all_sync(~0u, ok)) break;
                if (++it > (1 << 22)) __trap();
            }
        }
        float sc[2], mu[2];
        #pragma unroll
        for (int r = 0; r < 2; r++) {
            const unsigned long long u = r ? rc : ra, v = r ? rd : rb;
            const float ma = __uint_as_float((uint32_t)u), mb = __uint_as_float((uint32_t)v);
            float ms = ma + mb;
            ms += __shfl_xor_sync(~0u, ms, 1); ms += __shfl_xor_sync(~0u, ms, 2);
            const float mean = ms * 0.125f;
            float M2 = fabsf(__uint_as_float((uint32_t)(u >> 32))) + fabsf(__uint_as_float((uint32_t)(v >> 32))) + 72.f * ((ma - mean) * (ma - mean) + (mb - mean) * (mb - mean));
            M2 += __shfl_xor_sync(~0u, M2, 1); M2 += __shfl_xor_sync(~0u, M2, 2);
            const float var = M2 * (1.f / D_);
            const float r1 = rsqrtf(var + LN_EPS);
            const float var2 = var * r1 * r1;
            const float r2 = rsqrtf(var2 + LN_EPS);
            sc[r] = 0.5f * (r1 * r2); mu[r] = mean;
        }
        #pragma unroll
        for (int j = 0; j < 9; j++) {
            ndst[j * 256] = pack2((acc[4 * j] - mu[0]) * sc[0], (acc[4 * j + 1] - mu[0]) * sc[0]);
            ndst[j * 256 + 32] = pack2((acc[4 * j + 2] - mu[1]) * sc[1], (acc[4 * j + 3] - mu[1]) * sc[1]);
        }
        if (p == 1 && t < 2) g_ln[mt * 64 + w4 * 16 + gq + 8 * t] = 0ull;
        if (p == 0 && t < 2) {
            asm volatile("" : "+h"(bb0), "+h"(bb1));
            g_rc[mt * 64 + w4 * 16 + gq + 8 * t] = make_float2(1.f / (t ? sc[1] : sc[0]), (t ? mu[1] : mu[0]) + __uint_as_float((uint32_t)(t ? bb1 : bb0) << 16));
        }
    }
}

constexpr int PFT = 4, W2HEAD = 9;
constexpr int K3_STAGES = 6, K3_STAGE = 36864, K3_STAG = 6, K3_PRE = 2, K3_BAR = K3_STAGES * K3_STAGE, K3_SMEM = K3_BAR + 256;
DEVI uint32_t gelu2(float a0, float a1) {
    const float z0 = a0 * fmaf(a0 * a0, 0.2854192650904f, 1.5957691216057f), z1 = a1 * fmaf(a1 * a1, 0.2854192650904f, 1.5957691216057f);
    return pack2(fmaf(a0, tanh_fast(z0), a0), fmaf(a1, tanh_fast(z1), a1));
}
template<int NB> DEVI void k3_store(const float* q, uint32_t* dst) {
    #pragma unroll
    for (int j = 0; j < NB; j++) { dst[j * 256] = gelu2(q[4 * j], q[4 * j + 1]); dst[j * 256 + 32] = gelu2(q[4 * j + 2], q[4 * j + 3]); }
}
DEVI void k3_typeb(uint32_t sm_, int fc_, float bias0, float bias1, const bf16* __restrict__ b1) {
    const uint32_t sm = __shfl_sync(~0u, sm_, 0);
    const int fc = __shfl_sync(~0u, fc_, 0);
    const uint32_t bFull = sm + K3_BAR, bEmpty = bFull + K3_STAGES * 8;
    const int tid = threadIdx.x, lane = tid & 31, warp = __shfl_sync(~0u, tid >> 5, 0);
    const int wg = warp >> 2, w4 = warp & 3, gq = lane >> 2;
    const uint32_t st = sm + wg * 8192;
    const uint64_t da0 = mkdesc(st, 8192, 1024, 1);
    int s = 0, ps = 0; uint32_t ph = 0;
    {
            const int f2 = (fc + 2) * 64 + w4 * 16 + gq;
            const float bias2 = 0.5f * __bfloat162float(b1[f2]), bias3 = 0.5f * __bfloat162float(b1[f2 + 8]);
            float acc[48], acc2[24];
            const uint64_t da2 = mkdesc(sm + 16384, 8192, 1024, 1), db0 = mkdesc(sm + 24576, 128, 1024, 0), db2 = mkdesc(sm + 24576 + wg * 6144, 128, 1024, 0);
            #pragma unroll 1
            for (int i = 0; i < 32 - K3_STAG; i++) {
                mbar_wait(bFull + s * 8, ph);
                const uint32_t so = s * K3_STAGE;
                wg_fence();
                #pragma unroll
                for (int kk = 0; kk < 4; kk++) {
                    wgmma_n96<1, 1>(acc, dadv(da0, so + kk * 2048), dadv(db0, so + kk * 256), (i | kk) != 0);
                    wgmma_n48<1, 1>(acc2, dadv(da2, so + kk * 2048), dadv(db2, so + kk * 256), (i | kk) != 0);
                }
                wg_commit();
                wg_wait<1>();
                if (i > 0 && lane == 0) mbar_arrive(bEmpty + ps * 8);
                ps = s;
                if (++s == K3_STAGES) { s = 0; ph ^= 1; }
            }
            if (wg == 1) {
                wg_wait<0>();
                if (lane == 0) mbar_arrive(bEmpty + ps * 8);
                #pragma unroll
                for (int i = 32 - K3_STAG; i < 32; i++) mbar_wait(bFull + (i % K3_STAGES) * 8, (i / K3_STAGES) & 1);
                bar_sync(3, 256);
            }
            #pragma unroll
            for (int i = 32 - K3_STAG; i < 32; i++) {
                if (wg == 0) mbar_wait(bFull + (i % K3_STAGES) * 8, (i / K3_STAGES) & 1);
                const uint32_t so = (i % K3_STAGES) * K3_STAGE;
                wg_fence();
                #pragma unroll
                for (int kk = 0; kk < 4; kk++) {
                    wgmma_n96<1, 1>(acc, dadv(da0, so + kk * 2048), dadv(db0, so + kk * 256), 1);
                    wgmma_n48<1, 1>(acc2, dadv(da2, so + kk * 2048), dadv(db2, so + kk * 256), 1);
                }
                wg_commit();
                if (i == 32 - K3_STAG && wg == 0) { wg_wait<1>(); if (lane == 0) mbar_arrive(bEmpty + ps * 8); }
            }
            if (wg == 0) bar_arrive(3, 256);
            wg_wait<0>();
            reg_fence<48>(acc); reg_fence<24>(acc2);
            #pragma unroll
            for (int j = 0; j < 48; j++) acc[j] += (j & 2) ? bias1 : bias0;
            #pragma unroll
            for (int j = 0; j < 24; j++) acc2[j] += (j & 2) ? bias3 : bias2;
            k3_store<12>(acc, reinterpret_cast<uint32_t*>(g_u + ((fc + wg) * D_ + 480) * 64) + w4 * 64 + lane);
            k3_store<6>(acc2, reinterpret_cast<uint32_t*>(g_u + ((fc + 2) * D_ + 480 + wg * 48) * 64) + w4 * 64 + lane);
    }
}
__global__ void __cluster_dims__(2, 1, 1) __launch_bounds__(288, 1) k3_mix1(const __grid_constant__ CUtensorMap tmW1a, const __grid_constant__ CUtensorMap tmW1b,
                                                                             const bf16* __restrict__ b1, const bf16* __restrict__ w1, const bf16* __restrict__ w2) {
    extern __shared__ __align__(1024) char smem[];
    const uint32_t sm = smem_u32(smem);
    const uint32_t bFull = sm + K3_BAR, bEmpty = bFull + K3_STAGES * 8;
    const int tid = threadIdx.x, lane = tid & 31, warp = __shfl_sync(~0u, tid >> 5, 0);
    const int cl = blockIdx.x >> 1, rank = blockIdx.x & 1;
    bool tb = false; int fc, d0;
    if (cl < 36) { fc = 2 * cl; d0 = 160 * rank; }
    else if (cl < 60) { const int q = (cl - 36) >> 1, e = (cl - 36) & 1; tb = rank; fc = rank ? 6 * q + 3 * e : 6 * q + 4 * e; d0 = rank ? 480 : 320; }
    else { fc = 6 * (2 * (cl - 60) + rank) + 2; d0 = 320; }
    const CUtensorMap* tm = tb ? &tmW1b : &tmW1a;
    const uint32_t abytes = tb ? 24576 : 16384;
    if (tid == 256) {
        #pragma unroll
        for (int i = 0; i < K3_STAGES; i++) { mbar_init(bFull + i * 8, 1); mbar_init(bEmpty + i * 8, 8); }
        fence_mbar_init();
        #pragma unroll
        for (int i = 0; i < K3_STAGES; i++) mbar_expect(bFull + i * 8, K3_STAGE);
        #pragma unroll
        for (int i = 0; i < K3_PRE; i++) tma3d(sm + i * K3_STAGE, tm, bFull + i * 8, 0, i * 64, fc);
    }
    __syncthreads();
    if (warp == 8) {
        if (tid == 256) {
            pdl_wait();
            pdl_trigger();
            const bf16* hs = g_hnT + d0 * 64;
            #pragma unroll
            for (int i = 0; i < K3_STAGES; i++) {
                bulk_g2s(sm + i * K3_STAGE + abytes, hs + i * (D_ * 64), K3_STAGE - abytes, bFull + i * 8);
                if (i >= K3_PRE) tma3d(sm + i * K3_STAGE, tm, bFull + i * 8, 0, i * 64, fc);
            }
            int s = 0; uint32_t ph = 0;
            #pragma unroll 1
            for (int i = K3_STAGES; i < 32; i++) {
                mbar_wait(bEmpty + s * 8, ph);
                mbar_expect(bFull + s * 8, K3_STAGE);
                tma3d(sm + s * K3_STAGE, tm, bFull + s * 8, 0, i * 64, fc);
                bulk_g2s(sm + s * K3_STAGE + abytes, hs + i * (D_ * 64), K3_STAGE - abytes, bFull + s * 8);
                if (i == 18 && blockIdx.x < 128) l2_prefetch(w1 + (size_t)(2048 - 64 * PFT) * F_ + blockIdx.x * (2304 * PFT), 4608 * PFT);
                if (++s == K3_STAGES) { s = 0; ph ^= 1; }
            }
            if (blockIdx.x < 128) l2_prefetch(w2 + (size_t)(blockIdx.x & 1) * (2304 * S_) + (blockIdx.x >> 1) * (W2HEAD * 2048), W2HEAD * 4096);
        }
    } else {
        const int wg = warp >> 2, w4 = warp & 3, gq = lane >> 2;
        const int f0 = (fc + wg) * 64 + w4 * 16 + gq;
        const float bias0 = 0.5f * __bfloat162float(b1[f0]), bias1 = 0.5f * __bfloat162float(b1[f0 + 8]);
        uint32_t* dst = reinterpret_cast<uint32_t*>(g_u + ((fc + wg) * D_ + d0) * 64) + w4 * 64 + lane;
        const uint32_t st = sm + wg * 8192;
        const uint64_t da0 = mkdesc(st, 8192, 1024, 1);
        int s = 0, ps = 0; uint32_t ph = 0;
        if (!tb) {
            float acc[80];
            #pragma unroll
            for (int j = 0; j < 80; j++) acc[j] = (j & 2) ? bias1 : bias0;
            reg_fence<80>(acc);
            const uint64_t db0 = mkdesc(sm + 16384, 128, 1024, 0);
            #pragma unroll 1
            for (int i = 0; i < 32 - K3_STAG; i++) {
                mbar_wait(bFull + s * 8, ph);
                const uint64_t da = dadv(da0, s * K3_STAGE), db = dadv(db0, s * K3_STAGE);
                wg_fence();
                #pragma unroll
                for (int kk = 0; kk < 4; kk++)
                    wgmma_n160<1, 1>(acc, dadv(da, kk * 2048), dadv(db, kk * 256), 1);
                wg_commit();
                wg_wait<1>();
                if (i > 0 && lane == 0) mbar_arrive(bEmpty + ps * 8);
                ps = s;
                if (++s == K3_STAGES) { s = 0; ph ^= 1; }
            }
            if (wg == 1) {
                wg_wait<0>();
                if (lane == 0) mbar_arrive(bEmpty + ps * 8);
                #pragma unroll
                for (int i = 32 - K3_STAG; i < 32; i++) mbar_wait(bFull + (i % K3_STAGES) * 8, (i / K3_STAGES) & 1);
                bar_sync(3, 256);
            }
            #pragma unroll
            for (int i = 32 - K3_STAG; i < 32; i++) {
                if (wg == 0) mbar_wait(bFull + (i % K3_STAGES) * 8, (i / K3_STAGES) & 1);
                wg_fence();
                #pragma unroll
                for (int kk = 0; kk < 4; kk++)
                    wgmma_n160<1, 1>(acc, dadv(da0, (i % K3_STAGES) * K3_STAGE + kk * 2048), dadv(db0, (i % K3_STAGES) * K3_STAGE + kk * 256), 1);
                wg_commit();
                if (i == 32 - K3_STAG && wg == 0) { wg_wait<1>(); if (lane == 0) mbar_arrive(bEmpty + ps * 8); }
            }
            if (wg == 0) bar_arrive(3, 256);
            wg_wait<0>();
            reg_fence<80>(acc);
            k3_store<20>(acc, dst);
        } else {
            k3_typeb(sm, fc, bias0, bias1, b1);
        }
    }
}

constexpr int SLOTC = 700, SLOTP = 578, K4A0 = 1, K4_PD = 4;
constexpr int K4_STAGES = 5, K4_STAGE = 8192 + 36864, K4_STAG = 3, K4_BAR = K4_STAGES * K4_STAGE, K4_SMEM = K4_BAR + 256;
constexpr int K4_XS = (36 - K4_STAG - 1) % K4_STAGES;
__global__ void __cluster_dims__(2, 1, 1) __launch_bounds__(288, 1) k4_mix2(const __grid_constant__ CUtensorMap tmW2, const __grid_constant__ CUtensorMap tmOut) {
    extern __shared__ __align__(1024) char smem[];
    const uint32_t sm = smem_u32(smem);
    const uint32_t bFull = sm + K4_BAR, bEmpty = bFull + K4_STAGES * 8, bP = bEmpty + K4_STAGES * 8, bRdy = bP + 16, bH = bRdy + 8;
    const int tid = threadIdx.x, lane = tid & 31, warp = __shfl_sync(~0u, tid >> 5, 0);
    const int ks = blockIdx.x & 1, tm = (blockIdx.x >> 1) & 31, tn = blockIdx.x >> 6;
    const int k0 = ks * 36;
    if (tid == 256) {
        #pragma unroll
        for (int i = 0; i < K4_STAGES; i++) { mbar_init(bFull + i * 8, 1); mbar_init(bEmpty + i * 8, 8); }
        mbar_init(bP, 1); mbar_init(bP + 8, 1); mbar_init(bRdy, 8); mbar_init(bH, 1);
        fence_mbar_init();
        #pragma unroll
        for (int i = 0; i < K4A0; i++) tma3d(sm + i * K4_STAGE, &tmW2, bFull + i * 8, 0, (k0 + i) * 64, tm);
    }
    __syncthreads();
    cluster_arrive_relaxed();
    if (tid == 0) {
        #pragma unroll
        for (int i = K4A0; i < 2; i++) tma3d(sm + i * K4_STAGE, &tmW2, bFull + i * 8, 0, (k0 + i) * 64, tm);
    }
    if (tid == 32) {
        #pragma unroll
        for (int i = 0; i < K4_STAGES; i++) mbar_expect(bFull + i * 8, K4_STAGE);
    }
    if (tid == 128) { mbar_expect(bP, 9216); mbar_expect(bP + 8, 9216); prefetch_tm(&tmOut); }
    __syncwarp();
    if (warp == 8) {
        if (lane == 0) {
            pdl_wait();
            const bf16* us = g_u + ((size_t)k0 * D_ + tn * 288) * 64;
            uint32_t slot = clock() + SLOTC;
            #pragma unroll
            for (int i = 0; i < K4_STAGES; i++) {
                if (i >= 2) { tma3d(sm + i * K4_STAGE, &tmW2, bFull + i * 8, 0, (k0 + i) * 64, tm); while ((int)(clock() - slot) < 0) {} slot += SLOTP; }
                bulk_g2s(sm + i * K4_STAGE + 8192, us + (size_t)i * (D_ * 64), 36864, bFull + i * 8);
            }
            int s = 0; uint32_t ph = 0;
            #pragma unroll 1
            for (int i = K4_STAGES; i < 36; i++) {
                mbar_wait(bEmpty + s * 8, ph);
                mbar_expect(bFull + s * 8, K4_STAGE);
                tma3d(sm + s * K4_STAGE, &tmW2, bFull + s * 8, 0, (k0 + i) * 64, tm);
                if (i + K4_PD < 36 && ((i ^ tn) & 1)) tma3d_prefetch(&tmW2, 0, (k0 + i + K4_PD) * 64, tm);
                if (i < 32) { while ((int)(clock() - slot) < 0) {} slot += SLOTP; }
                bulk_g2s(sm + s * K4_STAGE + 8192, us + (size_t)i * (D_ * 64), 36864, bFull + s * 8);
                if (++s == K4_STAGES) { s = 0; ph ^= 1; }
            }
            static_assert(K4_STAG <= 3, "stage of step 31 is free");
            mbar_wait(bEmpty + s * 8, ph);
            mbar_expect(bH, 18432);
            bulk_g2s(sm + (31 % K4_STAGES) * K4_STAGE, g_hnT + (tm * D_ + tn * 288 + ks * 144) * 64, 18432, bH);
        }
        __syncwarp();
        cluster_wait();
        #pragma unroll
        for (int hh = 0; hh < 2; hh++) {
            bar_sync(4 + hh, 160);
            if (lane == 0) {
                tma2d_store(&tmOut, sm + K4_XS * K4_STAGE + 24576 + hh * 9216, tn * 288 + ks * 144 + hh * 72, tm * 64);
                bulk_commit();
            }
            __syncwarp();
        }
        if (lane == 0) { bulk_wait_read(); }
    } else {
        const int wg = warp >> 2, w4 = warp & 3, tw = tid & 127;
        const bool keep = wg == ks;
        float acc[72];
        const uint64_t da0 = mkdesc(sm, 8192, 1024, 1), db0 = mkdesc(sm + 8192 + wg * 18432, 128, 1024, 0);
        const uint32_t rdy = mapa(bRdy, ks ^ 1);
        cluster_wait();
        int s = 0, ps = 0; uint32_t ph = 0;
        #pragma unroll 1
        for (int i = 0; i < 36 - K4_STAG; i++) {
            mbar_wait(bFull + s * 8, ph);
            const uint64_t da = dadv(da0, s * K4_STAGE), db = dadv(db0, s * K4_STAGE);
            wg_fence();
            #pragma unroll
            for (int kk = 0; kk < 4; kk++)
                wgmma_n144<1, 1>(acc, dadv(da, kk * 2048), dadv(db, kk * 256), (i | kk) != 0);
            wg_commit();
            wg_wait<1>();
            if (i > 0 && lane == 0) mbar_arrive(bEmpty + ps * 8);
            ps = s;
            if (++s == K4_STAGES) { s = 0; ph ^= 1; }
        }
        const uint32_t xa = sm + K4_XS * K4_STAGE + tw * 16;
        const uint2 rc0 = ldg64(g_rc + tm * 64 + w4 * 16 + (lane >> 2)), rc1 = ldg64(g_rc + tm * 64 + w4 * 16 + (lane >> 2) + 8);
        float res[36];
        const uint32_t ya = sm + (31 % K4_STAGES) * K4_STAGE + 20480 + tw * 16;
        auto residual = [&](int hh) {
            uint32_t hp[20];
            mbar_wait(bH, 0);
            const uint32_t ha = sm + (31 % K4_STAGES) * K4_STAGE + hh * 9216 + (lane >> 4) * 1024 + w4 * 256 + (lane & 15) * 16;
            #pragma unroll
            for (int j = 0; j < 5; j++)
                asm volatile("ldmatrix.sync.aligned.m8n8.x4.shared.b16 {%0,%1,%2,%3}, [%4];" : "=r"(hp[4 * j]), "=r"(hp[4 * j + 1]), "=r"(hp[4 * j + 2]), "=r"(hp[4 * j + 3]) : "r"(ha + j * 2048) : "memory");
            #pragma unroll
            for (int j = 0; j < 18; j++) {
                const float is = __uint_as_float((j & 1) ? rc1.x : rc0.x), of = __uint_as_float((j & 1) ? rc1.y : rc0.y);
                res[2 * j] = fmaf(bf_lo(hp[j]), is, of); res[2 * j + 1] = fmaf(bf_hi(hp[j]), is, of);
            }
            reg_fence<36>(res);
        };
        auto partial = [&](int hh) {
            mbar_wait(bP + hh * 8, 0);
            uint32_t o[18];
            #pragma unroll
            for (int j = 0; j < 4; j++) { const uint4 v = lds128(xa + hh * 10240 + j * 2048); o[4 * j] = v.x; o[4 * j + 1] = v.y; o[4 * j + 2] = v.z; o[4 * j + 3] = v.w; }
            { const uint2 v = lds64(xa + hh * 10240 + 8192); o[16] = v.x; o[17] = v.y; }
            #pragma unroll
            for (int j = 0; j < 18; j++) { res[2 * j] += bf_lo(o[j]); res[2 * j + 1] += bf_hi(o[j]); }
        };
        if (!keep) {
            #pragma unroll
            for (int i = 36 - K4_STAG; i < 36; i++) {
                mbar_wait(bFull + (i % K4_STAGES) * 8, (i / K4_STAGES) & 1);
                wg_fence();
                #pragma unroll
                for (int kk = 0; kk < 4; kk++)
                    wgmma_n144<1, 1>(acc, dadv(da0, (i % K4_STAGES) * K4_STAGE + kk * 2048), dadv(db0, (i % K4_STAGES) * K4_STAGE + kk * 256), 1);
                wg_commit();
                if (i == 36 - K4_STAG) { wg_wait<1>(); if (lane == 0) mbar_arrive_remote(rdy); }
            }
            bar_arrive(3, 256);
            mbar_wait(bRdy, 0);
            wg_wait<0>();
            reg_fence<72>(acc);
            const uint32_t rd = mapa(xa, ks ^ 1), rb = mapa(bP, ks ^ 1);
            #pragma unroll
            for (int hh = 0; hh < 2; hh++) {
                const float* q = acc + hh * 36;
                #pragma unroll
                for (int j = 0; j < 4; j++)
                    asm volatile("st.async.shared::cluster.mbarrier::complete_tx::bytes.v4.b32 [%0], {%1,%2,%3,%4}, [%5];"
                                 :: "r"(rd + hh * 10240 + j * 2048), "r"(pack2(q[8 * j], q[8 * j + 1])), "r"(pack2(q[8 * j + 2], q[8 * j + 3])),
                                    "r"(pack2(q[8 * j + 4], q[8 * j + 5])), "r"(pack2(q[8 * j + 6], q[8 * j + 7])), "r"(rb + hh * 8) : "memory");
                asm volatile("st.async.shared::cluster.mbarrier::complete_tx::bytes.v2.b32 [%0], {%1,%2}, [%3];"
                             :: "r"(rd + hh * 10240 + 8192), "r"(pack2(q[32], q[33])), "r"(pack2(q[34], q[35])), "r"(rb + hh * 8) : "memory");
            }
            residual(1);
            partial(1);
            reg_fence<36>(res);
            bar_sync(1, 256);
            #pragma unroll
            for (int j = 0; j < 9; j++) {
                const uint4 v = lds128(ya + j * 2048);
                res[4 * j] += __uint_as_float(v.x); res[4 * j + 1] += __uint_as_float(v.y); res[4 * j + 2] += __uint_as_float(v.z); res[4 * j + 3] += __uint_as_float(v.w);
            }
        } else {
            wg_wait<0>();
            if (lane == 0) mbar_arrive_remote(rdy);
            #pragma unroll
            for (int i = 36 - K4_STAG; i < 36; i++) mbar_wait(bFull + (i % K4_STAGES) * 8, (i / K4_STAGES) & 1);
            bar_sync(3, 256);
            wg_fence();
            #pragma unroll
            for (int i = 36 - K4_STAG; i < 36; i++)
                #pragma unroll
                for (int kk = 0; kk < 4; kk++)
                    wgmma_n144<1, 1>(acc, dadv(da0, (i % K4_STAGES) * K4_STAGE + kk * 2048), dadv(db0, (i % K4_STAGES) * K4_STAGE + kk * 256), 1);
            wg_commit();
            residual(0);
            wg_wait<0>();
            reg_fence<72>(acc);
            #pragma unroll
            for (int j = 0; j < 9; j++)
                sts128(ya + j * 2048, __float_as_uint(acc[36 + 4 * j]), __float_as_uint(acc[37 + 4 * j]), __float_as_uint(acc[38 + 4 * j]), __float_as_uint(acc[39 + 4 * j]));
            bar_arrive(1, 256);
            #pragma unroll
            for (int j = 0; j < 36; j++) res[j] += acc[j];
            partial(0);
        }
        const int hh = keep ? 0 : 1;
        uint32_t o[18];
        #pragma unroll
        for (int j = 0; j < 18; j++) o[j] = pack2(res[2 * j], res[2 * j + 1]);
        const uint32_t ad = sm + K4_XS * K4_STAGE + 24576 + hh * 9216 + (w4 * 16 + ((lane >> 3) & 1) * 8 + (lane & 7)) * 144;
        #pragma unroll
        for (int j = 0; j < 4; j++) stsm4(ad + (lane >> 4) * 16 + j * 32, o[4 * j], o[4 * j + 1], o[4 * j + 2], o[4 * j + 3]);
        stsm2(ad + 128, o[16], o[17]);
        fence_async_smem();
        bar_arrive(4 + hh, 160);
    }
}

typedef CUresult (*EncFn)(CUtensorMap*, CUtensorMapDataType, cuuint32_t, void*, const cuuint64_t*, const cuuint64_t*, const cuuint32_t*,
                          const cuuint32_t*, CUtensorMapInterleave, CUtensorMapSwizzle, CUtensorMapL2promotion, CUtensorMapFloatOOBfill);

template <typename... KArgs, typename... Args>
static void launch(void (*kern)(KArgs...), dim3 grid, int block, int smem, bool pdl, Args... args) {
    cudaLaunchConfig_t cfg = {};
    cfg.gridDim = grid; cfg.blockDim = dim3(block); cfg.dynamicSmemBytes = smem; cfg.stream = cudaStreamPerThread;
    cudaLaunchAttribute at[1];
    at[0].id = cudaLaunchAttributeProgrammaticStreamSerialization; at[0].val.programmaticStreamSerializationAllowed = 1;
    cfg.attrs = at; cfg.numAttrs = pdl ? 1 : 0;
    cudaLaunchKernelEx(&cfg, kern, args...);
}

extern "C" void kernel_launch(void* const* d_in, const int* in_sizes, int n_in, void* d_out, int out_size) {
    const bf16* x = (const bf16*)d_in[0];
    const bf16* wqkv = (const bf16*)d_in[1];
    const bf16* wphi = (const bf16*)d_in[2];
    const bf16* wo = (const bf16*)d_in[3];
    const bf16* w1 = (const bf16*)d_in[5];
    const bf16* b1 = (const bf16*)d_in[6];
    const bf16* w2 = (const bf16*)d_in[7];
    const bf16* b2 = (const bf16*)d_in[8];
    static EncFn enc = nullptr;
    if (!enc) {
        void* fn = nullptr; cudaDriverEntryPointQueryResult qr;
        cudaGetDriverEntryPoint("cuTensorMapEncodeTiled", &fn, cudaEnableDefault, &qr);
        enc = (EncFn)fn;
        cudaFuncSetAttribute(ka_front, cudaFuncAttributeMaxDynamicSharedMemorySize, KA_SMEM);
        cudaFuncSetAttribute(k2_attn, cudaFuncAttributeMaxDynamicSharedMemorySize, K2_SMEM);
        cudaFuncSetAttribute(k3_mix1, cudaFuncAttributeMaxDynamicSharedMemorySize, K3_SMEM);
        cudaFuncSetAttribute(k4_mix2, cudaFuncAttributeMaxDynamicSharedMemorySize, K4_SMEM);
    }
    CUtensorMap tmW1, tmW1b, tmW2, tmOut, tmX, tmXA;
    const cuuint32_t es[3] = {1, 1, 1};
    {
        cuuint64_t dims[3] = {64, (cuuint64_t)S_, (cuuint64_t)(F_ / 64)}; cuuint64_t st[2] = {(cuuint64_t)F_ * 2, 128}; cuuint32_t box[3] = {64, 64, 2};
        enc(&tmW1, CU_TENSOR_MAP_DATA_TYPE_BFLOAT16, 3, (void*)w1, dims, st, box, es, CU_TENSOR_MAP_INTERLEAVE_NONE, CU_TENSOR_MAP_SWIZZLE_128B, CU_TENSOR_MAP_L2_PROMOTION_L2_128B, CU_TENSOR_MAP_FLOAT_OOB_FILL_NONE);
        box[2] = 3;
        enc(&tmW1b, CU_TENSOR_MAP_DATA_TYPE_BFLOAT16, 3, (void*)w1, dims, st, box, es, CU_TENSOR_MAP_INTERLEAVE_NONE, CU_TENSOR_MAP_SWIZZLE_128B, CU_TENSOR_MAP_L2_PROMOTION_L2_128B, CU_TENSOR_MAP_FLOAT_OOB_FILL_NONE);
    }
    {
        cuuint64_t dims[3] = {64, (cuuint64_t)F_, (cuuint64_t)(S_ / 64)}; cuuint64_t st[2] = {(cuuint64_t)S_ * 2, 128}; cuuint32_t box[3] = {64, 64, 1};
        enc(&tmW2, CU_TENSOR_MAP_DATA_TYPE_BFLOAT16, 3, (void*)w2, dims, st, box, es, CU_TENSOR_MAP_INTERLEAVE_NONE, CU_TENSOR_MAP_SWIZZLE_128B, CU_TENSOR_MAP_L2_PROMOTION_L2_128B, CU_TENSOR_MAP_FLOAT_OOB_FILL_NONE);
    }
    {
        cuuint64_t dims[2] = {(cuuint64_t)D_, (cuuint64_t)S_}; cuuint64_t st[1] = {(cuuint64_t)D_ * 2}; cuuint32_t box[2] = {72, 64};
        enc(&tmOut, CU_TENSOR_MAP_DATA_TYPE_BFLOAT16, 2, d_out, dims, st, box, es, CU_TENSOR_MAP_INTERLEAVE_NONE, CU_TENSOR_MAP_SWIZZLE_NONE, CU_TENSOR_MAP_L2_PROMOTION_NONE, CU_TENSOR_MAP_FLOAT_OOB_FILL_NONE);
        enc(&tmX, CU_TENSOR_MAP_DATA_TYPE_BFLOAT16, 2, (void*)x, dims, st, box, es, CU_TENSOR_MAP_INTERLEAVE_NONE, CU_TENSOR_MAP_SWIZZLE_NONE, CU_TENSOR_MAP_L2_PROMOTION_NONE, CU_TENSOR_MAP_FLOAT_OOB_FILL_NONE);
    }
    {
        cuuint64_t dims[3] = {64, (cuuint64_t)S_, 9}; cuuint64_t st[2] = {(cuuint64_t)D_ * 2, 128}; cuuint32_t box[3] = {64, 128, 1};
        enc(&tmXA, CU_TENSOR_MAP_DATA_TYPE_BFLOAT16, 3, (void*)x, dims, st, box, es, CU_TENSOR_MAP_INTERLEAVE_NONE, CU_TENSOR_MAP_SWIZZLE_128B, CU_TENSOR_MAP_L2_PROMOTION_L2_128B, CU_TENSOR_MAP_FLOAT_OOB_FILL_NONE);
    }
    launch(k0_prep, dim3(9, 8, 4), 256, 0, false, x, wqkv, wphi, wo);
    launch(ka_front, 132, 640, KA_SMEM, true, tmXA, x, wo, w1, b1);
    launch(k2_attn, 128, 256, K2_SMEM, true, tmX, b2);
    launch(k3_mix1, 132, 288, K3_SMEM, true, tmW1, tmW1b, b1, w1, w2);
    launch(k4_mix2, 128, 288, K4_SMEM, true, tmW2, tmOut);
}
```

```cpp
#include <cuda_runtime.h>
#include <cuda.h>
#include <cuda_bf16.h>
#include <stdint.h>

typedef __nv_bfloat16 bf16;
#define DEVI __device__ __forceinline__

constexpr int S_ = 2048, D_ = 576, F_ = 4608;
constexpr float LN_EPS = 1e-5f;
constexpr float LOG2E = 1.4426950408889634f;

__device__ __align__(1024) bf16 g_o[S_ * D_];
__device__ __align__(1024) bf16 g_wqkv[8 * 27 * 72 * 64];
__device__ __align__(16) float g_cs[8 * 18 * 216];
__device__ __align__(1024) bf16 g_wo[8 * 72 * 72 * 8];
constexpr int KV_H = 960;
__device__ __align__(1024) float g_kv[32 * KV_H];
__device__ __align__(1024) unsigned long long g_stats[S_ * 8];
__device__ __align__(16) unsigned long long g_ln[S_];
__device__ __align__(16) float2 g_rc[S_];
__device__ __align__(1024) bf16 g_hnT[D_ * S_];
__device__ __align__(1024) bf16 g_u[D_ * F_];
constexpr int CNT_S = 64;
__device__ __align__(256) unsigned int g_cnt[8 * CNT_S];

DEVI uint32_t smem_u32(const void* p) { return (uint32_t)__cvta_generic_to_shared(p); }
DEVI void mbar_init(uint32_t bar, int cnt) { asm volatile("mbarrier.init.shared::cta.b64 [%0], %1;" :: "r"(bar), "r"(cnt) : "memory"); }
DEVI void mbar_expect(uint32_t bar, uint32_t bytes) { asm volatile("mbarrier.arrive.expect_tx.shared::cta.b64 _, [%0], %1;" :: "r"(bar), "r"(bytes) : "memory"); }
DEVI void mbar_wait(uint32_t bar, uint32_t parity) {
    asm volatile("{\n.reg .pred p;\n.reg .u32 it;\n"
                 "mbarrier.try_wait.parity.shared::cta.b64 p, [%0], %1;\n@p bra MW_DONE;\n"
                 "mov.u32 it, 0;\n"
                 "MW_LOOP:\nmbarrier.try_wait.parity.shared::cta.b64 p, [%0], %1;\n@p bra MW_DONE;\n"
                 "add.u32 it, it, 1;\nsetp.lt.u32 p, it, 4194304;\n@p bra MW_LOOP;\ntrap;\n"
                 "MW_DONE:\n}" :: "r"(bar), "r"(parity) : "memory");
}
DEVI void mbar_arrive(uint32_t bar) { asm volatile("mbarrier.arrive.shared::cta.b64 _, [%0];" :: "r"(bar) : "memory"); }
DEVI uint32_t mapa(uint32_t addr, uint32_t cta) { uint32_t r; asm volatile("mapa.shared::cluster.u32 %0, %1, %2;" : "=r"(r) : "r"(addr), "r"(cta)); return r; }
DEVI void mbar_arrive_remote(uint32_t raddr) { asm volatile("mbarrier.arrive.shared::cluster.b64 _, [%0];" :: "r"(raddr) : "memory"); }
DEVI void fence_mbar_init() { asm volatile("fence.mbarrier_init.release.cluster;" ::: "memory"); }
DEVI void fence_async_smem() { asm volatile("fence.proxy.async.shared::cta;" ::: "memory"); }
DEVI void cluster_arrive_relaxed() { asm volatile("barrier.cluster.arrive.relaxed.aligned;" ::: "memory"); }
DEVI void cluster_wait() { asm volatile("barrier.cluster.wait.aligned;" ::: "memory"); }
DEVI void bar_sync(int id, int n) { asm volatile("bar.sync %0, %1;" :: "r"(id), "r"(n) : "memory"); }
DEVI void bar_arrive(int id, int n) { asm volatile("bar.arrive %0, %1;" :: "r"(id), "r"(n) : "memory"); }
DEVI void pdl_wait() { asm volatile("griddepcontrol.wait;" ::: "memory"); }
DEVI void pdl_trigger() { asm volatile("griddepcontrol.launch_dependents;" ::: "memory"); }
DEVI void bulk_g2s(uint32_t dst, const void* src, uint32_t bytes, uint32_t bar) {
    asm volatile("cp.async.bulk.shared::cluster.global.mbarrier::complete_tx::bytes [%0], [%1], %2, [%3];" :: "r"(dst), "l"(src), "r"(bytes), "r"(bar) : "memory");
}
DEVI void bulk_s2g(void* dst, uint32_t src, uint32_t bytes) {
    asm volatile("cp.async.bulk.global.shared::cta.bulk_group [%0], [%1], %2;" :: "l"(dst), "r"(src), "r"(bytes) : "memory");
}
DEVI void l2_prefetch(const void* p, uint32_t bytes) { asm volatile("cp.async.bulk.prefetch.L2.global [%0], %1;" :: "l"(p), "r"(bytes) : "memory"); }
DEVI void bulk_commit() { asm volatile("cp.async.bulk.commit_group;" ::: "memory"); }
DEVI void bulk_wait_read() { asm volatile("cp.async.bulk.wait_group.read 0;" ::: "memory"); }
DEVI void tma2d(uint32_t dst, const CUtensorMap* tm, uint32_t bar, int c0, int c1) {
    asm volatile("cp.async.bulk.tensor.2d.shared::cluster.global.mbarrier::complete_tx::bytes [%0], [%1, {%3, %4}], [%2];" :: "r"(dst), "l"(tm), "r"(bar), "r"(c0), "r"(c1) : "memory");
}
DEVI void tma3d(uint32_t dst, const CUtensorMap* tm, uint32_t bar, int c0, int c1, int c2) {
    asm volatile("cp.async.bulk.tensor.3d.shared::cluster.global.mbarrier::complete_tx::bytes [%0], [%1, {%3, %4, %5}], [%2];" :: "r"(dst), "l"(tm), "r"(bar), "r"(c0), "r"(c1), "r"(c2) : "memory");
}
DEVI void tma3d_prefetch(const CUtensorMap* tm, int c0, int c1, int c2) {
    asm volatile("cp.async.bulk.prefetch.tensor.3d.L2.global [%0, {%1, %2, %3}];" :: "l"(tm), "r"(c0), "r"(c1), "r"(c2) : "memory");
}
DEVI void tma2d_store(const CUtensorMap* tm, uint32_t src, int c0, int c1) {
    asm volatile("cp.async.bulk.tensor.2d.global.shared::cta.bulk_group [%0, {%2, %3}], [%1];" :: "l"(tm), "r"(src), "r"(c0), "r"(c1) : "memory");
}
DEVI void prefetch_tm(const CUtensorMap* tm) { asm volatile("prefetch.tensormap [%0];" :: "l"(tm) : "memory"); }
DEVI uint64_t mkdesc(uint32_t addr, uint32_t lbo, uint32_t sbo, uint64_t swz) {
    return (uint64_t)((addr & 0x3FFFF) >> 4) | ((uint64_t)(lbo >> 4) << 16) | ((uint64_t)(sbo >> 4) << 32) | (swz << 62);
}
DEVI uint64_t dadv(uint64_t d, uint32_t bytes) { return (d & 0xffffffff00000000ull) | (uint64_t)((uint32_t)d + (bytes >> 4)); }
DEVI void wg_fence() { asm volatile("wgmma.fence.sync.aligned;" ::: "memory"); }
DEVI void wg_commit() { asm volatile("wgmma.commit_group.sync.aligned;" ::: "memory"); }
template<int N> DEVI void wg_wait() { asm volatile("wgmma.wait_group.sync.aligned %0;" :: "n"(N) : "memory"); }
template<int N> DEVI void reg_fence(float* d) {
    #pragma unroll
    for (int i = 0; i < N; i++) asm volatile("" : "+f"(d[i]) :: "memory");
}
DEVI uint32_t pack2(float lo, float hi) { uint32_t r; asm("cvt.rn.bf16x2.f32 %0, %1, %2;" : "=r"(r) : "f"(hi), "f"(lo)); return r; }
DEVI float bf_lo(uint32_t v) { return __uint_as_float(v << 16); }
DEVI float bf_hi(uint32_t v) { return __uint_as_float(v & 0xffff0000u); }
DEVI float ex2(float x) { float r; asm("ex2.approx.ftz.f32 %0, %1;" : "=f"(r) : "f"(x)); return r; }
DEVI float rcp(float x) { float r; asm("rcp.approx.ftz.f32 %0, %1;" : "=f"(r) : "f"(x)); return r; }
DEVI float rcp_full(float x) { float r; asm("rcp.approx.f32 %0, %1;" : "=f"(r) : "f"(x)); return r; }
DEVI float tanh_fast(float x) { float r; asm("tanh.approx.f32 %0, %1;" : "=f"(r) : "f"(x)); return r; }
DEVI void mma16816(float* c, uint32_t a0, uint32_t a1, uint32_t a2, uint32_t a3, uint32_t b0, uint32_t b1) {
    asm("mma.sync.aligned.m16n8k16.row.col.f32.bf16.bf16.f32 {%0,%1,%2,%3}, {%4,%5,%6,%7}, {%8,%9}, {%0,%1,%2,%3};"
        : "+f"(c[0]), "+f"(c[1]), "+f"(c[2]), "+f"(c[3]) : "r"(a0), "r"(a1), "r"(a2), "r"(a3), "r"(b0), "r"(b1));
}
DEVI void mma1688(float* c, uint32_t a0, uint32_t a1, uint32_t b0) {
    asm("mma.sync.aligned.m16n8k8.row.col.f32.bf16.bf16.f32 {%0,%1,%2,%3}, {%4,%5}, {%6}, {%0,%1,%2,%3};"
        : "+f"(c[0]), "+f"(c[1]), "+f"(c[2]), "+f"(c[3]) : "r"(a0), "r"(a1), "r"(b0));
}
DEVI void ldsm4t(uint32_t addr, uint32_t& r0, uint32_t& r1, uint32_t& r2, uint32_t& r3) {
    asm volatile("ldmatrix.sync.aligned.m8n8.x4.trans.shared.b16 {%0,%1,%2,%3}, [%4];" : "=r"(r0), "=r"(r1), "=r"(r2), "=r"(r3) : "r"(addr) : "memory");
}
DEVI void stsm4(uint32_t addr, uint32_t r0, uint32_t r1, uint32_t r2, uint32_t r3) {
    asm volatile("stmatrix.sync.aligned.m8n8.x4.shared.b16 [%0], {%1,%2,%3,%4};" :: "r"(addr), "r"(r0), "r"(r1), "r"(r2), "r"(r3) : "memory");
}
DEVI void stsm2(uint32_t addr, uint32_t r0, uint32_t r1) {
    asm volatile("stmatrix.sync.aligned.m8n8.x2.shared.b16 [%0], {%1,%2};" :: "r"(addr), "r"(r0), "r"(r1) : "memory");
}
DEVI void sts128(uint32_t addr, uint32_t r0, uint32_t r1, uint32_t r2, uint32_t r3) {
    asm volatile("st.shared.v4.b32 [%0], {%1,%2,%3,%4};" :: "r"(addr), "r"(r0), "r"(r1), "r"(r2), "r"(r3) : "memory");
}
DEVI void sts32(uint32_t addr, uint32_t r0) { asm volatile("st.shared.b32 [%0], %1;" :: "r"(addr), "r"(r0) : "memory"); }
DEVI uint32_t lds32(uint32_t addr) { uint32_t r; asm volatile("ld.shared.b32 %0, [%1];" : "=r"(r) : "r"(addr) : "memory"); return r; }
DEVI void wgmma_rs_n80(float* d, uint32_t a0, uint32_t a1, uint32_t a2, uint32_t a3, uint64_t db, int sd) {
  asm volatile("{\n.reg .pred p;\nsetp.ne.b32 p, %45, 0;\n"
    "wgmma.mma_async.sync.aligned.m64n80k16.f32.bf16.bf16 {%0, %1, %2, %3, %4, %5, %6, %7, %8, %9, %10, %11, %12, %13, %14, %15, %16, %17, %18, %19, %20, %21, %22, %23, %24, %25, %26, %27, %28, %29, %30, %31, %32, %33, %34, %35, %36, %37, %38, %39}, {%40, %41, %42, %43}, %44, p, 1, 1, 0;\n}\n"
    : "+f"(d[0]), "+f"(d[1]), "+f"(d[2]), "+f"(d[3]), "+f"(d[4]), "+f"(d[5]), "+f"(d[6]), "+f"(d[7]), "+f"(d[8]), "+f"(d[9]), "+f"(d[10]), "+f"(d[11]), "+f"(d[12]), "+f"(d[13]), "+f"(d[14]), "+f"(d[15]), "+f"(d[16]), "+f"(d[17]), "+f"(d[18]), "+f"(d[19]), "+f"(d[20]), "+f"(d[21]), "+f"(d[22]), "+f"(d[23]), "+f"(d[24]), "+f"(d[25]), "+f"(d[26]), "+f"(d[27]), "+f"(d[28]), "+f"(d[29]), "+f"(d[30]), "+f"(d[31]), "+f"(d[32]), "+f"(d[33]), "+f"(d[34]), "+f"(d[35]), "+f"(d[36]), "+f"(d[37]), "+f"(d[38]), "+f"(d[39]) : "r"(a0), "r"(a1), "r"(a2), "r"(a3), "l"(db), "r"(sd));
}
template<int TA, int TB> DEVI void wgmma_n40(float* d, uint64_t da, uint64_t db, int sd) {
  asm volatile("{\n.reg .pred p;\nsetp.ne.b32 p, %22, 0;\n"
    "wgmma.mma_async.sync.aligned.m64n40k16.f32.bf16.bf16 {%0, %1, %2, %3, %4, %5, %6, %7, %8, %9, %10, %11, %12, %13, %14, %15, %16, %17, %18, %19}, %20, %21, p, 1, 1, %23, %24;\n}\n"
    : "+f"(d[0]), "+f"(d[1]), "+f"(d[2]), "+f"(d[3]), "+f"(d[4]), "+f"(d[5]), "+f"(d[6]), "+f"(d[7]), "+f"(d[8]), "+f"(d[9]), "+f"(d[10]), "+f"(d[11]), "+f"(d[12]), "+f"(d[13]), "+f"(d[14]), "+f"(d[15]), "+f"(d[16]), "+f"(d[17]), "+f"(d[18]), "+f"(d[19]) : "l"(da), "l"(db), "r"(sd), "n"(TA), "n"(TB));
}
template<int TA, int TB> DEVI void wgmma_n48(float* d, uint64_t da, uint64_t db, int sd) {
  asm volatile("{\n.reg .pred p;\nsetp.ne.b32 p, %26, 0;\n"
    "wgmma.mma_async.sync.aligned.m64n48k16.f32.bf16.bf16 {%0, %1, %2, %3, %4, %5, %6, %7, %8, %9, %10, %11, %12, %13, %14, %15, %16, %17, %18, %19, %20, %21, %22, %23}, %24, %25, p, 1, 1, %27, %28;\n}\n"
    : "+f"(d[0]), "+f"(d[1]), "+f"(d[2]), "+f"(d[3]), "+f"(d[4]), "+f"(d[5]), "+f"(d[6]), "+f"(d[7]), "+f"(d[8]), "+f"(d[9]), "+f"(d[10]), "+f"(d[11]), "+f"(d[12]), "+f"(d[13]), "+f"(d[14]), "+f"(d[15]), "+f"(d[16]), "+f"(d[17]), "+f"(d[18]), "+f"(d[19]), "+f"(d[20]), "+f"(d[21]), "+f"(d[22]), "+f"(d[23]) : "l"(da), "l"(db), "r"(sd), "n"(TA), "n"(TB));
}
template<int TA, int TB> DEVI void wgmma_n72(float* d, uint64_t da, uint64_t db, int sd) {
  asm volatile("{\n.reg .pred p;\nsetp.ne.b32 p, %38, 0;\n"
    "wgmma.mma_async.sync.aligned.m64n72k16.f32.bf16.bf16 {%0, %1, %2, %3, %4, %5, %6, %7, %8, %9, %10, %11, %12, %13, %14, %15, %16, %17, %18, %19, %20, %21, %22, %23, %24, %25, %26, %27, %28, %29, %30, %31, %32, %33, %34, %35}, %36, %37, p, 1, 1, %39, %40;\n}\n"
    : "+f"(d[0]), "+f"(d[1]), "+f"(d[2]), "+f"(d[3]), "+f"(d[4]), "+f"(d[5]), "+f"(d[6]), "+f"(d[7]), "+f"(d[8]), "+f"(d[9]), "+f"(d[10]), "+f"(d[11]), "+f"(d[12]), "+f"(d[13]), "+f"(d[14]), "+f"(d[15]), "+f"(d[16]), "+f"(d[17]), "+f"(d[18]), "+f"(d[19]), "+f"(d[20]), "+f"(d[21]), "+f"(d[22]), "+f"(d[23]), "+f"(d[24]), "+f"(d[25]), "+f"(d[26]), "+f"(d[27]), "+f"(d[28]), "+f"(d[29]), "+f"(d[30]), "+f"(d[31]), "+f"(d[32]), "+f"(d[33]), "+f"(d[34]), "+f"(d[35]) : "l"(da), "l"(db), "r"(sd), "n"(TA), "n"(TB));
}
template<int TA, int TB> DEVI void wgmma_n96(float* d, uint64_t da, uint64_t db, int sd) {
  asm volatile("{\n.reg .pred p;\nsetp.ne.b32 p, %50, 0;\n"
    "wgmma.mma_async.sync.aligned.m64n96k16.f32.bf16.bf16 {%0, %1, %2, %3, %4, %5, %6, %7, %8, %9, %10, %11, %12, %13, %14, %15, %16, %17, %18, %19, %20, %21, %22, %23, %24, %25, %26, %27, %28, %29, %30, %31, %32, %33, %34, %35, %36, %37, %38, %39, %40, %41, %42, %43, %44, %45, %46, %47}, %48, %49, p, 1, 1, %51, %52;\n}\n"
    : "+f"(d[0]), "+f"(d[1]), "+f"(d[2]), "+f"(d[3]), "+f"(d[4]), "+f"(d[5]), "+f"(d[6]), "+f"(d[7]), "+f"(d[8]), "+f"(d[9]), "+f"(d[10]), "+f"(d[11]), "+f"(d[12]), "+f"(d[13]), "+f"(d[14]), "+f"(d[15]), "+f"(d[16]), "+f"(d[17]), "+f"(d[18]), "+f"(d[19]), "+f"(d[20]), "+f"(d[21]), "+f"(d[22]), "+f"(d[23]), "+f"(d[24]), "+f"(d[25]), "+f"(d[26]), "+f"(d[27]), "+f"(d[28]), "+f"(d[29]), "+f"(d[30]), "+f"(d[31]), "+f"(d[32]), "+f"(d[33]), "+f"(d[34]), "+f"(d[35]), "+f"(d[36]), "+f"(d[37]), "+f"(d[38]), "+f"(d[39]), "+f"(d[40]), "+f"(d[41]), "+f"(d[42]), "+f"(d[43]), "+f"(d[44]), "+f"(d[45]), "+f"(d[46]), "+f"(d[47]) : "l"(da), "l"(db), "r"(sd), "n"(TA), "n"(TB));
}
template<int TA, int TB> DEVI void wgmma_n144(float* d, uint64_t da, uint64_t db, int sd) {
  asm volatile("{\n.reg .pred p;\nsetp.ne.b32 p, %74, 0;\n"
    "wgmma.mma_async.sync.aligned.m64n144k16.f32.bf16.bf16 {%0, %1, %2, %3, %4, %5, %6, %7, %8, %9, %10, %11, %12, %13, %14, %15, %16, %17, %18, %19, %20, %21, %22, %23, %24, %25, %26, %27, %28, %29, %30, %31, %32, %33, %34, %35, %36, %37, %38, %39, %40, %41, %42, %43, %44, %45, %46, %47, %48, %49, %50, %51, %52, %53, %54, %55, %56, %57, %58, %59, %60, %61, %62, %63, %64, %65, %66, %67, %68, %69, %70, %71}, %72, %73, p, 1, 1, %75, %76;\n}\n"
    : "+f"(d[0]), "+f"(d[1]), "+f"(d[2]), "+f"(d[3]), "+f"(d[4]), "+f"(d[5]), "+f"(d[6]), "+f"(d[7]), "+f"(d[8]), "+f"(d[9]), "+f"(d[10]), "+f"(d[11]), "+f"(d[12]), "+f"(d[13]), "+f"(d[14]), "+f"(d[15]), "+f"(d[16]), "+f"(d[17]), "+f"(d[18]), "+f"(d[19]), "+f"(d[20]), "+f"(d[21]), "+f"(d[22]), "+f"(d[23]), "+f"(d[24]), "+f"(d[25]), "+f"(d[26]), "+f"(d[27]), "+f"(d[28]), "+f"(d[29]), "+f"(d[30]), "+f"(d[31]), "+f"(d[32]), "+f"(d[33]), "+f"(d[34]), "+f"(d[35]), "+f"(d[36]), "+f"(d[37]), "+f"(d[38]), "+f"(d[39]), "+f"(d[40]), "+f"(d[41]), "+f"(d[42]), "+f"(d[43]), "+f"(d[44]), "+f"(d[45]), "+f"(d[46]), "+f"(d[47]), "+f"(d[48]), "+f"(d[49]), "+f"(d[50]), "+f"(d[51]), "+f"(d[52]), "+f"(d[53]), "+f"(d[54]), "+f"(d[55]), "+f"(d[56]), "+f"(d[57]), "+f"(d[58]), "+f"(d[59]), "+f"(d[60]), "+f"(d[61]), "+f"(d[62]), "+f"(d[63]), "+f"(d[64]), "+f"(d[65]), "+f"(d[66]), "+f"(d[67]), "+f"(d[68]), "+f"(d[69]), "+f"(d[70]), "+f"(d[71]) : "l"(da), "l"(db), "r"(sd), "n"(TA), "n"(TB));
}
template<int TA, int TB> DEVI void wgmma_n160(float* d, uint64_t da, uint64_t db, int sd) {
  asm volatile("{\n.reg .pred p;\nsetp.ne.b32 p, %82, 0;\n"
    "wgmma.mma_async.sync.aligned.m64n160k16.f32.bf16.bf16 {%0, %1, %2, %3, %4, %5, %6, %7, %8, %9, %10, %11, %12, %13, %14, %15, %16, %17, %18, %19, %20, %21, %22, %23, %24, %25, %26, %27, %28, %29, %30, %31, %32, %33, %34, %35, %36, %37, %38, %39, %40, %41, %42, %43, %44, %45, %46, %47, %48, %49, %50, %51, %52, %53, %54, %55, %56, %57, %58, %59, %60, %61, %62, %63, %64, %65, %66, %67, %68, %69, %70, %71, %72, %73, %74, %75, %76, %77, %78, %79}, %80, %81, p, 1, 1, %83, %84;\n}\n"
    : "+f"(d[0]), "+f"(d[1]), "+f"(d[2]), "+f"(d[3]), "+f"(d[4]), "+f"(d[5]), "+f"(d[6]), "+f"(d[7]), "+f"(d[8]), "+f"(d[9]), "+f"(d[10]), "+f"(d[11]), "+f"(d[12]), "+f"(d[13]), "+f"(d[14]), "+f"(d[15]), "+f"(d[16]), "+f"(d[17]), "+f"(d[18]), "+f"(d[19]), "+f"(d[20]), "+f"(d[21]), "+f"(d[22]), "+f"(d[23]), "+f"(d[24]), "+f"(d[25]), "+f"(d[26]), "+f"(d[27]), "+f"(d[28]), "+f"(d[29]), "+f"(d[30]), "+f"(d[31]), "+f"(d[32]), "+f"(d[33]), "+f"(d[34]), "+f"(d[35]), "+f"(d[36]), "+f"(d[37]), "+f"(d[38]), "+f"(d[39]), "+f"(d[40]), "+f"(d[41]), "+f"(d[42]), "+f"(d[43]), "+f"(d[44]), "+f"(d[45]), "+f"(d[46]), "+f"(d[47]), "+f"(d[48]), "+f"(d[49]), "+f"(d[50]), "+f"(d[51]), "+f"(d[52]), "+f"(d[53]), "+f"(d[54]), "+f"(d[55]), "+f"(d[56]), "+f"(d[57]), "+f"(d[58]), "+f"(d[59]), "+f"(d[60]), "+f"(d[61]), "+f"(d[62]), "+f"(d[63]), "+f"(d[64]), "+f"(d[65]), "+f"(d[66]), "+f"(d[67]), "+f"(d[68]), "+f"(d[69]), "+f"(d[70]), "+f"(d[71]), "+f"(d[72]), "+f"(d[73]), "+f"(d[74]), "+f"(d[75]), "+f"(d[76]), "+f"(d[77]), "+f"(d[78]), "+f"(d[79]) : "l"(da), "l"(db), "r"(sd), "n"(TA), "n"(TB));
}

__host__ __device__ constexpr int ka_seq(int p, int c) { return p == 0 ? c : c >= 5 ? 2 * c - 2 + p : p == 1 ? 17 + c : 22 + c; }
__global__ void __launch_bounds__(256, 3) k0_prep(const bf16* __restrict__ x, const bf16* __restrict__ wqkv, const bf16* __restrict__ wphi) {
    __shared__ __align__(16) uint32_t s_in[64 * 36 + 64];
    pdl_trigger();
    const int tid = threadIdx.x, lane = tid & 31, warp = __shfl_sync(~0u, tid >> 5, 0);
    const int c = blockIdx.x, g = blockIdx.y, p = blockIdx.z;
    const bool fold = p == 0 || p == 2;
    const int b = (p * 8 + g) * 9 + c;
    if (p == 3) {
        const int j = b - 216;
        const uint4 z = make_uint4(0u, 0u, 0u, 0u);
        if (j < 32) reinterpret_cast<uint4*>(g_stats)[j * 256 + tid] = z;
        else if (j < 62) reinterpret_cast<uint4*>(g_kv)[(j - 32) * 256 + tid] = z;
        else if (j == 66 && tid < 8) g_cnt[tid * CNT_S] = 0u;
        return;
    }
    constexpr int ld = 1728;
    const bf16* src = wqkv + ((p == 2 ? 0 : p + 1) * 576 + c * 64 * ld + g * 72);
    const uint32_t si = smem_u32(s_in);
    #pragma unroll
    for (int j = 0; j < 3; j++) {
        const int i = tid + j * 256, r = (i * 7282) >> 16;
        if (j < 2 || tid < 64) asm volatile("cp.async.cg.shared.global [%0], [%1], 16;" :: "r"(si + i * 16 + (r >> 3) * 32), "l"(src + (r * (ld - 72) + i * 8)) : "memory");
    }
    const int t = warp & 3, half = warp >> 2, g8 = lane >> 2, c4 = lane & 3;
    uint32_t af[3][3];
    if (fold) {
        const unsigned short* ph = reinterpret_cast<const unsigned short*>(wphi) + (g * 4 + t) * 324;
        unsigned short lo[3][3], hi[3][3];
        #pragma unroll
        for (int fb = 0; fb < 3; fb++)
            #pragma unroll
            for (int db = 0; db < 3; db++) {
                const int o = min(2 * c4 + 8 * db, 16) * 18 + min(g8 + 8 * fb, 17);
                lo[fb][db] = __ldg(ph + o); hi[fb][db] = __ldg(ph + o + 18);
            }
        #pragma unroll
        for (int fb = 0; fb < 3; fb++)
            #pragma unroll
            for (int db = 0; db < 3; db++) af[fb][db] = (uint32_t)lo[fb][db] | ((uint32_t)hi[fb][db] << 16);
    } else {
        const uint32_t v = (g8 == 2 * c4 ? 0x3f80u : 0u) | (g8 == 2 * c4 + 1 ? 0x3f800000u : 0u);
        #pragma unroll
        for (int fb = 0; fb < 3; fb++)
            #pragma unroll
            for (int db = 0; db < 3; db++) af[fb][db] = fb == db ? v : 0u;
    }
    bf16* dst = g_wqkv + (g * 27 + ka_seq(p, c)) * 4608;
    float* csd = g_cs + (g * 18 + c * 2 + half) * 216 + p * 72 + 2 * t;
    asm volatile("cp.async.wait_all;" ::: "memory");
    __syncthreads();
    if (tid < 96 && b < 192) asm volatile("prefetch.global.L2 [%0];" :: "l"(x + b * 6144 + tid * 64));
    uint32_t ov[3][4];
    const uint32_t* wr = &s_in[(half * 32 + (g8 >> 1) * 8 + (g8 & 1)) * 36 + (half * 4 + (g8 >> 1)) * 8 + t * 9 + c4];
    #pragma unroll
    for (int j = 0; j < 4; j++) {
        const uint32_t b0 = wr[j * 72], b1 = wr[j * 72 + 4], b2 = c4 == 0 ? wr[j * 72 + 8] : 0u;
        float c0[4] = {0.f, 0.f, 0.f, 0.f}, c1[4] = {0.f, 0.f, 0.f, 0.f};
        mma16816(c0, af[0][0], af[1][0], af[0][1], af[1][1], b0, b1);
        mma1688(c0, af[0][2], af[1][2], b2);
        mma16816(c1, af[2][0], 0u, af[2][1], 0u, b0, b1);
        mma1688(c1, af[2][2], 0u, b2);
        ov[0][j] = pack2(c0[0], c0[1]); ov[1][j] = pack2(c0[2], c0[3]); ov[2][j] = pack2(c1[0], c1[1]);
    }
    {
        const int nl = 2 * t + (g8 & 1);
        uint4* o = reinterpret_cast<uint4*>(dst) + ((g8 >> 1) * 8 + nl) * 8 + ((half * 4 + c4) ^ nl);
        o[0] = make_uint4(ov[0][0], ov[0][1], ov[0][2], ov[0][3]);
        o[256] = make_uint4(ov[1][0], ov[1][1], ov[1][2], ov[1][3]);
        if (g8 < 2) o[512] = make_uint4(ov[2][0], ov[2][1], ov[2][2], ov[2][3]);
    }
    {
        float cs0[4] = {0.f, 0.f, 0.f, 0.f}, cs1[4] = {0.f, 0.f, 0.f, 0.f};
        mma16816(cs0, ov[0][0], ov[1][0], ov[0][1], ov[1][1], 0x3f803f80u, 0x3f803f80u);
        mma16816(cs1, ov[2][0], 0u, ov[2][1], 0u, 0x3f803f80u, 0x3f803f80u);
        mma16816(cs0, ov[0][2], ov[1][2], ov[0][3], ov[1][3], 0x3f803f80u, 0x3f803f80u);
        mma16816(cs1, ov[2][2], 0u, ov[2][3], 0u, 0x3f803f80u, 0x3f803f80u);
        const int f = g8 + 8 * c4;
        if (f < 18) csd[8 * (f >> 1) + (f & 1)] = c4 == 0 ? cs0[0] : c4 == 1 ? cs0[2] : cs1[0];
    }
}

DEVI void dual_softmax(const float* a, float scale, uint32_t* o) {
    float mx = a[0], mn = a[0];
    #pragma unroll
    for (int j = 1; j < 18; j++) { mx = fmaxf(mx, a[j]); mn = fminf(mn, a[j]); }
    const float mxs = -mx * scale, mns = mn * scale;
    float ep[18], en[18], sp = 0.f, sn = 0.f;
    #pragma unroll
    for (int j = 0; j < 18; j++) {
        ep[j] = ex2(fmaf(a[j], scale, mxs)); sp += ep[j];
        en[j] = ex2(fmaf(a[j], -scale, mns)); sn += en[j];
    }
    const float rp = rcp(sp), rn = rcp(sn);
    #pragma unroll
    for (int j = 0; j < 9; j++) {
        o[j] = pack2(ep[2 * j] * rp, ep[2 * j + 1] * rp);
        o[9 + j] = pack2(en[2 * j] * rn, en[2 * j + 1] * rn);
    }
}

DEVI uint4 ldg128(const void* p) { uint4 v; asm volatile("ld.global.cg.v4.u32 {%0,%1,%2,%3}, [%4];" : "=r"(v.x), "=r"(v.y), "=r"(v.z), "=r"(v.w) : "l"(p)); return v; }
DEVI uint2 ldg64(const void* p) { uint2 v; asm volatile("ld.global.cg.v2.u32 {%0,%1}, [%2];" : "=r"(v.x), "=r"(v.y) : "l"(p)); return v; }
DEVI uint4 lds128(uint32_t a) { uint4 v; asm volatile("ld.shared.v4.u32 {%0,%1,%2,%3}, [%4];" : "=r"(v.x), "=r"(v.y), "=r"(v.z), "=r"(v.w) : "r"(a) : "memory"); return v; }
DEVI uint2 lds64(uint32_t a) { uint2 v; asm volatile("ld.shared.v2.u32 {%0,%1}, [%2];" : "=r"(v.x), "=r"(v.y) : "r"(a) : "memory"); return v; }
DEVI uint32_t packu(uint32_t lo, uint32_t hi) { return pack2(__uint_as_float(lo), __uint_as_float(hi)); }
DEVI void spin_ge(const unsigned int* p, unsigned int n) {
    uint32_t f; int it = 0;
    do {
        asm volatile("ld.acquire.gpu.global.u32 %0, [%1];" : "=r"(f) : "l"(p) : "memory");
        if (++it > (1 << 22)) __trap();
    } while (f < n);
}
constexpr int KA_PRE = 3, KA_REC = 5 * 16384, KA_B = 147456, KA_CS = KA_B + 9 * 9216, KA_LN = KA_CS + 864, KA_BAR = KA_LN + 1024, KA_SMEM = KA_BAR + 160;
static_assert(KA_SMEM <= 232448, "smem");
DEVI void ka_kv(uint32_t recs, float* kvh, int w4, int lane) {
    float ck[2][20];
    const uint64_t dr = mkdesc(recs, 8192, 1024, 1);
    wg_fence();
    #pragma unroll
    for (int ks = 0; ks < 4; ks++)
        #pragma unroll
        for (int hh = 0; hh < 2; hh++) wgmma_n40<1, 1>(ck[hh], dadv(dr, hh * 8192 + ks * 2048), dadv(dr, hh * 8192 + ks * 2048), ks != 0);
    wg_commit();
    wg_wait<0>();
    reg_fence<20>(ck[0]); reg_fence<20>(ck[1]);
    if (w4 >= 2) {
        #pragma unroll
        for (int e = 1; e >= 0; e--) {
            const int nt = 2 * w4 + e - 5;
            if (nt >= 0 && (nt < 2 || lane < 12)) {
                float* p = kvh + nt * 320;
                float q[10];
                #pragma unroll
                for (int j = 0; j < 10; j++) q[j] = ck[0][(j >> 1) * 4 + 2 * e + (j & 1)] + ck[1][(j >> 1) * 4 + 2 * e + (j & 1)];
                asm volatile("red.global.add.v4.f32 [%0], {%1, %2, %3, %4};" :: "l"(p + lane * 4), "f"(q[0]), "f"(q[1]), "f"(q[2]), "f"(q[3]) : "memory");
                asm volatile("red.global.add.v4.f32 [%0], {%1, %2, %3, %4};" :: "l"(p + 128 + lane * 4), "f"(q[4]), "f"(q[5]), "f"(q[6]), "f"(q[7]) : "memory");
                if ((lane & 3) < 2) asm volatile("red.global.add.v2.f32 [%0], {%1, %2};" :: "l"(p + 256 + lane * 2), "f"(q[8]), "f"(q[9]) : "memory");
            }
        }
        __syncwarp();
        bar_arrive(2, 288);
    }
}
DEVI int gpc_pos() {
    unsigned smid, nsm;
    asm volatile("mov.u32 %0, %%smid;" : "=r"(smid));
    asm volatile("mov.u32 %0, %%nsmid;" : "=r"(nsm));
    if (nsm != 132) return blockIdx.x;
    const int tpc = smid >> 1, o = smid & 1;
    if (smid == 13 || smid == 15) return 124 + tpc;
    if (tpc < 32) return (tpc & 7) * 16 + (tpc >> 3) * 2 + o;
    if (tpc < 60) { const int j = tpc - 32, r = j / 7; return (1 + j - r * 7) * 16 + 8 + r * 2 + o; }
    if (tpc < 62) return o ? 68 + tpc : (tpc - 54) * 16 + 1;
    return 8 + (tpc - 62) * 2 + o;
}
__global__ void __launch_bounds__(640, 1) ka_front(const __grid_constant__ CUtensorMap tmXA, const bf16* __restrict__ x, const bf16* __restrict__ wo, const bf16* __restrict__ w1, const bf16* __restrict__ b1) {
    extern __shared__ __align__(1024) char smem[];
    const uint32_t sm = smem_u32(smem);
    const uint32_t bFull = sm + KA_BAR, bEmpty = bFull + 9 * 8, bLn = bEmpty + 9 * 8;
    const int tid = threadIdx.x, lane = tid & 31, warp = __shfl_sync(~0u, tid >> 5, 0);
    const int pos = gpc_pos();
    if (pos >= 128) {
        const int ns = pos - 128;
        if (tid == 0) {
            #pragma unroll
            for (int q = 0; q < 6; q++) mbar_init(bFull + q * 8, 1);
            fence_mbar_init();
            #pragma unroll
            for (int q = 0; q < 6; q++) mbar_expect(bFull + q * 8, 96 * 288);
        }
        __syncthreads();
        if (tid < 576) {
            const int h = tid / 18, d = tid - h * 18, r = (h >> 2) * 72 + (d >> 1) * 8 + 2 * (h & 3) + (d & 1);
            bulk_g2s(sm + r * 304, wo + tid * 576 + ns * 144, 288, bFull + (r / 96) * 8);
        }
        #pragma unroll 1
        for (int q = 0; q < 6; q++) {
            const uint32_t ob = sm + 175104 + (q & 1) * 27648;
            mbar_wait(bFull + q * 8, 0);
            if (tid == 0) asm volatile("cp.async.bulk.wait_group.read 1;" ::: "memory");
            __syncthreads();
            if (warp < 18) {
                #pragma unroll
                for (int rb = 0; rb < 3; rb++) {
                    uint32_t r0, r1, r2, r3;
                    ldsm4t(sm + (q * 96 + rb * 32 + lane) * 304 + warp * 16, r0, r1, r2, r3);
                    stsm4(ob + (warp / 9) * 13824 + ((rb * 4 + (lane >> 3)) * 72 + (warp % 9) * 8 + (lane & 7)) * 16, r0, r1, r2, r3);
                }
            }
            fence_async_smem();
            __syncthreads();
            if (tid == 0) {
                bulk_s2g(g_wo + (ns * 2) * (72 * 576) + q * 6912, ob, 13824);
                bulk_s2g(g_wo + (ns * 2 + 1) * (72 * 576) + q * 6912, ob + 13824, 13824);
                bulk_commit();
            }
        }
        if (tid == 0) {
            asm volatile("cp.async.bulk.wait_group 0;\nfence.proxy.async.global;\nfence.acq_rel.gpu;" ::: "memory");
            pdl_wait();
            pdl_trigger();
        }
        return;
    }
    const int g = ((pos >> 4) & 1) * 4 + (pos & 3), mt = (pos >> 5) * 4 + ((pos >> 2) & 3);
    if (warp >= 16) {
        asm volatile("setmaxnreg.dec.sync.aligned.u32 32;");
        if (warp == 16) {
            if (lane == 0) {
                #pragma unroll
                for (int c = 0; c < 9; c++) { mbar_init(bFull + c * 8, 1); mbar_init(bEmpty + c * 8, 8); }
                mbar_init(bLn, 64);
                fence_mbar_init();
            }
            __syncwarp();
            bar_arrive(0, 640);
        } else {
            bar_sync(0, 640);
            if (tid == 544) {
                #pragma unroll
                for (int c = 0; c < 9; c++) mbar_expect(bFull + c * 8, 16384 + 9216);
            }
            __syncwarp();
        }
        if (tid == 512) {
            #pragma unroll
            for (int c = 0; c < KA_PRE; c++) tma3d(sm + c * 16384, &tmXA, bFull + c * 8, 0, mt * 128, c);
            pdl_wait();
            const bf16* wsrc = g_wqkv + g * (27 * 4608);
            const uint32_t sb = sm + KA_B;
            #pragma unroll
            for (int c = 0; c < 9; c++) {
                bulk_g2s(sb + c * 9216, wsrc + c * 4608, 9216, bFull + c * 8);
                const int xc = c + KA_PRE - 2;
                if (c >= 2 && xc < 9) tma3d(sm + xc * 16384, &tmXA, bFull + xc * 8, 0, mt * 128, xc);
            }
            pdl_trigger();
            #pragma unroll 1
            for (int p = 1; p < 3; p++) {
                #pragma unroll
                for (int c = 0; c < 9; c++) {
                    mbar_wait(bEmpty + c * 8, p - 1); mbar_expect(bFull + c * 8, 9216);
                    bulk_g2s(sb + c * 9216, wsrc + (p * 9 + c) * 4608, 9216, bFull + c * 8);
                }
            }
            l2_prefetch(w1 + pos * 13824, 27648);
            if (pos == 0) l2_prefetch(b1, 9216);
        } else if (warp == 17) {
            bar_sync(2, 288);
            if (lane == 0) {
                asm volatile("red.release.gpu.global.add.u32 [%0], 1;" :: "l"(g_cnt + g * CNT_S) : "memory");
                spin_ge(g_cnt + g * CNT_S, 16);
            }
            __syncwarp();
            bar_arrive(1, 288);
        } else if (warp >= 18) {
            const int m = warp - 18;
            {
                const unsigned long long* lp = g_ln + mt * 128 + m * 64 + (lane >> 3) * 16 + (lane & 7);
                unsigned long long r0, r1; int it = 0;
                __nanosleep(700);
                while (true) {
                    asm volatile("ld.relaxed.gpu.global.u64 %0, [%1];" : "=l"(r0) : "l"(lp) : "memory");
                    asm volatile("ld.relaxed.gpu.global.u64 %0, [%1];" : "=l"(r1) : "l"(lp + 8) : "memory");
                    if (__all_sync(~0u, (long long)(r0 & r1) < 0)) break;
                    if (++it > (1 << 22)) __trap();
                }
                sts128(sm + KA_LN + (m * 32 + lane) * 16, (uint32_t)r0, (uint32_t)(r0 >> 32), (uint32_t)r1, (uint32_t)(r1 >> 32));
                mbar_arrive(bLn);
            }
        }
    } else {
        const int xrow = mt * 128 + g * 16 + warp;
        uint4 xv[3];
        {
            const uint4* xr = reinterpret_cast<const uint4*>(x + xrow * D_);
            xv[0] = ldg128(xr + lane); xv[1] = ldg128(xr + lane + 32); xv[2] = ldg128(xr + 64 + (lane & 7));
        }
        asm volatile("setmaxnreg.inc.sync.aligned.u32 112;");
        bar_sync(0, 640);
        const int wg = warp >> 2, m = wg & 1, w4 = warp & 3, gq = lane >> 2, t = lane & 3;
        {
            const uint32_t w[12] = {xv[0].x, xv[0].y, xv[0].z, xv[0].w, xv[1].x, xv[1].y, xv[1].z, xv[1].w, xv[2].x, xv[2].y, xv[2].z, xv[2].w};
            float s = 0.f, s2 = 0.f;
            #pragma unroll
            for (int i = 0; i < 12; i++) { if (i < 8) s += bf_lo(w[i]) + bf_hi(w[i]); else s2 += bf_lo(w[i]) + bf_hi(w[i]); }
            if (lane < 8) s += s2;
            #pragma unroll
            for (int o = 16; o; o >>= 1) s += __shfl_xor_sync(~0u, s, o);
            const float mean = s * (1.f / D_);
            float q = 0.f, q2 = 0.f;
            #pragma unroll
            for (int i = 0; i < 12; i++) {
                const float e0 = bf_lo(w[i]) - mean, e1 = bf_hi(w[i]) - mean;
                if (i < 8) q += e0 * e0 + e1 * e1; else q2 += e0 * e0 + e1 * e1;
            }
            if (lane < 8) q += q2;
            #pragma unroll
            for (int o = 16; o; o >>= 1) q += __shfl_xor_sync(~0u, q, o);
            const unsigned long long lrec = ((unsigned long long)(__float_as_uint(rsqrtf(q * (1.f / D_) + LN_EPS)) | 0x80000000u) << 32) | __float_as_uint(mean);
            if (lane == 0) asm volatile("st.relaxed.gpu.global.u64 [%0], %1;" :: "l"(g_ln + xrow), "l"(lrec) : "memory");
        }
        float2 ln0, ln1;
        auto ln_get = [&]() {
            mbar_wait(bLn, 0);
            const uint4 v = lds128(sm + KA_LN + (m * 32 + w4 * 8 + gq) * 16);
            ln0 = make_float2(__uint_as_float(v.x), fabsf(__uint_as_float(v.y))); ln1 = make_float2(__uint_as_float(v.z), fabsf(__uint_as_float(v.w)));
        };
        const uint64_t da = mkdesc(sm + m * 8192, 16, 1024, 1), db = mkdesc(sm + KA_B, 16, 1024, 1);
        const uint32_t csa = sm + KA_CS + 8 * t;
        const int rot = (gq + 2 * t) & 7;
        const uint32_t rec = sm + KA_REC + t * 16384 + m * 8192 + (w4 * 16 + rot) * 128;
        const uint32_t kvb = sm + KA_REC;
        if (wg < 2) {
            float acc[36]; uint2 cs[9];
            #pragma unroll
            for (int c = 0; c < 9; c++) {
                mbar_wait(bFull + c * 8, 0);
                wg_fence();
                #pragma unroll
                for (int kk = 0; kk < 4; kk++) wgmma_n72<0, 0>(acc, dadv(da, c * 16384 + kk * 32), dadv(db, c * 9216 + kk * 32), (c | kk) != 0);
                wg_commit();
                if (c > 0) { wg_wait<1>(); if (lane == 0) mbar_arrive(bEmpty + (c - 1) * 8); }
            }
            wg_wait<0>();
            reg_fence<36>(acc);
            bar_arrive(5, 512);
            if (lane == 0) mbar_arrive(bEmpty + 8 * 8);
            bar_sync(6, 384);
            #pragma unroll
            for (int j = 0; j < 9; j++) cs[j] = lds64(csa + 32 * j);
            ln_get();
            uint32_t ph[2][18];
            #pragma unroll
            for (int r = 0; r < 2; r++) {
                float a[18];
                const float2 ln = r ? ln1 : ln0;
                #pragma unroll
                for (int j = 0; j < 9; j++) { a[2 * j] = fmaf(-ln.x, __uint_as_float(cs[j].x), acc[4 * j + 2 * r]); a[2 * j + 1] = fmaf(-ln.x, __uint_as_float(cs[j].y), acc[4 * j + 2 * r + 1]); }
                dual_softmax(a, ln.y * LOG2E, ph[r]);
            }
            #pragma unroll
            for (int j = 0; j < 18; j++) asm volatile("" : "+r"(ph[0][j]), "+r"(ph[1][j]));
            bar_sync(3 + m, 256);
            #pragma unroll
            for (int r = 0; r < 2; r++) {
                #pragma unroll
                for (int j = 0; j < 4; j++) sts128(rec + r * 1024 + ((j ^ rot) << 4), ph[r][4 * j], ph[r][4 * j + 1], ph[r][4 * j + 2], ph[r][4 * j + 3]);
                sts128(rec + r * 1024 + ((4 ^ rot) << 4), ph[r][16], ph[r][17], 0u, 0u);
            }
            fence_async_smem();
            bar_sync(8, 512);
            ka_kv(sm + KA_REC + wg * 16384, g_kv + (g * 4 + wg) * KV_H, w4, lane);
            bar_arrive(7, 512);
            bar_sync(11, 256);
            #pragma unroll
            for (int j = 0; j < 6; j++) if (j < 5 || tid < 196) sts128(kvb + (j * 256 + tid) * 16, 0u, 0u, 0u, 0u);
            const float* kp = g_kv + (g * 4 + w4) * KV_H + lane * 2;
            const uint32_t kd = kvb + t * 1312 + ((gq >> 1) * 8 + 2 * w4 + (gq & 1)) * 16 + w4 * 4;
            bar_sync(1, 288);
            if (m == 0) {
                const uint4 u0 = ldg128(kp + lane * 2), u1 = ldg128(kp + 128 + lane * 2); const uint2 u2 = ldg64(kp + 256);
                const uint4 v0 = ldg128(kp + 640 + lane * 2), v1 = ldg128(kp + 768 + lane * 2); const uint2 v2 = ldg64(kp + 896);
                sts32(kd, packu(u0.x, u0.y)); sts32(kd + 5248, packu(u0.z, u0.w)); sts32(kd + 10496, packu(u1.x, u1.y)); sts32(kd + 15744, packu(u1.z, u1.w));
                if (t < 2) sts32(kd + 20992, packu(u2.x, u2.y));
                if (gq < 3) {
                    sts32(kd + 1024, packu(v0.x, v0.y)); sts32(kd + 6272, packu(v0.z, v0.w)); sts32(kd + 11520, packu(v1.x, v1.y)); sts32(kd + 16768, packu(v1.z, v1.w));
                    if (t < 2) sts32(kd + 22016, packu(v2.x, v2.y));
                }
            } else {
                const uint4 u0 = ldg128(kp + 320 + lane * 2), u1 = ldg128(kp + 448 + lane * 2); const uint2 u2 = ldg64(kp + 576);
                sts32(kd + 512, packu(u0.x, u0.y)); sts32(kd + 5760, packu(u0.z, u0.w)); sts32(kd + 11008, packu(u1.x, u1.y)); sts32(kd + 16256, packu(u1.z, u1.w));
                if (t < 2) sts32(kd + 21504, packu(u2.x, u2.y));
            }
            fence_async_smem();
            bar_arrive(9, 512);
        } else {
            float avq[36], acc[36]; uint2 cs[9];
            if (m == 1) {
                pdl_wait();
                if (tid < 384 + 108) {
                    uint2 pc[18];
                    #pragma unroll
                    for (int j = 0; j < 18; j++) pc[j] = ldg64(g_cs + (g * 18 + j) * 216 + (tid - 384) * 2);
                    float a = 0.f, c = 0.f;
                    #pragma unroll
                    for (int j = 0; j < 18; j++) { a += __uint_as_float(pc[j].x); c += __uint_as_float(pc[j].y); }
                    asm volatile("st.shared.v2.f32 [%0], {%1, %2};" :: "r"(sm + KA_CS + (tid - 384) * 8), "f"(a), "f"(c) : "memory");
                }
                bar_arrive(6, 384);
            }
            bar_sync(5, 512);
            #pragma unroll
            for (int i = 9; i < 22; i++) {
                const int c = i < 17 ? (i + 1) / 2 : i - 17;
                mbar_wait(bFull + (i % 9) * 8, (i / 9) & 1);
                wg_fence();
                #pragma unroll
                for (int kk = 0; kk < 4; kk++)
                    wgmma_n72<0, 0>((i < 17 && !(i & 1)) ? acc : avq, dadv(da, c * 16384 + kk * 32), dadv(db, (i % 9) * 9216 + kk * 32), i > 10 || kk != 0);
                wg_commit();
                if (i > 9 && i <= 18) { wg_wait<1>(); if (lane == 0) mbar_arrive(bEmpty + ((i - 1) % 9) * 8); }
                if (i == 17) bar_arrive(3 + m, 256);
                if (i == 18) bar_sync(14 + m, 128);
            }
            #pragma unroll
            for (int j = 0; j < 9; j++) cs[j] = lds64(csa + 288 + 32 * j);
            ln_get();
            wg_wait<0>();
            reg_fence<36>(avq);
            #pragma unroll
            for (int r = 0; r < 2; r++) {
                uint32_t pv[9];
                const float2 ln = r ? ln1 : ln0;
                #pragma unroll
                for (int j = 0; j < 9; j++)
                    pv[j] = pack2(fmaf(-ln.x, __uint_as_float(cs[j].x), avq[4 * j + 2 * r]) * ln.y, fmaf(-ln.x, __uint_as_float(cs[j].y), avq[4 * j + 2 * r + 1]) * ln.y);
                sts128(rec + r * 1024 + ((5 ^ rot) << 4), pv[0], pv[1], pv[2], pv[3]);
                sts128(rec + r * 1024 + ((6 ^ rot) << 4), pv[4], pv[5], pv[6], pv[7]);
                sts128(rec + r * 1024 + ((7 ^ rot) << 4), pv[8], 0x00003f80u, 0u, 0u);
            }
            fence_async_smem();
            bar_sync(8, 512);
            ka_kv(sm + KA_REC + wg * 16384, g_kv + (g * 4 + wg) * KV_H, w4, lane);
            const uint32_t sm2 = __shfl_sync(~0u, sm, 1);
            const uint64_t da2 = mkdesc(sm2 + m * 8192, 16, 1024, 1), db2 = mkdesc(sm2 + KA_B, 16, 1024, 1);
            #pragma unroll
            for (int i = 22; i < 27; i++) mbar_wait(bFull + (i % 9) * 8, 0);
            #pragma unroll
            for (int j = 0; j < 9; j++) cs[j] = lds64(csa + 576 + 32 * j);
            bar_sync(7, 512);
            wg_fence();
            #pragma unroll
            for (int i = 22; i < 27; i++)
                #pragma unroll
                for (int kk = 0; kk < 4; kk++) wgmma_n72<0, 0>(acc, dadv(da2, (i - 22) * 16384 + kk * 32), dadv(db2, (i % 9) * 9216 + kk * 32), 1);
            wg_commit();
            wg_wait<0>();
            reg_fence<36>(acc);
            uint32_t ph[2][18];
            #pragma unroll
            for (int r = 0; r < 2; r++) {
                float a[18];
                const float2 ln = r ? ln1 : ln0;
                #pragma unroll
                for (int j = 0; j < 9; j++) { a[2 * j] = fmaf(-ln.x, __uint_as_float(cs[j].x), acc[4 * j + 2 * r]); a[2 * j + 1] = fmaf(-ln.x, __uint_as_float(cs[j].y), acc[4 * j + 2 * r + 1]); }
                dual_softmax(a, ln.y * LOG2E, ph[r]);
            }
            #pragma unroll
            for (int j = 0; j < 18; j++) asm volatile("" : "+r"(ph[0][j]), "+r"(ph[1][j]));
            uint32_t* og = reinterpret_cast<uint32_t*>(g_o + (mt * 2 + m) * (64 * D_) + g * 4608) + w4 * 64 + lane;
            asm volatile("" : "+l"(og));
            const uint64_t dk = mkdesc(sm2 + KA_REC, 1312, 128, 0);
            float oc[40];
            bar_sync(9, 512);
            wg_fence();
            #pragma unroll
            for (int j = 0; j < 9; j++) wgmma_rs_n80(oc, ph[0][2 * j], ph[1][2 * j], ph[0][2 * j + 1], ph[1][2 * j + 1], dadv(dk, j * 2624), j != 0);
            wg_commit();
            wg_wait<0>();
            reg_fence<40>(oc);
            const float r0 = rcp_full(oc[36] + 1e-6f), r1 = rcp_full(oc[38] + 1e-6f);
            #pragma unroll
            for (int j = 0; j < 9; j++) { og[j * 256] = pack2(oc[4 * j] * r0, oc[4 * j + 1] * r0); og[j * 256 + 32] = pack2(oc[4 * j + 2] * r1, oc[4 * j + 3] * r1); }
        }
    }
}

constexpr int K2PRE = 2, K2_B = 73728, K2_PIECE = 27648, K2_X = K2_B + 5 * K2_PIECE, K2_BAR = K2_X + 18432, K2_SMEM = K2_BAR + 128;
__global__ void __cluster_dims__(2, 1, 1) __launch_bounds__(256, 1) k2_attn(const __grid_constant__ CUtensorMap tmX, const bf16* __restrict__ b2) {
    extern __shared__ __align__(1024) char smem[];
    const uint32_t sm = smem_u32(smem);
    const uint32_t bFull = sm + K2_BAR, bX = bFull + 6 * 8;
    const int tid = threadIdx.x, lane = tid & 31, warp = __shfl_sync(~0u, tid >> 5, 0);
    const int ns = blockIdx.x & 3, mt = blockIdx.x >> 2;
    const int wg = warp >> 2, w4 = warp & 3, gq = lane >> 2, t = lane & 3;
    const bf16* wsrc = g_wo + ns * (2 * 72 * 576);
    unsigned short bb0, bb1;
    asm volatile("ld.global.nc.u16 %0, [%1];" : "=h"(bb0) : "l"(b2 + mt * 64 + w4 * 16 + gq));
    asm volatile("ld.global.nc.u16 %0, [%1];" : "=h"(bb1) : "l"(b2 + mt * 64 + w4 * 16 + gq + 8));
    auto load_w = [&](int i) {
        bulk_g2s(sm + K2_B + (i % 5) * K2_PIECE, wsrc + i * (K2_PIECE / 4), K2_PIECE / 2, bFull + i * 8);
        bulk_g2s(sm + K2_B + (i % 5) * K2_PIECE + K2_PIECE / 2, wsrc + 72 * 576 + i * (K2_PIECE / 4), K2_PIECE / 2, bFull + i * 8);
    };
    if (tid == 0) {
        #pragma unroll
        for (int i = 0; i < 7; i++) mbar_init(bFull + i * 8, 1);
        fence_mbar_init();
        #pragma unroll
        for (int i = 0; i < 6; i++) mbar_expect(bFull + i * 8, K2_PIECE + 12288);
        mbar_expect(bX, 18432);
        #pragma unroll
        for (int i = 0; i < K2PRE; i++) load_w(i);
        prefetch_tm(&tmX);
    }
    __syncthreads();
    if (tid == 0) {
        pdl_wait();
        pdl_trigger();
        const bf16* osrc = g_o + mt * (64 * D_);
        #pragma unroll
        for (int i = 0; i < 6; i++) {
            bulk_g2s(sm + i * 12288, osrc + i * 6144, 12288, bFull + i * 8);
            if (i + 1 >= K2PRE && i < 4) load_w(i + 1);
        }
        tma2d(sm + K2_X, &tmX, bX, ns * 144, mt * 64);
        tma2d(sm + K2_X + 9216, &tmX, bX, ns * 144 + 72, mt * 64);
    }
    __syncwarp();
    {
        float acc[36];
        const uint32_t xs = sm + K2_X + wg * 9216;
        uint32_t xr[18];
        const int p = ns * 2 + wg;
        unsigned long long* sb = g_stats + (mt * 4 + w4) * 128 + gq * 2;
        unsigned long long* sw = sb + p * 16;
        const unsigned long long* sr = sb + t * 32;
        uint32_t* ndst = reinterpret_cast<uint32_t*>(g_hnT + (mt * D_ + p * 72) * 64) + w4 * 64 + lane;
        asm volatile("" : "+l"(sw), "+l"(sr), "+l"(ndst));
        const uint64_t da0 = mkdesc(sm, 1024, 128, 0), db0 = mkdesc(sm + K2_B + wg * (K2_PIECE / 2), 1152, 128, 0);
        #pragma unroll
        for (int i = 0; i < 6; i++) {
            mbar_wait(bFull + i * 8, 0);
            wg_fence();
            #pragma unroll
            for (int kk = 0; kk < 6; kk++)
                wgmma_n72<0, 0>(acc, dadv(da0, i * 12288 + kk * 2048), dadv(db0, (i % 5) * K2_PIECE + kk * 2304), (i | kk) != 0);
            wg_commit();
            if (i == 1) {
                wg_wait<1>();
                bar_sync(1 + wg, 128);
                if ((tid & 127) == 96) bulk_g2s(sm + K2_B + wg * (K2_PIECE / 2), wsrc + wg * (72 * 576) + 5 * (K2_PIECE / 4), K2_PIECE / 2, bFull + 5 * 8);
                __syncwarp();
            }
            if (i == 5) {
                mbar_wait(bX, 0);
                #pragma unroll
                for (int j = 0; j < 9; j++) {
                    xr[2 * j] = lds32(xs + (w4 * 16 + gq) * 144 + j * 16 + t * 4); xr[2 * j + 1] = lds32(xs + (w4 * 16 + gq + 8) * 144 + j * 16 + t * 4);
                }
            }
        }
        wg_wait<0>();
        reg_fence<36>(acc);
        #pragma unroll
        for (int j = 0; j < 18; j++) { acc[2 * j] += bf_lo(xr[j]); acc[2 * j + 1] += bf_hi(xr[j]); }
        float m0 = 0.f, m1 = 0.f;
        #pragma unroll
        for (int j = 0; j < 9; j++) { m0 += acc[4 * j] + acc[4 * j + 1]; m1 += acc[4 * j + 2] + acc[4 * j + 3]; }
        m0 *= (1.f / 18); m1 *= (1.f / 18);
        float q0 = 0.f, q1 = 0.f, q2 = 0.f, q3 = 0.f;
        #pragma unroll
        for (int j = 0; j < 9; j++) {
            float e;
            e = acc[4 * j] - m0; q0 = fmaf(e, e, q0); e = acc[4 * j + 1] - m0; q2 = fmaf(e, e, q2);
            e = acc[4 * j + 2] - m1; q1 = fmaf(e, e, q1); e = acc[4 * j + 3] - m1; q3 = fmaf(e, e, q3);
        }
        q0 += q2; q1 += q3;
        #pragma unroll
        for (int o = 1; o < 4; o <<= 1) {
            const float a0 = __shfl_xor_sync(~0u, m0, o), a1 = __shfl_xor_sync(~0u, m1, o), b0 = __shfl_xor_sync(~0u, q0, o), b1 = __shfl_xor_sync(~0u, q1, o);
            q0 += b0 + (a0 - m0) * (a0 - m0) * (9.f * o); q1 += b1 + (a1 - m1) * (a1 - m1) * (9.f * o);
            m0 = 0.5f * (m0 + a0); m1 = 0.5f * (m1 + a1);
        }
        if (t == 0) {
            const unsigned long long r0 = ((unsigned long long)(__float_as_uint(q0) | 0x80000000u) << 32) | __float_as_uint(m0);
            const unsigned long long r1 = ((unsigned long long)(__float_as_uint(q1) | 0x80000000u) << 32) | __float_as_uint(m1);
            asm volatile("st.relaxed.gpu.global.v2.u64 [%0], {%1, %2};" :: "l"(sw), "l"(r0), "l"(r1) : "memory");
        }
        unsigned long long ra, rb, rc, rd;
        {
            int it = 0;
            while (true) {
                asm volatile("ld.relaxed.gpu.global.v2.u64 {%0, %1}, [%2];" : "=l"(ra), "=l"(rc) : "l"(sr) : "memory");
                asm volatile("ld.relaxed.gpu.global.v2.u64 {%0, %1}, [%2];" : "=l"(rb), "=l"(rd) : "l"(sr + 16) : "memory");
                const bool ok = (long long)(ra & rb & rc & rd) < 0;
                if (__all_sync(~0u, ok)) break;
                if (++it > (1 << 22)) __trap();
            }
        }
        float sc[2], mu[2];
        #pragma unroll
        for (int r = 0; r < 2; r++) {
            const unsigned long long u = r ? rc : ra, v = r ? rd : rb;
            const float ma = __uint_as_float((uint32_t)u), mb = __uint_as_float((uint32_t)v);
            float ms = ma + mb;
            ms += __shfl_xor_sync(~0u, ms, 1); ms += __shfl_xor_sync(~0u, ms, 2);
            const float mean = ms * 0.125f;
            float M2 = fabsf(__uint_as_float((uint32_t)(u >> 32))) + fabsf(__uint_as_float((uint32_t)(v >> 32))) + 72.f * ((ma - mean) * (ma - mean) + (mb - mean) * (mb - mean));
            M2 += __shfl_xor_sync(~0u, M2, 1); M2 += __shfl_xor_sync(~0u, M2, 2);
            const float var = M2 * (1.f / D_);
            const float r1 = rsqrtf(var + LN_EPS);
            const float var2 = var * r1 * r1;
            const float r2 = rsqrtf(var2 + LN_EPS);
            sc[r] = 0.5f * (r1 * r2); mu[r] = mean;
        }
        #pragma unroll
        for (int j = 0; j < 9; j++) {
            ndst[j * 256] = pack2((acc[4 * j] - mu[0]) * sc[0], (acc[4 * j + 1] - mu[0]) * sc[0]);
            ndst[j * 256 + 32] = pack2((acc[4 * j + 2] - mu[1]) * sc[1], (acc[4 * j + 3] - mu[1]) * sc[1]);
        }
        if (p == 1 && t < 2) g_ln[mt * 64 + w4 * 16 + gq + 8 * t] = 0ull;
        if (p == 0 && t < 2) {
            asm volatile("" : "+h"(bb0), "+h"(bb1));
            g_rc[mt * 64 + w4 * 16 + gq + 8 * t] = make_float2(1.f / (t ? sc[1] : sc[0]), (t ? mu[1] : mu[0]) + __uint_as_float((uint32_t)(t ? bb1 : bb0) << 16));
        }
    }
}

constexpr int PFT = 4, W2HEAD = 9;
constexpr int K3_STAGES = 6, K3_STAGE = 36864, K3_STAG = 6, K3_PRE = 2, K3_BAR = K3_STAGES * K3_STAGE, K3_SMEM = K3_BAR + 256;
DEVI uint32_t gelu2(float a0, float a1) {
    const float z0 = a0 * fmaf(a0 * a0, 0.2854192650904f, 1.5957691216057f), z1 = a1 * fmaf(a1 * a1, 0.2854192650904f, 1.5957691216057f);
    return pack2(fmaf(a0, tanh_fast(z0), a0), fmaf(a1, tanh_fast(z1), a1));
}
template<int NB> DEVI void k3_store(const float* q, uint32_t* dst) {
    #pragma unroll
    for (int j = 0; j < NB; j++) { dst[j * 256] = gelu2(q[4 * j], q[4 * j + 1]); dst[j * 256 + 32] = gelu2(q[4 * j + 2], q[4 * j + 3]); }
}
DEVI void k3_typeb(uint32_t sm_, int fc_, float bias0, float bias1, const bf16* __restrict__ b1) {
    const uint32_t sm = __shfl_sync(~0u, sm_, 0);
    const int fc = __shfl_sync(~0u, fc_, 0);
    const uint32_t bFull = sm + K3_BAR, bEmpty = bFull + K3_STAGES * 8;
    const int tid = threadIdx.x, lane = tid & 31, warp = __shfl_sync(~0u, tid >> 5, 0);
    const int wg = warp >> 2, w4 = warp & 3, gq = lane >> 2;
    const uint32_t st = sm + wg * 8192;
    const uint64_t da0 = mkdesc(st, 8192, 1024, 1);
    int s = 0, ps = 0; uint32_t ph = 0;
    {
            const int f2 = (fc + 2) * 64 + w4 * 16 + gq;
            const float bias2 = 0.5f * __bfloat162float(b1[f2]), bias3 = 0.5f * __bfloat162float(b1[f2 + 8]);
            float acc[48], acc2[24];
            const uint64_t da2 = mkdesc(sm + 16384, 8192, 1024, 1), db0 = mkdesc(sm + 24576, 128, 1024, 0), db2 = mkdesc(sm + 24576 + wg * 6144, 128, 1024, 0);
            #pragma unroll 1
            for (int i = 0; i < 32 - K3_STAG; i++) {
                mbar_wait(bFull + s * 8, ph);
                const uint32_t so = s * K3_STAGE;
                wg_fence();
                #pragma unroll
                for (int kk = 0; kk < 4; kk++) {
                    wgmma_n96<1, 1>(acc, dadv(da0, so + kk * 2048), dadv(db0, so + kk * 256), (i | kk) != 0);
                    wgmma_n48<1, 1>(acc2, dadv(da2, so + kk * 2048), dadv(db2, so + kk * 256), (i | kk) != 0);
                }
                wg_commit();
                wg_wait<1>();
                if (i > 0 && lane == 0) mbar_arrive(bEmpty + ps * 8);
                ps = s;
                if (++s == K3_STAGES) { s = 0; ph ^= 1; }
            }
            if (wg == 1) {
                wg_wait<0>();
                if (lane == 0) mbar_arrive(bEmpty + ps * 8);
                #pragma unroll
                for (int i = 32 - K3_STAG; i < 32; i++) mbar_wait(bFull + (i % K3_STAGES) * 8, (i / K3_STAGES) & 1);
                bar_sync(3, 256);
            }
            #pragma unroll
            for (int i = 32 - K3_STAG; i < 32; i++) {
                if (wg == 0) mbar_wait(bFull + (i % K3_STAGES) * 8, (i / K3_STAGES) & 1);
                const uint32_t so = (i % K3_STAGES) * K3_STAGE;
                wg_fence();
                #pragma unroll
                for (int kk = 0; kk < 4; kk++) {
                    wgmma_n96<1, 1>(acc, dadv(da0, so + kk * 2048), dadv(db0, so + kk * 256), 1);
                    wgmma_n48<1, 1>(acc2, dadv(da2, so + kk * 2048), dadv(db2, so + kk * 256), 1);
                }
                wg_commit();
                if (i == 32 - K3_STAG && wg == 0) { wg_wait<1>(); if (lane == 0) mbar_arrive(bEmpty + ps * 8); }
            }
            if (wg == 0) bar_arrive(3, 256);
            wg_wait<0>();
            reg_fence<48>(acc); reg_fence<24>(acc2);
            #pragma unroll
            for (int j = 0; j < 48; j++) acc[j] += (j & 2) ? bias1 : bias0;
            #pragma unroll
            for (int j = 0; j < 24; j++) acc2[j] += (j & 2) ? bias3 : bias2;
            k3_store<12>(acc, reinterpret_cast<uint32_t*>(g_u + ((fc + wg) * D_ + 480) * 64) + w4 * 64 + lane);
            k3_store<6>(acc2, reinterpret_cast<uint32_t*>(g_u + ((fc + 2) * D_ + 480 + wg * 48) * 64) + w4 * 64 + lane);
    }
}
__global__ void __cluster_dims__(2, 1, 1) __launch_bounds__(288, 1) k3_mix1(const __grid_constant__ CUtensorMap tmW1a, const __grid_constant__ CUtensorMap tmW1b,
                                                                             const bf16* __restrict__ b1, const bf16* __restrict__ w1, const bf16* __restrict__ w2) {
    extern __shared__ __align__(1024) char smem[];
    const uint32_t sm = smem_u32(smem);
    const uint32_t bFull = sm + K3_BAR, bEmpty = bFull + K3_STAGES * 8;
    const int tid = threadIdx.x, lane = tid & 31, warp = __shfl_sync(~0u, tid >> 5, 0);
    const int cl = blockIdx.x >> 1, rank = blockIdx.x & 1;
    bool tb = false; int fc, d0;
    if (cl < 36) { fc = 2 * cl; d0 = 160 * rank; }
    else if (cl < 60) { const int q = (cl - 36) >> 1, e = (cl - 36) & 1; tb = rank; fc = rank ? 6 * q + 3 * e : 6 * q + 4 * e; d0 = rank ? 480 : 320; }
    else { fc = 6 * (2 * (cl - 60) + rank) + 2; d0 = 320; }
    const CUtensorMap* tm = tb ? &tmW1b : &tmW1a;
    const uint32_t abytes = tb ? 24576 : 16384;
    if (tid == 256) {
        #pragma unroll
        for (int i = 0; i < K3_STAGES; i++) { mbar_init(bFull + i * 8, 1); mbar_init(bEmpty + i * 8, 8); }
        fence_mbar_init();
        #pragma unroll
        for (int i = 0; i < K3_STAGES; i++) mbar_expect(bFull + i * 8, K3_STAGE);
        #pragma unroll
        for (int i = 0; i < K3_PRE; i++) tma3d(sm + i * K3_STAGE, tm, bFull + i * 8, 0, i * 64, fc);
    }
    __syncthreads();
    if (warp == 8) {
        if (tid == 256) {
            pdl_wait();
            pdl_trigger();
            const bf16* hs = g_hnT + d0 * 64;
            #pragma unroll
            for (int i = 0; i < K3_STAGES; i++) {
                bulk_g2s(sm + i * K3_STAGE + abytes, hs + i * (D_ * 64), K3_STAGE - abytes, bFull + i * 8);
                if (i >= K3_PRE) tma3d(sm + i * K3_STAGE, tm, bFull + i * 8, 0, i * 64, fc);
            }
            int s = 0; uint32_t ph = 0;
            #pragma unroll 1
            for (int i = K3_STAGES; i < 32; i++) {
                mbar_wait(bEmpty + s * 8, ph);
                mbar_expect(bFull + s * 8, K3_STAGE);
                tma3d(sm + s * K3_STAGE, tm, bFull + s * 8, 0, i * 64, fc);
                bulk_g2s(sm + s * K3_STAGE + abytes, hs + i * (D_ * 64), K3_STAGE - abytes, bFull + s * 8);
                if (i == 18 && blockIdx.x < 128) l2_prefetch(w1 + (size_t)(2048 - 64 * PFT) * F_ + blockIdx.x * (2304 * PFT), 4608 * PFT);
                if (++s == K3_STAGES) { s = 0; ph ^= 1; }
            }
            if (blockIdx.x < 128) l2_prefetch(w2 + (size_t)(blockIdx.x & 1) * (2304 * S_) + (blockIdx.x >> 1) * (W2HEAD * 2048), W2HEAD * 4096);
        }
    } else {
        const int wg = warp >> 2, w4 = warp & 3, gq = lane >> 2;
        const int f0 = (fc + wg) * 64 + w4 * 16 + gq;
        const float bias0 = 0.5f * __bfloat162float(b1[f0]), bias1 = 0.5f * __bfloat162float(b1[f0 + 8]);
        uint32_t* dst = reinterpret_cast<uint32_t*>(g_u + ((fc + wg) * D_ + d0) * 64) + w4 * 64 + lane;
        const uint32_t st = sm + wg * 8192;
        const uint64_t da0 = mkdesc(st, 8192, 1024, 1);
        int s = 0, ps = 0; uint32_t ph = 0;
        if (!tb) {
            float acc[80];
            #pragma unroll
            for (int j = 0; j < 80; j++) acc[j] = (j & 2) ? bias1 : bias0;
            reg_fence<80>(acc);
            const uint64_t db0 = mkdesc(sm + 16384, 128, 1024, 0);
            #pragma unroll 1
            for (int i = 0; i < 32 - K3_STAG; i++) {
                mbar_wait(bFull + s * 8, ph);
                const uint64_t da = dadv(da0, s * K3_STAGE), db = dadv(db0, s * K3_STAGE);
                wg_fence();
                #pragma unroll
                for (int kk = 0; kk < 4; kk++)
                    wgmma_n160<1, 1>(acc, dadv(da, kk * 2048), dadv(db, kk * 256), 1);
                wg_commit();
                wg_wait<1>();
                if (i > 0 && lane == 0) mbar_arrive(bEmpty + ps * 8);
                ps = s;
                if (++s == K3_STAGES) { s = 0; ph ^= 1; }
            }
            if (wg == 1) {
                wg_wait<0>();
                if (lane == 0) mbar_arrive(bEmpty + ps * 8);
                #pragma unroll
                for (int i = 32 - K3_STAG; i < 32; i++) mbar_wait(bFull + (i % K3_STAGES) * 8, (i / K3_STAGES) & 1);
                bar_sync(3, 256);
            }
            #pragma unroll
            for (int i = 32 - K3_STAG; i < 32; i++) {
                if (wg == 0) mbar_wait(bFull + (i % K3_STAGES) * 8, (i / K3_STAGES) & 1);
                wg_fence();
                #pragma unroll
                for (int kk = 0; kk < 4; kk++)
                    wgmma_n160<1, 1>(acc, dadv(da0, (i % K3_STAGES) * K3_STAGE + kk * 2048), dadv(db0, (i % K3_STAGES) * K3_STAGE + kk * 256), 1);
                wg_commit();
                if (i == 32 - K3_STAG && wg == 0) { wg_wait<1>(); if (lane == 0) mbar_arrive(bEmpty + ps * 8); }
            }
            if (wg == 0) bar_arrive(3, 256);
            wg_wait<0>();
            reg_fence<80>(acc);
            k3_store<20>(acc, dst);
        } else {
            k3_typeb(sm, fc, bias0, bias1, b1);
        }
    }
}

constexpr int SLOTC = 700, SLOTP = 578, K4A0 = 1, K4_PD = 4;
constexpr int K4_STAGES = 5, K4_STAGE = 8192 + 36864, K4_STAG = 3, K4_BAR = K4_STAGES * K4_STAGE, K4_SMEM = K4_BAR + 256;
constexpr int K4_XS = (36 - K4_STAG - 1) % K4_STAGES;
__global__ void __cluster_dims__(2, 1, 1) __launch_bounds__(288, 1) k4_mix2(const __grid_constant__ CUtensorMap tmW2, const __grid_constant__ CUtensorMap tmOut) {
    extern __shared__ __align__(1024) char smem[];
    const uint32_t sm = smem_u32(smem);
    const uint32_t bFull = sm + K4_BAR, bEmpty = bFull + K4_STAGES * 8, bP = bEmpty + K4_STAGES * 8, bRdy = bP + 16, bH = bRdy + 8;
    const int tid = threadIdx.x, lane = tid & 31, warp = __shfl_sync(~0u, tid >> 5, 0);
    const int ks = blockIdx.x & 1, tm = (blockIdx.x >> 1) & 31, tn = blockIdx.x >> 6;
    const int k0 = ks * 36;
    if (tid == 256) {
        #pragma unroll
        for (int i = 0; i < K4_STAGES; i++) { mbar_init(bFull + i * 8, 1); mbar_init(bEmpty + i * 8, 8); }
        mbar_init(bP, 1); mbar_init(bP + 8, 1); mbar_init(bRdy, 8); mbar_init(bH, 1);
        fence_mbar_init();
        #pragma unroll
        for (int i = 0; i < K4A0; i++) tma3d(sm + i * K4_STAGE, &tmW2, bFull + i * 8, 0, (k0 + i) * 64, tm);
    }
    __syncthreads();
    cluster_arrive_relaxed();
    if (tid == 0) {
        #pragma unroll
        for (int i = K4A0; i < 2; i++) tma3d(sm + i * K4_STAGE, &tmW2, bFull + i * 8, 0, (k0 + i) * 64, tm);
    }
    if (tid == 32) {
        #pragma unroll
        for (int i = 0; i < K4_STAGES; i++) mbar_expect(bFull + i * 8, K4_STAGE);
    }
    if (tid == 128) { mbar_expect(bP, 9216); mbar_expect(bP + 8, 9216); prefetch_tm(&tmOut); }
    __syncwarp();
    if (warp == 8) {
        if (lane == 0) {
            pdl_wait();
            const bf16* us = g_u + ((size_t)k0 * D_ + tn * 288) * 64;
            uint32_t slot = clock() + SLOTC;
            #pragma unroll
            for (int i = 0; i < K4_STAGES; i++) {
                if (i >= 2) { tma3d(sm + i * K4_STAGE, &tmW2, bFull + i * 8, 0, (k0 + i) * 64, tm); while ((int)(clock() - slot) < 0) {} slot += SLOTP; }
                bulk_g2s(sm + i * K4_STAGE + 8192, us + (size_t)i * (D_ * 64), 36864, bFull + i * 8);
            }
            int s = 0; uint32_t ph = 0;
            #pragma unroll 1
            for (int i = K4_STAGES; i < 36; i++) {
                mbar_wait(bEmpty + s * 8, ph);
                mbar_expect(bFull + s * 8, K4_STAGE);
                tma3d(sm + s * K4_STAGE, &tmW2, bFull + s * 8, 0, (k0 + i) * 64, tm);
                if (i + K4_PD < 36 && ((i ^ tn) & 1)) tma3d_prefetch(&tmW2, 0, (k0 + i + K4_PD) * 64, tm);
                if (i < 32) { while ((int)(clock() - slot) < 0) {} slot += SLOTP; }
                bulk_g2s(sm + s * K4_STAGE + 8192, us + (size_t)i * (D_ * 64), 36864, bFull + s * 8);
                if (++s == K4_STAGES) { s = 0; ph ^= 1; }
            }
            static_assert(K4_STAG <= 3, "stage of step 31 is free");
            mbar_wait(bEmpty + s * 8, ph);
            mbar_expect(bH, 18432);
            bulk_g2s(sm + (31 % K4_STAGES) * K4_STAGE, g_hnT + (tm * D_ + tn * 288 + ks * 144) * 64, 18432, bH);
        }
        __syncwarp();
        cluster_wait();
        #pragma unroll
        for (int hh = 0; hh < 2; hh++) {
            bar_sync(4 + hh, 160);
            if (lane == 0) {
                tma2d_store(&tmOut, sm + K4_XS * K4_STAGE + 24576 + hh * 9216, tn * 288 + ks * 144 + hh * 72, tm * 64);
                bulk_commit();
            }
            __syncwarp();
        }
        if (lane == 0) { bulk_wait_read(); }
    } else {
        const int wg = warp >> 2, w4 = warp & 3, tw = tid & 127;
        const bool keep = wg == ks;
        float acc[72];
        const uint64_t da0 = mkdesc(sm, 8192, 1024, 1), db0 = mkdesc(sm + 8192 + wg * 18432, 128, 1024, 0);
        const uint32_t rdy = mapa(bRdy, ks ^ 1);
        cluster_wait();
        int s = 0, ps = 0; uint32_t ph = 0;
        #pragma unroll 1
        for (int i = 0; i < 36 - K4_STAG; i++) {
            mbar_wait(bFull + s * 8, ph);
            const uint64_t da = dadv(da0, s * K4_STAGE), db = dadv(db0, s * K4_STAGE);
            wg_fence();
            #pragma unroll
            for (int kk = 0; kk < 4; kk++)
                wgmma_n144<1, 1>(acc, dadv(da, kk * 2048), dadv(db, kk * 256), (i | kk) != 0);
            wg_commit();
            wg_wait<1>();
            if (i > 0 && lane == 0) mbar_arrive(bEmpty + ps * 8);
            ps = s;
            if (++s == K4_STAGES) { s = 0; ph ^= 1; }
        }
        const uint32_t xa = sm + K4_XS * K4_STAGE + tw * 16;
        const uint2 rc0 = ldg64(g_rc + tm * 64 + w4 * 16 + (lane >> 2)), rc1 = ldg64(g_rc + tm * 64 + w4 * 16 + (lane >> 2) + 8);
        float res[36];
        const uint32_t ya = sm + (31 % K4_STAGES) * K4_STAGE + 20480 + tw * 16;
        auto residual = [&](int hh) {
            uint32_t hp[20];
            mbar_wait(bH, 0);
            const uint32_t ha = sm + (31 % K4_STAGES) * K4_STAGE + hh * 9216 + (lane >> 4) * 1024 + w4 * 256 + (lane & 15) * 16;
            #pragma unroll
            for (int j = 0; j < 5; j++)
                asm volatile("ldmatrix.sync.aligned.m8n8.x4.shared.b16 {%0,%1,%2,%3}, [%4];" : "=r"(hp[4 * j]), "=r"(hp[4 * j + 1]), "=r"(hp[4 * j + 2]), "=r"(hp[4 * j + 3]) : "r"(ha + j * 2048) : "memory");
            #pragma unroll
            for (int j = 0; j < 18; j++) {
                const float is = __uint_as_float((j & 1) ? rc1.x : rc0.x), of = __uint_as_float((j & 1) ? rc1.y : rc0.y);
                res[2 * j] = fmaf(bf_lo(hp[j]), is, of); res[2 * j + 1] = fmaf(bf_hi(hp[j]), is, of);
            }
            reg_fence<36>(res);
        };
        auto partial = [&](int hh) {
            mbar_wait(bP + hh * 8, 0);
            uint32_t o[18];
            #pragma unroll
            for (int j = 0; j < 4; j++) { const uint4 v = lds128(xa + hh * 10240 + j * 2048); o[4 * j] = v.x; o[4 * j + 1] = v.y; o[4 * j + 2] = v.z; o[4 * j + 3] = v.w; }
            { const uint2 v = lds64(xa + hh * 10240 + 8192); o[16] = v.x; o[17] = v.y; }
            #pragma unroll
            for (int j = 0; j < 18; j++) { res[2 * j] += bf_lo(o[j]); res[2 * j + 1] += bf_hi(o[j]); }
        };
        if (!keep) {
            #pragma unroll
            for (int i = 36 - K4_STAG; i < 36; i++) {
                mbar_wait(bFull + (i % K4_STAGES) * 8, (i / K4_STAGES) & 1);
                wg_fence();
                #pragma unroll
                for (int kk = 0; kk < 4; kk++)
                    wgmma_n144<1, 1>(acc, dadv(da0, (i % K4_STAGES) * K4_STAGE + kk * 2048), dadv(db0, (i % K4_STAGES) * K4_STAGE + kk * 256), 1);
                wg_commit();
                if (i == 36 - K4_STAG) { wg_wait<1>(); if (lane == 0) mbar_arrive_remote(rdy); }
            }
            bar_arrive(3, 256);
            mbar_wait(bRdy, 0);
            wg_wait<0>();
            reg_fence<72>(acc);
            const uint32_t rd = mapa(xa, ks ^ 1), rb = mapa(bP, ks ^ 1);
            #pragma unroll
            for (int hh = 0; hh < 2; hh++) {
                const float* q = acc + hh * 36;
                #pragma unroll
                for (int j = 0; j < 4; j++)
                    asm volatile("st.async.shared::cluster.mbarrier::complete_tx::bytes.v4.b32 [%0], {%1,%2,%3,%4}, [%5];"
                                 :: "r"(rd + hh * 10240 + j * 2048), "r"(pack2(q[8 * j], q[8 * j + 1])), "r"(pack2(q[8 * j + 2], q[8 * j + 3])),
                                    "r"(pack2(q[8 * j + 4], q[8 * j + 5])), "r"(pack2(q[8 * j + 6], q[8 * j + 7])), "r"(rb + hh * 8) : "memory");
                asm volatile("st.async.shared::cluster.mbarrier::complete_tx::bytes.v2.b32 [%0], {%1,%2}, [%3];"
                             :: "r"(rd + hh * 10240 + 8192), "r"(pack2(q[32], q[33])), "r"(pack2(q[34], q[35])), "r"(rb + hh * 8) : "memory");
            }
            residual(1);
            partial(1);
            reg_fence<36>(res);
            bar_sync(1, 256);
            #pragma unroll
            for (int j = 0; j < 9; j++) {
                const uint4 v = lds128(ya + j * 2048);
                res[4 * j] += __uint_as_float(v.x); res[4 * j + 1] += __uint_as_float(v.y); res[4 * j + 2] += __uint_as_float(v.z); res[4 * j + 3] += __uint_as_float(v.w);
            }
        } else {
            wg_wait<0>();
            if (lane == 0) mbar_arrive_remote(rdy);
            #pragma unroll
            for (int i = 36 - K4_STAG; i < 36; i++) mbar_wait(bFull + (i % K4_STAGES) * 8, (i / K4_STAGES) & 1);
            bar_sync(3, 256);
            wg_fence();
            #pragma unroll
            for (int i = 36 - K4_STAG; i < 36; i++)
                #pragma unroll
                for (int kk = 0; kk < 4; kk++)
                    wgmma_n144<1, 1>(acc, dadv(da0, (i % K4_STAGES) * K4_STAGE + kk * 2048), dadv(db0, (i % K4_STAGES) * K4_STAGE + kk * 256), 1);
            wg_commit();
            residual(0);
            wg_wait<0>();
            reg_fence<72>(acc);
            #pragma unroll
            for (int j = 0; j < 9; j++)
                sts128(ya + j * 2048, __float_as_uint(acc[36 + 4 * j]), __float_as_uint(acc[37 + 4 * j]), __float_as_uint(acc[38 + 4 * j]), __float_as_uint(acc[39 + 4 * j]));
            bar_arrive(1, 256);
            #pragma unroll
            for (int j = 0; j < 36; j++) res[j] += acc[j];
            partial(0);
        }
        const int hh = keep ? 0 : 1;
        uint32_t o[18];
        #pragma unroll
        for (int j = 0; j < 18; j++) o[j] = pack2(res[2 * j], res[2 * j + 1]);
        const uint32_t ad = sm + K4_XS * K4_STAGE + 24576 + hh * 9216 + (w4 * 16 + ((lane >> 3) & 1) * 8 + (lane & 7)) * 144;
        #pragma unroll
        for (int j = 0; j < 4; j++) stsm4(ad + (lane >> 4) * 16 + j * 32, o[4 * j], o[4 * j + 1], o[4 * j + 2], o[4 * j + 3]);
        stsm2(ad + 128, o[16], o[17]);
        fence_async_smem();
        bar_arrive(4 + hh, 160);
    }
}

typedef CUresult (*EncFn)(CUtensorMap*, CUtensorMapDataType, cuuint32_t, void*, const cuuint64_t*, const cuuint64_t*, const cuuint32_t*,
                          const cuuint32_t*, CUtensorMapInterleave, CUtensorMapSwizzle, CUtensorMapL2promotion, CUtensorMapFloatOOBfill);

template <typename... KArgs, typename... Args>
static void launch(void (*kern)(KArgs...), dim3 grid, int block, int smem, bool pdl, Args... args) {
    cudaLaunchConfig_t cfg = {};
    cfg.gridDim = grid; cfg.blockDim = dim3(block); cfg.dynamicSmemBytes = smem; cfg.stream = cudaStreamPerThread;
    cudaLaunchAttribute at[1];
    at[0].id = cudaLaunchAttributeProgrammaticStreamSerialization; at[0].val.programmaticStreamSerializationAllowed = 1;
    cfg.attrs = at; cfg.numAttrs = pdl ? 1 : 0;
    cudaLaunchKernelEx(&cfg, kern, args...);
}

extern "C" void kernel_launch(void* const* d_in, const int* in_sizes, int n_in, void* d_out, int out_size) {
    const bf16* x = (const bf16*)d_in[0];
    const bf16* wqkv = (const bf16*)d_in[1];
    const bf16* wphi = (const bf16*)d_in[2];
    const bf16* wo = (const bf16*)d_in[3];
    const bf16* w1 = (const bf16*)d_in[5];
    const bf16* b1 = (const bf16*)d_in[6];
    const bf16* w2 = (const bf16*)d_in[7];
    const bf16* b2 = (const bf16*)d_in[8];
    static EncFn enc = nullptr;
    if (!enc) {
        void* fn = nullptr; cudaDriverEntryPointQueryResult qr;
        cudaGetDriverEntryPoint("cuTensorMapEncodeTiled", &fn, cudaEnableDefault, &qr);
        enc = (EncFn)fn;
        cudaFuncSetAttribute(ka_front, cudaFuncAttributeMaxDynamicSharedMemorySize, KA_SMEM);
        cudaFuncSetAttribute(k2_attn, cudaFuncAttributeMaxDynamicSharedMemorySize, K2_SMEM);
        cudaFuncSetAttribute(k3_mix1, cudaFuncAttributeMaxDynamicSharedMemorySize, K3_SMEM);
        cudaFuncSetAttribute(k4_mix2, cudaFuncAttributeMaxDynamicSharedMemorySize, K4_SMEM);
    }
    CUtensorMap tmW1, tmW1b, tmW2, tmOut, tmX, tmXA;
    const cuuint32_t es[3] = {1, 1, 1};
    {
        cuuint64_t dims[3] = {64, (cuuint64_t)S_, (cuuint64_t)(F_ / 64)}; cuuint64_t st[2] = {(cuuint64_t)F_ * 2, 128}; cuuint32_t box[3] = {64, 64, 2};
        enc(&tmW1, CU_TENSOR_MAP_DATA_TYPE_BFLOAT16, 3, (void*)w1, dims, st, box, es, CU_TENSOR_MAP_INTERLEAVE_NONE, CU_TENSOR_MAP_SWIZZLE_128B, CU_TENSOR_MAP_L2_PROMOTION_L2_128B, CU_TENSOR_MAP_FLOAT_OOB_FILL_NONE);
        box[2] = 3;
        enc(&tmW1b, CU_TENSOR_MAP_DATA_TYPE_BFLOAT16, 3, (void*)w1, dims, st, box, es, CU_TENSOR_MAP_INTERLEAVE_NONE, CU_TENSOR_MAP_SWIZZLE_128B, CU_TENSOR_MAP_L2_PROMOTION_L2_128B, CU_TENSOR_MAP_FLOAT_OOB_FILL_NONE);
    }
    {
        cuuint64_t dims[3] = {64, (cuuint64_t)F_, (cuuint64_t)(S_ / 64)}; cuuint64_t st[2] = {(cuuint64_t)S_ * 2, 128}; cuuint32_t box[3] = {64, 64, 1};
        enc(&tmW2, CU_TENSOR_MAP_DATA_TYPE_BFLOAT16, 3, (void*)w2, dims, st, box, es, CU_TENSOR_MAP_INTERLEAVE_NONE, CU_TENSOR_MAP_SWIZZLE_128B, CU_TENSOR_MAP_L2_PROMOTION_L2_128B, CU_TENSOR_MAP_FLOAT_OOB_FILL_NONE);
    }
    {
        cuuint64_t dims[2] = {(cuuint64_t)D_, (cuuint64_t)S_}; cuuint64_t st[1] = {(cuuint64_t)D_ * 2}; cuuint32_t box[2] = {72, 64};
        enc(&tmOut, CU_TENSOR_MAP_DATA_TYPE_BFLOAT16, 2, d_out, dims, st, box, es, CU_TENSOR_MAP_INTERLEAVE_NONE, CU_TENSOR_MAP_SWIZZLE_NONE, CU_TENSOR_MAP_L2_PROMOTION_NONE, CU_TENSOR_MAP_FLOAT_OOB_FILL_NONE);
        enc(&tmX, CU_TENSOR_MAP_DATA_TYPE_BFLOAT16, 2, (void*)x, dims, st, box, es, CU_TENSOR_MAP_INTERLEAVE_NONE, CU_TENSOR_MAP_SWIZZLE_NONE, CU_TENSOR_MAP_L2_PROMOTION_NONE, CU_TENSOR_MAP_FLOAT_OOB_FILL_NONE);
    }
    {
        cuuint64_t dims[3] = {64, (cuuint64_t)S_, 9}; cuuint64_t st[2] = {(cuuint64_t)D_ * 2, 128}; cuuint32_t box[3] = {64, 128, 1};
        enc(&tmXA, CU_TENSOR_MAP_DATA_TYPE_BFLOAT16, 3, (void*)x, dims, st, box, es, CU_TENSOR_MAP_INTERLEAVE_NONE, CU_TENSOR_MAP_SWIZZLE_128B, CU_TENSOR_MAP_L2_PROMOTION_L2_128B, CU_TENSOR_MAP_FLOAT_OOB_FILL_NONE);
    }
    launch(k0_prep, dim3(9, 8, 4), 256, 0, false, x, wqkv, wphi);
    launch(ka_front, 132, 640, KA_SMEM, true, tmXA, x, wo, w1, b1);
    launch(k2_attn, 128, 256, K2_SMEM, true, tmX, b2);
    launch(k3_mix1, 132, 288, K3_SMEM, true, tmW1, tmW1b, b1, w1, w2);
    launch(k4_mix2, 128, 288, K4_SMEM, true, tmW2, tmOut);
}
```

```cpp
#include <cuda_runtime.h>
#include <cuda.h>
#include <cuda_bf16.h>
#include <stdint.h>

typedef __nv_bfloat16 bf16;
#define DEVI __device__ __forceinline__

constexpr int S_ = 2048, D_ = 576, F_ = 4608;
constexpr float LN_EPS = 1e-5f;
constexpr float LOG2E = 1.4426950408889634f;

__device__ __align__(1024) bf16 g_o[S_ * D_];
__device__ __align__(1024) bf16 g_wqkv[8 * 27 * 72 * 64];
__device__ __align__(16) float g_cs[8 * 18 * 216];
__device__ __align__(1024) bf16 g_wo[8 * 72 * 72 * 8];
constexpr int KV_H = 960;
__device__ __align__(1024) float g_kv[32 * KV_H];
__device__ __align__(1024) unsigned long long g_stats[S_ * 8];
__device__ __align__(16) unsigned long long g_ln[S_];
__device__ __align__(16) float2 g_rc[S_];
__device__ __align__(1024) bf16 g_hnT[D_ * S_];
__device__ __align__(1024) bf16 g_u[D_ * F_];
constexpr int CNT_S = 64;
__device__ __align__(256) unsigned int g_cnt[8 * CNT_S];

DEVI uint32_t smem_u32(const void* p) { return (uint32_t)__cvta_generic_to_shared(p); }
DEVI void mbar_init(uint32_t bar, int cnt) { asm volatile("mbarrier.init.shared::cta.b64 [%0], %1;" :: "r"(bar), "r"(cnt) : "memory"); }
DEVI void mbar_expect(uint32_t bar, uint32_t bytes) { asm volatile("mbarrier.arrive.expect_tx.shared::cta.b64 _, [%0], %1;" :: "r"(bar), "r"(bytes) : "memory"); }
DEVI void mbar_wait(uint32_t bar, uint32_t parity) {
    asm volatile("{\n.reg .pred p;\n.reg .u32 it;\n"
                 "mbarrier.try_wait.parity.shared::cta.b64 p, [%0], %1;\n@p bra MW_DONE;\n"
                 "mov.u32 it, 0;\n"
                 "MW_LOOP:\nmbarrier.try_wait.parity.shared::cta.b64 p, [%0], %1;\n@p bra MW_DONE;\n"
                 "add.u32 it, it, 1;\nsetp.lt.u32 p, it, 4194304;\n@p bra MW_LOOP;\ntrap;\n"
                 "MW_DONE:\n}" :: "r"(bar), "r"(parity) : "memory");
}
DEVI void mbar_arrive(uint32_t bar) { asm volatile("mbarrier.arrive.shared::cta.b64 _, [%0];" :: "r"(bar) : "memory"); }
DEVI uint32_t mapa(uint32_t addr, uint32_t cta) { uint32_t r; asm volatile("mapa.shared::cluster.u32 %0, %1, %2;" : "=r"(r) : "r"(addr), "r"(cta)); return r; }
DEVI void mbar_arrive_remote(uint32_t raddr) { asm volatile("mbarrier.arrive.shared::cluster.b64 _, [%0];" :: "r"(raddr) : "memory"); }
DEVI void fence_mbar_init() { asm volatile("fence.mbarrier_init.release.cluster;" ::: "memory"); }
DEVI void fence_async_smem() { asm volatile("fence.proxy.async.shared::cta;" ::: "memory"); }
DEVI void cluster_arrive_relaxed() { asm volatile("barrier.cluster.arrive.relaxed.aligned;" ::: "memory"); }
DEVI void cluster_wait() { asm volatile("barrier.cluster.wait.aligned;" ::: "memory"); }
DEVI void bar_sync(int id, int n) { asm volatile("bar.sync %0, %1;" :: "r"(id), "r"(n) : "memory"); }
DEVI void bar_arrive(int id, int n) { asm volatile("bar.arrive %0, %1;" :: "r"(id), "r"(n) : "memory"); }
DEVI void pdl_wait() { asm volatile("griddepcontrol.wait;" ::: "memory"); }
DEVI void pdl_trigger() { asm volatile("griddepcontrol.launch_dependents;" ::: "memory"); }
DEVI void bulk_g2s(uint32_t dst, const void* src, uint32_t bytes, uint32_t bar) {
    asm volatile("cp.async.bulk.shared::cluster.global.mbarrier::complete_tx::bytes [%0], [%1], %2, [%3];" :: "r"(dst), "l"(src), "r"(bytes), "r"(bar) : "memory");
}
DEVI void bulk_s2g(void* dst, uint32_t src, uint32_t bytes) {
    asm volatile("cp.async.bulk.global.shared::cta.bulk_group [%0], [%1], %2;" :: "l"(dst), "r"(src), "r"(bytes) : "memory");
}
DEVI void l2_prefetch(const void* p, uint32_t bytes) { asm volatile("cp.async.bulk.prefetch.L2.global [%0], %1;" :: "l"(p), "r"(bytes) : "memory"); }
DEVI void bulk_commit() { asm volatile("cp.async.bulk.commit_group;" ::: "memory"); }
DEVI void bulk_wait_read() { asm volatile("cp.async.bulk.wait_group.read 0;" ::: "memory"); }
DEVI void tma2d(uint32_t dst, const CUtensorMap* tm, uint32_t bar, int c0, int c1) {
    asm volatile("cp.async.bulk.tensor.2d.shared::cluster.global.mbarrier::complete_tx::bytes [%0], [%1, {%3, %4}], [%2];" :: "r"(dst), "l"(tm), "r"(bar), "r"(c0), "r"(c1) : "memory");
}
DEVI void tma3d(uint32_t dst, const CUtensorMap* tm, uint32_t bar, int c0, int c1, int c2) {
    asm volatile("cp.async.bulk.tensor.3d.shared::cluster.global.mbarrier::complete_tx::bytes [%0], [%1, {%3, %4, %5}], [%2];" :: "r"(dst), "l"(tm), "r"(bar), "r"(c0), "r"(c1), "r"(c2) : "memory");
}
DEVI void tma3d_prefetch(const CUtensorMap* tm, int c0, int c1, int c2) {
    asm volatile("cp.async.bulk.prefetch.tensor.3d.L2.global [%0, {%1, %2, %3}];" :: "l"(tm), "r"(c0), "r"(c1), "r"(c2) : "memory");
}
DEVI void tma2d_store(const CUtensorMap* tm, uint32_t src, int c0, int c1) {
    asm volatile("cp.async.bulk.tensor.2d.global.shared::cta.bulk_group [%0, {%2, %3}], [%1];" :: "l"(tm), "r"(src), "r"(c0), "r"(c1) : "memory");
}
DEVI void prefetch_tm(const CUtensorMap* tm) { asm volatile("prefetch.tensormap [%0];" :: "l"(tm) : "memory"); }
DEVI uint64_t mkdesc(uint32_t addr, uint32_t lbo, uint32_t sbo, uint64_t swz) {
    return (uint64_t)((addr & 0x3FFFF) >> 4) | ((uint64_t)(lbo >> 4) << 16) | ((uint64_t)(sbo >> 4) << 32) | (swz << 62);
}
DEVI uint64_t dadv(uint64_t d, uint32_t bytes) { return (d & 0xffffffff00000000ull) | (uint64_t)((uint32_t)d + (bytes >> 4)); }
DEVI void wg_fence() { asm volatile("wgmma.fence.sync.aligned;" ::: "memory"); }
DEVI void wg_commit() { asm volatile("wgmma.commit_group.sync.aligned;" ::: "memory"); }
template<int N> DEVI void wg_wait() { asm volatile("wgmma.wait_group.sync.aligned %0;" :: "n"(N) : "memory"); }
template<int N> DEVI void reg_fence(float* d) {
    #pragma unroll
    for (int i = 0; i < N; i++) asm volatile("" : "+f"(d[i]) :: "memory");
}
DEVI uint32_t pack2(float lo, float hi) { uint32_t r; asm("cvt.rn.bf16x2.f32 %0, %1, %2;" : "=r"(r) : "f"(hi), "f"(lo)); return r; }
DEVI float bf_lo(uint32_t v) { return __uint_as_float(v << 16); }
DEVI float bf_hi(uint32_t v) { return __uint_as_float(v & 0xffff0000u); }
DEVI float ex2(float x) { float r; asm("ex2.approx.ftz.f32 %0, %1;" : "=f"(r) : "f"(x)); return r; }
DEVI float rcp(float x) { float r; asm("rcp.approx.ftz.f32 %0, %1;" : "=f"(r) : "f"(x)); return r; }
DEVI float rcp_full(float x) { float r; asm("rcp.approx.f32 %0, %1;" : "=f"(r) : "f"(x)); return r; }
DEVI float tanh_fast(float x) { float r; asm("tanh.approx.f32 %0, %1;" : "=f"(r) : "f"(x)); return r; }
DEVI void mma16816(float* c, uint32_t a0, uint32_t a1, uint32_t a2, uint32_t a3, uint32_t b0, uint32_t b1) {
    asm("mma.sync.aligned.m16n8k16.row.col.f32.bf16.bf16.f32 {%0,%1,%2,%3}, {%4,%5,%6,%7}, {%8,%9}, {%0,%1,%2,%3};"
        : "+f"(c[0]), "+f"(c[1]), "+f"(c[2]), "+f"(c[3]) : "r"(a0), "r"(a1), "r"(a2), "r"(a3), "r"(b0), "r"(b1));
}
DEVI void mma1688(float* c, uint32_t a0, uint32_t a1, uint32_t b0) {
    asm("mma.sync.aligned.m16n8k8.row.col.f32.bf16.bf16.f32 {%0,%1,%2,%3}, {%4,%5}, {%6}, {%0,%1,%2,%3};"
        : "+f"(c[0]), "+f"(c[1]), "+f"(c[2]), "+f"(c[3]) : "r"(a0), "r"(a1), "r"(b0));
}
DEVI void ldsm4t(uint32_t addr, uint32_t& r0, uint32_t& r1, uint32_t& r2, uint32_t& r3) {
    asm volatile("ldmatrix.sync.aligned.m8n8.x4.trans.shared.b16 {%0,%1,%2,%3}, [%4];" : "=r"(r0), "=r"(r1), "=r"(r2), "=r"(r3) : "r"(addr) : "memory");
}
DEVI void stsm4(uint32_t addr, uint32_t r0, uint32_t r1, uint32_t r2, uint32_t r3) {
    asm volatile("stmatrix.sync.aligned.m8n8.x4.shared.b16 [%0], {%1,%2,%3,%4};" :: "r"(addr), "r"(r0), "r"(r1), "r"(r2), "r"(r3) : "memory");
}
DEVI void stsm2(uint32_t addr, uint32_t r0, uint32_t r1) {
    asm volatile("stmatrix.sync.aligned.m8n8.x2.shared.b16 [%0], {%1,%2};" :: "r"(addr), "r"(r0), "r"(r1) : "memory");
}
DEVI void sts128(uint32_t addr, uint32_t r0, uint32_t r1, uint32_t r2, uint32_t r3) {
    asm volatile("st.shared.v4.b32 [%0], {%1,%2,%3,%4};" :: "r"(addr), "r"(r0), "r"(r1), "r"(r2), "r"(r3) : "memory");
}
DEVI void sts32(uint32_t addr, uint32_t r0) { asm volatile("st.shared.b32 [%0], %1;" :: "r"(addr), "r"(r0) : "memory"); }
DEVI uint32_t lds32(uint32_t addr) { uint32_t r; asm volatile("ld.shared.b32 %0, [%1];" : "=r"(r) : "r"(addr) : "memory"); return r; }
DEVI void wgmma_rs_n80(float* d, uint32_t a0, uint32_t a1, uint32_t a2, uint32_t a3, uint64_t db, int sd) {
  asm volatile("{\n.reg .pred p;\nsetp.ne.b32 p, %45, 0;\n"
    "wgmma.mma_async.sync.aligned.m64n80k16.f32.bf16.bf16 {%0, %1, %2, %3, %4, %5, %6, %7, %8, %9, %10, %11, %12, %13, %14, %15, %16, %17, %18, %19, %20, %21, %22, %23, %24, %25, %26, %27, %28, %29, %30, %31, %32, %33, %34, %35, %36, %37, %38, %39}, {%40, %41, %42, %43}, %44, p, 1, 1, 0;\n}\n"
    : "+f"(d[0]), "+f"(d[1]), "+f"(d[2]), "+f"(d[3]), "+f"(d[4]), "+f"(d[5]), "+f"(d[6]), "+f"(d[7]), "+f"(d[8]), "+f"(d[9]), "+f"(d[10]), "+f"(d[11]), "+f"(d[12]), "+f"(d[13]), "+f"(d[14]), "+f"(d[15]), "+f"(d[16]), "+f"(d[17]), "+f"(d[18]), "+f"(d[19]), "+f"(d[20]), "+f"(d[21]), "+f"(d[22]), "+f"(d[23]), "+f"(d[24]), "+f"(d[25]), "+f"(d[26]), "+f"(d[27]), "+f"(d[28]), "+f"(d[29]), "+f"(d[30]), "+f"(d[31]), "+f"(d[32]), "+f"(d[33]), "+f"(d[34]), "+f"(d[35]), "+f"(d[36]), "+f"(d[37]), "+f"(d[38]), "+f"(d[39]) : "r"(a0), "r"(a1), "r"(a2), "r"(a3), "l"(db), "r"(sd));
}
template<int TA, int TB> DEVI void wgmma_n40(float* d, uint64_t da, uint64_t db, int sd) {
  asm volatile("{\n.reg .pred p;\nsetp.ne.b32 p, %22, 0;\n"
    "wgmma.mma_async.sync.aligned.m64n40k16.f32.bf16.bf16 {%0, %1, %2, %3, %4, %5, %6, %7, %8, %9, %10, %11, %12, %13, %14, %15, %16, %17, %18, %19}, %20, %21, p, 1, 1, %23, %24;\n}\n"
    : "+f"(d[0]), "+f"(d[1]), "+f"(d[2]), "+f"(d[3]), "+f"(d[4]), "+f"(d[5]), "+f"(d[6]), "+f"(d[7]), "+f"(d[8]), "+f"(d[9]), "+f"(d[10]), "+f"(d[11]), "+f"(d[12]), "+f"(d[13]), "+f"(d[14]), "+f"(d[15]), "+f"(d[16]), "+f"(d[17]), "+f"(d[18]), "+f"(d[19]) : "l"(da), "l"(db), "r"(sd), "n"(TA), "n"(TB));
}
template<int TA, int TB> DEVI void wgmma_n48(float* d, uint64_t da, uint64_t db, int sd) {
  asm volatile("{\n.reg .pred p;\nsetp.ne.b32 p, %26, 0;\n"
    "wgmma.mma_async.sync.aligned.m64n48k16.f32.bf16.bf16 {%0, %1, %2, %3, %4, %5, %6, %7, %8, %9, %10, %11, %12, %13, %14, %15, %16, %17, %18, %19, %20, %21, %22, %23}, %24, %25, p, 1, 1, %27, %28;\n}\n"
    : "+f"(d[0]), "+f"(d[1]), "+f"(d[2]), "+f"(d[3]), "+f"(d[4]), "+f"(d[5]), "+f"(d[6]), "+f"(d[7]), "+f"(d[8]), "+f"(d[9]), "+f"(d[10]), "+f"(d[11]), "+f"(d[12]), "+f"(d[13]), "+f"(d[14]), "+f"(d[15]), "+f"(d[16]), "+f"(d[17]), "+f"(d[18]), "+f"(d[19]), "+f"(d[20]), "+f"(d[21]), "+f"(d[22]), "+f"(d[23]) : "l"(da), "l"(db), "r"(sd), "n"(TA), "n"(TB));
}
template<int TA, int TB> DEVI void wgmma_n72(float* d, uint64_t da, uint64_t db, int sd) {
  asm volatile("{\n.reg .pred p;\nsetp.ne.b32 p, %38, 0;\n"
    "wgmma.mma_async.sync.aligned.m64n72k16.f32.bf16.bf16 {%0, %1, %2, %3, %4, %5, %6, %7, %8, %9, %10, %11, %12, %13, %14, %15, %16, %17, %18, %19, %20, %21, %22, %23, %24, %25, %26, %27, %28, %29, %30, %31, %32, %33, %34, %35}, %36, %37, p, 1, 1, %39, %40;\n}\n"
    : "+f"(d[0]), "+f"(d[1]), "+f"(d[2]), "+f"(d[3]), "+f"(d[4]), "+f"(d[5]), "+f"(d[6]), "+f"(d[7]), "+f"(d[8]), "+f"(d[9]), "+f"(d[10]), "+f"(d[11]), "+f"(d[12]), "+f"(d[13]), "+f"(d[14]), "+f"(d[15]), "+f"(d[16]), "+f"(d[17]), "+f"(d[18]), "+f"(d[19]), "+f"(d[20]), "+f"(d[21]), "+f"(d[22]), "+f"(d[23]), "+f"(d[24]), "+f"(d[25]), "+f"(d[26]), "+f"(d[27]), "+f"(d[28]), "+f"(d[29]), "+f"(d[30]), "+f"(d[31]), "+f"(d[32]), "+f"(d[33]), "+f"(d[34]), "+f"(d[35]) : "l"(da), "l"(db), "r"(sd), "n"(TA), "n"(TB));
}
template<int TA, int TB> DEVI void wgmma_n96(float* d, uint64_t da, uint64_t db, int sd) {
  asm volatile("{\n.reg .pred p;\nsetp.ne.b32 p, %50, 0;\n"
    "wgmma.mma_async.sync.aligned.m64n96k16.f32.bf16.bf16 {%0, %1, %2, %3, %4, %5, %6, %7, %8, %9, %10, %11, %12, %13, %14, %15, %16, %17, %18, %19, %20, %21, %22, %23, %24, %25, %26, %27, %28, %29, %30, %31, %32, %33, %34, %35, %36, %37, %38, %39, %40, %41, %42, %43, %44, %45, %46, %47}, %48, %49, p, 1, 1, %51, %52;\n}\n"
    : "+f"(d[0]), "+f"(d[1]), "+f"(d[2]), "+f"(d[3]), "+f"(d[4]), "+f"(d[5]), "+f"(d[6]), "+f"(d[7]), "+f"(d[8]), "+f"(d[9]), "+f"(d[10]), "+f"(d[11]), "+f"(d[12]), "+f"(d[13]), "+f"(d[14]), "+f"(d[15]), "+f"(d[16]), "+f"(d[17]), "+f"(d[18]), "+f"(d[19]), "+f"(d[20]), "+f"(d[21]), "+f"(d[22]), "+f"(d[23]), "+f"(d[24]), "+f"(d[25]), "+f"(d[26]), "+f"(d[27]), "+f"(d[28]), "+f"(d[29]), "+f"(d[30]), "+f"(d[31]), "+f"(d[32]), "+f"(d[33]), "+f"(d[34]), "+f"(d[35]), "+f"(d[36]), "+f"(d[37]), "+f"(d[38]), "+f"(d[39]), "+f"(d[40]), "+f"(d[41]), "+f"(d[42]), "+f"(d[43]), "+f"(d[44]), "+f"(d[45]), "+f"(d[46]), "+f"(d[47]) : "l"(da), "l"(db), "r"(sd), "n"(TA), "n"(TB));
}
template<int TA, int TB> DEVI void wgmma_n144(float* d, uint64_t da, uint64_t db, int sd) {
  asm volatile("{\n.reg .pred p;\nsetp.ne.b32 p, %74, 0;\n"
    "wgmma.mma_async.sync.aligned.m64n144k16.f32.bf16.bf16 {%0, %1, %2, %3, %4, %5, %6, %7, %8, %9, %10, %11, %12, %13, %14, %15, %16, %17, %18, %19, %20, %21, %22, %23, %24, %25, %26, %27, %28, %29, %30, %31, %32, %33, %34, %35, %36, %37, %38, %39, %40, %41, %42, %43, %44, %45, %46, %47, %48, %49, %50, %51, %52, %53, %54, %55, %56, %57, %58, %59, %60, %61, %62, %63, %64, %65, %66, %67, %68, %69, %70, %71}, %72, %73, p, 1, 1, %75, %76;\n}\n"
    : "+f"(d[0]), "+f"(d[1]), "+f"(d[2]), "+f"(d[3]), "+f"(d[4]), "+f"(d[5]), "+f"(d[6]), "+f"(d[7]), "+f"(d[8]), "+f"(d[9]), "+f"(d[10]), "+f"(d[11]), "+f"(d[12]), "+f"(d[13]), "+f"(d[14]), "+f"(d[15]), "+f"(d[16]), "+f"(d[17]), "+f"(d[18]), "+f"(d[19]), "+f"(d[20]), "+f"(d[21]), "+f"(d[22]), "+f"(d[23]), "+f"(d[24]), "+f"(d[25]), "+f"(d[26]), "+f"(d[27]), "+f"(d[28]), "+f"(d[29]), "+f"(d[30]), "+f"(d[31]), "+f"(d[32]), "+f"(d[33]), "+f"(d[34]), "+f"(d[35]), "+f"(d[36]), "+f"(d[37]), "+f"(d[38]), "+f"(d[39]), "+f"(d[40]), "+f"(d[41]), "+f"(d[42]), "+f"(d[43]), "+f"(d[44]), "+f"(d[45]), "+f"(d[46]), "+f"(d[47]), "+f"(d[48]), "+f"(d[49]), "+f"(d[50]), "+f"(d[51]), "+f"(d[52]), "+f"(d[53]), "+f"(d[54]), "+f"(d[55]), "+f"(d[56]), "+f"(d[57]), "+f"(d[58]), "+f"(d[59]), "+f"(d[60]), "+f"(d[61]), "+f"(d[62]), "+f"(d[63]), "+f"(d[64]), "+f"(d[65]), "+f"(d[66]), "+f"(d[67]), "+f"(d[68]), "+f"(d[69]), "+f"(d[70]), "+f"(d[71]) : "l"(da), "l"(db), "r"(sd), "n"(TA), "n"(TB));
}
template<int TA, int TB> DEVI void wgmma_n160(float* d, uint64_t da, uint64_t db, int sd) {
  asm volatile("{\n.reg .pred p;\nsetp.ne.b32 p, %82, 0;\n"
    "wgmma.mma_async.sync.aligned.m64n160k16.f32.bf16.bf16 {%0, %1, %2, %3, %4, %5, %6, %7, %8, %9, %10, %11, %12, %13, %14, %15, %16, %17, %18, %19, %20, %21, %22, %23, %24, %25, %26, %27, %28, %29, %30, %31, %32, %33, %34, %35, %36, %37, %38, %39, %40, %41, %42, %43, %44, %45, %46, %47, %48, %49, %50, %51, %52, %53, %54, %55, %56, %57, %58, %59, %60, %61, %62, %63, %64, %65, %66, %67, %68, %69, %70, %71, %72, %73, %74, %75, %76, %77, %78, %79}, %80, %81, p, 1, 1, %83, %84;\n}\n"
    : "+f"(d[0]), "+f"(d[1]), "+f"(d[2]), "+f"(d[3]), "+f"(d[4]), "+f"(d[5]), "+f"(d[6]), "+f"(d[7]), "+f"(d[8]), "+f"(d[9]), "+f"(d[10]), "+f"(d[11]), "+f"(d[12]), "+f"(d[13]), "+f"(d[14]), "+f"(d[15]), "+f"(d[16]), "+f"(d[17]), "+f"(d[18]), "+f"(d[19]), "+f"(d[20]), "+f"(d[21]), "+f"(d[22]), "+f"(d[23]), "+f"(d[24]), "+f"(d[25]), "+f"(d[26]), "+f"(d[27]), "+f"(d[28]), "+f"(d[29]), "+f"(d[30]), "+f"(d[31]), "+f"(d[32]), "+f"(d[33]), "+f"(d[34]), "+f"(d[35]), "+f"(d[36]), "+f"(d[37]), "+f"(d[38]), "+f"(d[39]), "+f"(d[40]), "+f"(d[41]), "+f"(d[42]), "+f"(d[43]), "+f"(d[44]), "+f"(d[45]), "+f"(d[46]), "+f"(d[47]), "+f"(d[48]), "+f"(d[49]), "+f"(d[50]), "+f"(d[51]), "+f"(d[52]), "+f"(d[53]), "+f"(d[54]), "+f"(d[55]), "+f"(d[56]), "+f"(d[57]), "+f"(d[58]), "+f"(d[59]), "+f"(d[60]), "+f"(d[61]), "+f"(d[62]), "+f"(d[63]), "+f"(d[64]), "+f"(d[65]), "+f"(d[66]), "+f"(d[67]), "+f"(d[68]), "+f"(d[69]), "+f"(d[70]), "+f"(d[71]), "+f"(d[72]), "+f"(d[73]), "+f"(d[74]), "+f"(d[75]), "+f"(d[76]), "+f"(d[77]), "+f"(d[78]), "+f"(d[79]) : "l"(da), "l"(db), "r"(sd), "n"(TA), "n"(TB));
}

__host__ __device__ constexpr int ka_seq(int p, int c) { return p == 0 ? c : c >= 5 ? 2 * c - 2 + p : p == 1 ? 17 + c : 22 + c; }
__global__ void __launch_bounds__(256, 3) k0_prep(const bf16* __restrict__ x, const bf16* __restrict__ wqkv, const bf16* __restrict__ wphi) {
    __shared__ __align__(16) uint32_t s_in[64 * 36 + 64];
    pdl_trigger();
    const int tid = threadIdx.x, lane = tid & 31, warp = __shfl_sync(~0u, tid >> 5, 0);
    const int c = blockIdx.x, g = blockIdx.y, p = blockIdx.z;
    const bool fold = p == 0 || p == 2;
    const int b = (p * 8 + g) * 9 + c;
    if (p == 3) {
        const int j = b - 216;
        const uint4 z = make_uint4(0u, 0u, 0u, 0u);
        if (j < 32) reinterpret_cast<uint4*>(g_stats)[j * 256 + tid] = z;
        else if (j < 62) reinterpret_cast<uint4*>(g_kv)[(j - 32) * 256 + tid] = z;
        else if (j == 66 && tid < 8) g_cnt[tid * CNT_S] = 0u;
        return;
    }
    constexpr int ld = 1728;
    const bf16* src = wqkv + ((p == 2 ? 0 : p + 1) * 576 + c * 64 * ld + g * 72);
    const uint32_t si = smem_u32(s_in);
    #pragma unroll
    for (int j = 0; j < 3; j++) {
        const int i = tid + j * 256, r = (i * 7282) >> 16;
        if (j < 2 || tid < 64) asm volatile("cp.async.cg.shared.global [%0], [%1], 16;" :: "r"(si + i * 16 + (r >> 3) * 32), "l"(src + (r * (ld - 72) + i * 8)) : "memory");
    }
    const int t = warp & 3, half = warp >> 2, g8 = lane >> 2, c4 = lane & 3;
    uint32_t af[3][3];
    if (fold) {
        const unsigned short* ph = reinterpret_cast<const unsigned short*>(wphi) + (g * 4 + t) * 324;
        unsigned short lo[3][3], hi[3][3];
        #pragma unroll
        for (int fb = 0; fb < 3; fb++)
            #pragma unroll
            for (int db = 0; db < 3; db++) {
                const int o = min(2 * c4 + 8 * db, 16) * 18 + min(g8 + 8 * fb, 17);
                lo[fb][db] = __ldg(ph + o); hi[fb][db] = __ldg(ph + o + 18);
            }
        #pragma unroll
        for (int fb = 0; fb < 3; fb++)
            #pragma unroll
            for (int db = 0; db < 3; db++) af[fb][db] = (uint32_t)lo[fb][db] | ((uint32_t)hi[fb][db] << 16);
    } else {
        const uint32_t v = (g8 == 2 * c4 ? 0x3f80u : 0u) | (g8 == 2 * c4 + 1 ? 0x3f800000u : 0u);
        #pragma unroll
        for (int fb = 0; fb < 3; fb++)
            #pragma unroll
            for (int db = 0; db < 3; db++) af[fb][db] = fb == db ? v : 0u;
    }
    bf16* dst = g_wqkv + (g * 27 + ka_seq(p, c)) * 4608;
    float* csd = g_cs + (g * 18 + c * 2 + half) * 216 + p * 72 + 2 * t;
    asm volatile("cp.async.wait_all;" ::: "memory");
    __syncthreads();
    if (tid < 96 && b < 192) asm volatile("prefetch.global.L2 [%0];" :: "l"(x + b * 6144 + tid * 64));
    uint32_t ov[3][4];
    const uint32_t* wr = &s_in[(half * 32 + (g8 >> 1) * 8 + (g8 & 1)) * 36 + (half * 4 + (g8 >> 1)) * 8 + t * 9 + c4];
    #pragma unroll
    for (int j = 0; j < 4; j++) {
        const uint32_t b0 = wr[j * 72], b1 = wr[j * 72 + 4], b2 = c4 == 0 ? wr[j * 72 + 8] : 0u;
        float c0[4] = {0.f, 0.f, 0.f, 0.f}, c1[4] = {0.f, 0.f, 0.f, 0.f};
        mma16816(c0, af[0][0], af[1][0], af[0][1], af[1][1], b0, b1);
        mma1688(c0, af[0][2], af[1][2], b2);
        mma16816(c1, af[2][0], 0u, af[2][1], 0u, b0, b1);
        mma1688(c1, af[2][2], 0u, b2);
        ov[0][j] = pack2(c0[0], c0[1]); ov[1][j] = pack2(c0[2], c0[3]); ov[2][j] = pack2(c1[0], c1[1]);
    }
    {
        const int nl = 2 * t + (g8 & 1);
        uint4* o = reinterpret_cast<uint4*>(dst) + ((g8 >> 1) * 8 + nl) * 8 + ((half * 4 + c4) ^ nl);
        o[0] = make_uint4(ov[0][0], ov[0][1], ov[0][2], ov[0][3]);
        o[256] = make_uint4(ov[1][0], ov[1][1], ov[1][2], ov[1][3]);
        if (g8 < 2) o[512] = make_uint4(ov[2][0], ov[2][1], ov[2][2], ov[2][3]);
    }
    {
        float cs0[4] = {0.f, 0.f, 0.f, 0.f}, cs1[4] = {0.f, 0.f, 0.f, 0.f};
        mma16816(cs0, ov[0][0], ov[1][0], ov[0][1], ov[1][1], 0x3f803f80u, 0x3f803f80u);
        mma16816(cs1, ov[2][0], 0u, ov[2][1], 0u, 0x3f803f80u, 0x3f803f80u);
        mma16816(cs0, ov[0][2], ov[1][2], ov[0][3], ov[1][3], 0x3f803f80u, 0x3f803f80u);
        mma16816(cs1, ov[2][2], 0u, ov[2][3], 0u, 0x3f803f80u, 0x3f803f80u);
        const int f = g8 + 8 * c4;
        if (f < 18) csd[8 * (f >> 1) + (f & 1)] = c4 == 0 ? cs0[0] : c4 == 1 ? cs0[2] : cs1[0];
    }
}

DEVI void dual_softmax(const float* a, float scale, uint32_t* o) {
    float mx = a[0], mn = a[0];
    #pragma unroll
    for (int j = 1; j < 18; j++) { mx = fmaxf(mx, a[j]); mn = fminf(mn, a[j]); }
    const float mxs = -mx * scale, mns = mn * scale;
    float ep[18], en[18], sp = 0.f, sn = 0.f;
    #pragma unroll
    for (int j = 0; j < 18; j++) {
        ep[j] = ex2(fmaf(a[j], scale, mxs)); sp += ep[j];
        en[j] = ex2(fmaf(a[j], -scale, mns)); sn += en[j];
    }
    const float rp = rcp(sp), rn = rcp(sn);
    #pragma unroll
    for (int j = 0; j < 9; j++) {
        o[j] = pack2(ep[2 * j] * rp, ep[2 * j + 1] * rp);
        o[9 + j] = pack2(en[2 * j] * rn, en[2 * j + 1] * rn);
    }
}

DEVI uint4 ldg128(const void* p) { uint4 v; asm volatile("ld.global.cg.v4.u32 {%0,%1,%2,%3}, [%4];" : "=r"(v.x), "=r"(v.y), "=r"(v.z), "=r"(v.w) : "l"(p)); return v; }
DEVI uint2 ldg64(const void* p) { uint2 v; asm volatile("ld.global.cg.v2.u32 {%0,%1}, [%2];" : "=r"(v.x), "=r"(v.y) : "l"(p)); return v; }
DEVI uint4 lds128(uint32_t a) { uint4 v; asm volatile("ld.shared.v4.u32 {%0,%1,%2,%3}, [%4];" : "=r"(v.x), "=r"(v.y), "=r"(v.z), "=r"(v.w) : "r"(a) : "memory"); return v; }
DEVI uint2 lds64(uint32_t a) { uint2 v; asm volatile("ld.shared.v2.u32 {%0,%1}, [%2];" : "=r"(v.x), "=r"(v.y) : "r"(a) : "memory"); return v; }
DEVI uint32_t packu(uint32_t lo, uint32_t hi) { return pack2(__uint_as_float(lo), __uint_as_float(hi)); }
DEVI void spin_ge(const unsigned int* p, unsigned int n) {
    uint32_t f; int it = 0;
    do {
        asm volatile("ld.acquire.gpu.global.u32 %0, [%1];" : "=r"(f) : "l"(p) : "memory");
        if (++it > (1 << 22)) __trap();
    } while (f < n);
}
constexpr int KA_PRE = 3, KA_REC = 5 * 16384, KA_B = 147456, KA_CS = KA_B + 9 * 9216, KA_LN = KA_CS + 864, KA_BAR = KA_LN + 1024, KA_SMEM = KA_BAR + 160;
static_assert(KA_SMEM <= 232448, "smem");
DEVI void ka_kv(uint32_t recs, float* kvh, int w4, int lane) {
    float ck[2][20];
    const uint64_t dr = mkdesc(recs, 8192, 1024, 1);
    wg_fence();
    #pragma unroll
    for (int ks = 0; ks < 4; ks++)
        #pragma unroll
        for (int hh = 0; hh < 2; hh++) wgmma_n40<1, 1>(ck[hh], dadv(dr, hh * 8192 + ks * 2048), dadv(dr, hh * 8192 + ks * 2048), ks != 0);
    wg_commit();
    wg_wait<0>();
    reg_fence<20>(ck[0]); reg_fence<20>(ck[1]);
    if (w4 >= 2) {
        #pragma unroll
        for (int e = 1; e >= 0; e--) {
            const int nt = 2 * w4 + e - 5;
            if (nt >= 0 && (nt < 2 || lane < 12)) {
                float* p = kvh + nt * 320;
                float q[10];
                #pragma unroll
                for (int j = 0; j < 10; j++) q[j] = ck[0][(j >> 1) * 4 + 2 * e + (j & 1)] + ck[1][(j >> 1) * 4 + 2 * e + (j & 1)];
                asm volatile("red.global.add.v4.f32 [%0], {%1, %2, %3, %4};" :: "l"(p + lane * 4), "f"(q[0]), "f"(q[1]), "f"(q[2]), "f"(q[3]) : "memory");
                asm volatile("red.global.add.v4.f32 [%0], {%1, %2, %3, %4};" :: "l"(p + 128 + lane * 4), "f"(q[4]), "f"(q[5]), "f"(q[6]), "f"(q[7]) : "memory");
                if ((lane & 3) < 2) asm volatile("red.global.add.v2.f32 [%0], {%1, %2};" :: "l"(p + 256 + lane * 2), "f"(q[8]), "f"(q[9]) : "memory");
            }
        }
        __syncwarp();
        bar_arrive(2, 288);
    }
}
DEVI int gpc_pos() {
    unsigned smid, nsm;
    asm volatile("mov.u32 %0, %%smid;" : "=r"(smid));
    asm volatile("mov.u32 %0, %%nsmid;" : "=r"(nsm));
    if (nsm != 132) return blockIdx.x;
    const int tpc = smid >> 1, o = smid & 1;
    if (smid == 13 || smid == 15) return 124 + tpc;
    if (tpc < 32) return (tpc & 7) * 16 + (tpc >> 3) * 2 + o;
    if (tpc < 60) { const int j = tpc - 32, r = j / 7; return (1 + j - r * 7) * 16 + 8 + r * 2 + o; }
    if (tpc < 62) return o ? 68 + tpc : (tpc - 54) * 16 + 1;
    return 8 + (tpc - 62) * 2 + o;
}
__global__ void __launch_bounds__(640, 1) ka_front(const __grid_constant__ CUtensorMap tmXA, const bf16* __restrict__ x, const bf16* __restrict__ wo, const bf16* __restrict__ w1, const bf16* __restrict__ b1) {
    extern __shared__ __align__(1024) char smem[];
    const uint32_t sm = smem_u32(smem);
    const uint32_t bFull = sm + KA_BAR, bEmpty = bFull + 9 * 8, bLn = bEmpty + 9 * 8;
    const int tid = threadIdx.x, lane = tid & 31, warp = __shfl_sync(~0u, tid >> 5, 0);
    const int pos = gpc_pos();
    if (pos >= 128) {
        const int ns = pos - 128;
        if (tid == 0) {
            #pragma unroll
            for (int q = 0; q < 6; q++) mbar_init(bFull + q * 8, 1);
            fence_mbar_init();
            #pragma unroll
            for (int q = 0; q < 6; q++) mbar_expect(bFull + q * 8, 96 * 288);
        }
        __syncthreads();
        if (tid < 576) {
            const int h = tid / 18, d = tid - h * 18, r = (h >> 2) * 72 + (d >> 1) * 8 + 2 * (h & 3) + (d & 1);
            bulk_g2s(sm + r * 304, wo + tid * 576 + ns * 144, 288, bFull + (r / 96) * 8);
        }
        #pragma unroll 1
        for (int q = 0; q < 6; q++) {
            const uint32_t ob = sm + 175104 + (q & 1) * 27648;
            mbar_wait(bFull + q * 8, 0);
            if (tid == 0) asm volatile("cp.async.bulk.wait_group.read 1;" ::: "memory");
            __syncthreads();
            if (warp < 18) {
                #pragma unroll
                for (int rb = 0; rb < 3; rb++) {
                    uint32_t r0, r1, r2, r3;
                    ldsm4t(sm + (q * 96 + rb * 32 + lane) * 304 + warp * 16, r0, r1, r2, r3);
                    stsm4(ob + (warp / 9) * 13824 + ((rb * 4 + (lane >> 3)) * 72 + (warp % 9) * 8 + (lane & 7)) * 16, r0, r1, r2, r3);
                }
            }
            fence_async_smem();
            __syncthreads();
            if (tid == 0) {
                bulk_s2g(g_wo + (ns * 2) * (72 * 576) + q * 6912, ob, 13824);
                bulk_s2g(g_wo + (ns * 2 + 1) * (72 * 576) + q * 6912, ob + 13824, 13824);
                bulk_commit();
            }
        }
        if (tid == 0) {
            asm volatile("cp.async.bulk.wait_group 0;\nfence.proxy.async.global;\nfence.acq_rel.gpu;" ::: "memory");
            pdl_wait();
            pdl_trigger();
        }
        return;
    }
    const int g = ((pos >> 4) & 1) * 4 + (pos & 3), mt = (pos >> 5) * 4 + ((pos >> 2) & 3);
    if (warp >= 16) {
        asm volatile("setmaxnreg.dec.sync.aligned.u32 32;");
        if (warp == 16) {
            if (lane == 0) {
                #pragma unroll
                for (int c = 0; c < 9; c++) { mbar_init(bFull + c * 8, 1); mbar_init(bEmpty + c * 8, 8); }
                mbar_init(bLn, 64);
                fence_mbar_init();
            }
            __syncwarp();
            bar_arrive(0, 640);
        } else {
            bar_sync(0, 640);
            if (tid == 544) {
                #pragma unroll
                for (int c = 0; c < 9; c++) mbar_expect(bFull + c * 8, 16384 + 9216);
            }
            __syncwarp();
        }
        if (tid == 512) {
            #pragma unroll
            for (int c = 0; c < KA_PRE; c++) tma3d(sm + c * 16384, &tmXA, bFull + c * 8, 0, mt * 128, c);
            pdl_wait();
            const bf16* wsrc = g_wqkv + g * (27 * 4608);
            const uint32_t sb = sm + KA_B;
            #pragma unroll
            for (int c = 0; c < 9; c++) {
                bulk_g2s(sb + c * 9216, wsrc + c * 4608, 9216, bFull + c * 8);
                const int xc = c + KA_PRE - 2;
                if (c >= 2 && xc < 9) tma3d(sm + xc * 16384, &tmXA, bFull + xc * 8, 0, mt * 128, xc);
            }
            pdl_trigger();
            #pragma unroll 1
            for (int p = 1; p < 3; p++) {
                #pragma unroll
                for (int c = 0; c < 9; c++) {
                    mbar_wait(bEmpty + c * 8, p - 1); mbar_expect(bFull + c * 8, 9216);
                    bulk_g2s(sb + c * 9216, wsrc + (p * 9 + c) * 4608, 9216, bFull + c * 8);
                }
            }
            l2_prefetch(w1 + pos * 13824, 27648);
            if (pos == 0) l2_prefetch(b1, 9216);
        } else if (warp == 17) {
            bar_sync(2, 288);
            if (lane == 0) {
                asm volatile("red.release.gpu.global.add.u32 [%0], 1;" :: "l"(g_cnt + g * CNT_S) : "memory");
                spin_ge(g_cnt + g * CNT_S, 16);
            }
            __syncwarp();
            bar_arrive(1, 288);
        } else if (warp >= 18) {
            const int m = warp - 18;
            {
                const unsigned long long* lp = g_ln + mt * 128 + m * 64 + (lane >> 3) * 16 + (lane & 7);
                unsigned long long r0, r1; int it = 0;
                __nanosleep(700);
                while (true) {
                    asm volatile("ld.relaxed.gpu.global.u64 %0, [%1];" : "=l"(r0) : "l"(lp) : "memory");
                    asm volatile("ld.relaxed.gpu.global.u64 %0, [%1];" : "=l"(r1) : "l"(lp + 8) : "memory");
                    if (__all_sync(~0u, (long long)(r0 & r1) < 0)) break;
                    if (++it > (1 << 22)) __trap();
                }
                sts128(sm + KA_LN + (m * 32 + lane) * 16, (uint32_t)r0, (uint32_t)(r0 >> 32), (uint32_t)r1, (uint32_t)(r1 >> 32));
                mbar_arrive(bLn);
            }
        }
    } else {
        const int xrow = mt * 128 + g * 16 + warp;
        uint4 xv[3];
        {
            const uint4* xr = reinterpret_cast<const uint4*>(x + xrow * D_);
            xv[0] = ldg128(xr + lane); xv[1] = ldg128(xr + lane + 32); xv[2] = ldg128(xr + 64 + (lane & 7));
        }
        asm volatile("setmaxnreg.inc.sync.aligned.u32 112;");
        bar_sync(0, 640);
        const int wg = warp >> 2, m = wg & 1, w4 = warp & 3, gq = lane >> 2, t = lane & 3;
        {
            const uint32_t w[12] = {xv[0].x, xv[0].y, xv[0].z, xv[0].w, xv[1].x, xv[1].y, xv[1].z, xv[1].w, xv[2].x, xv[2].y, xv[2].z, xv[2].w};
            float s = 0.f, s2 = 0.f;
            #pragma unroll
            for (int i = 0; i < 12; i++) { if (i < 8) s += bf_lo(w[i]) + bf_hi(w[i]); else s2 += bf_lo(w[i]) + bf_hi(w[i]); }
            if (lane < 8) s += s2;
            #pragma unroll
            for (int o = 16; o; o >>= 1) s += __shfl_xor_sync(~0u, s, o);
            const float mean = s * (1.f / D_);
            float q = 0.f, q2 = 0.f;
            #pragma unroll
            for (int i = 0; i < 12; i++) {
                const float e0 = bf_lo(w[i]) - mean, e1 = bf_hi(w[i]) - mean;
                if (i < 8) q += e0 * e0 + e1 * e1; else q2 += e0 * e0 + e1 * e1;
            }
            if (lane < 8) q += q2;
            #pragma unroll
            for (int o = 16; o; o >>= 1) q += __shfl_xor_sync(~0u, q, o);
            const unsigned long long lrec = ((unsigned long long)(__float_as_uint(rsqrtf(q * (1.f / D_) + LN_EPS)) | 0x80000000u) << 32) | __float_as_uint(mean);
            if (lane == 0) asm volatile("st.relaxed.gpu.global.u64 [%0], %1;" :: "l"(g_ln + xrow), "l"(lrec) : "memory");
        }
        float2 ln0, ln1;
        auto ln_get = [&]() {
            mbar_wait(bLn, 0);
            const uint4 v = lds128(sm + KA_LN + (m * 32 + w4 * 8 + gq) * 16);
            ln0 = make_float2(__uint_as_float(v.x), fabsf(__uint_as_float(v.y))); ln1 = make_float2(__uint_as_float(v.z), fabsf(__uint_as_float(v.w)));
        };
        const uint64_t da = mkdesc(sm + m * 8192, 16, 1024, 1), db = mkdesc(sm + KA_B, 16, 1024, 1);
        const uint32_t csa = sm + KA_CS + 8 * t;
        const int rot = (gq + 2 * t) & 7;
        const uint32_t rec = sm + KA_REC + t * 16384 + m * 8192 + (w4 * 16 + rot) * 128;
        const uint32_t kvb = sm + KA_REC;
        if (wg < 2) {
            float acc[36]; uint2 cs[9];
            #pragma unroll
            for (int c = 0; c < 9; c++) {
                mbar_wait(bFull + c * 8, 0);
                wg_fence();
                #pragma unroll
                for (int kk = 0; kk < 4; kk++) wgmma_n72<0, 0>(acc, dadv(da, c * 16384 + kk * 32), dadv(db, c * 9216 + kk * 32), (c | kk) != 0);
                wg_commit();
                if (c > 0) { wg_wait<1>(); if (lane == 0) mbar_arrive(bEmpty + (c - 1) * 8); }
            }
            wg_wait<0>();
            reg_fence<36>(acc);
            bar_arrive(5, 512);
            if (lane == 0) mbar_arrive(bEmpty + 8 * 8);
            bar_sync(6, 384);
            #pragma unroll
            for (int j = 0; j < 9; j++) cs[j] = lds64(csa + 32 * j);
            ln_get();
            uint32_t ph[2][18];
            #pragma unroll
            for (int r = 0; r < 2; r++) {
                float a[18];
                const float2 ln = r ? ln1 : ln0;
                #pragma unroll
                for (int j = 0; j < 9; j++) { a[2 * j] = fmaf(-ln.x, __uint_as_float(cs[j].x), acc[4 * j + 2 * r]); a[2 * j + 1] = fmaf(-ln.x, __uint_as_float(cs[j].y), acc[4 * j + 2 * r + 1]); }
                dual_softmax(a, ln.y * LOG2E, ph[r]);
            }
            #pragma unroll
            for (int j = 0; j < 18; j++) asm volatile("" : "+r"(ph[0][j]), "+r"(ph[1][j]));
            bar_sync(3 + m, 256);
            #pragma unroll
            for (int r = 0; r < 2; r++) {
                #pragma unroll
                for (int j = 0; j < 4; j++) sts128(rec + r * 1024 + ((j ^ rot) << 4), ph[r][4 * j], ph[r][4 * j + 1], ph[r][4 * j + 2], ph[r][4 * j + 3]);
                sts128(rec + r * 1024 + ((4 ^ rot) << 4), ph[r][16], ph[r][17], 0u, 0u);
            }
            fence_async_smem();
            bar_sync(8, 512);
            ka_kv(sm + KA_REC + wg * 16384, g_kv + (g * 4 + wg) * KV_H, w4, lane);
            bar_arrive(7, 512);
            bar_sync(11, 256);
            #pragma unroll
            for (int j = 0; j < 6; j++) if (j < 5 || tid < 196) sts128(kvb + (j * 256 + tid) * 16, 0u, 0u, 0u, 0u);
            const float* kp = g_kv + (g * 4 + w4) * KV_H + lane * 2;
            const uint32_t kd = kvb + t * 1312 + ((gq >> 1) * 8 + 2 * w4 + (gq & 1)) * 16 + w4 * 4;
            bar_sync(1, 288);
            if (m == 0) {
                const uint4 u0 = ldg128(kp + lane * 2), u1 = ldg128(kp + 128 + lane * 2); const uint2 u2 = ldg64(kp + 256);
                const uint4 v0 = ldg128(kp + 640 + lane * 2), v1 = ldg128(kp + 768 + lane * 2); const uint2 v2 = ldg64(kp + 896);
                sts32(kd, packu(u0.x, u0.y)); sts32(kd + 5248, packu(u0.z, u0.w)); sts32(kd + 10496, packu(u1.x, u1.y)); sts32(kd + 15744, packu(u1.z, u1.w));
                if (t < 2) sts32(kd + 20992, packu(u2.x, u2.y));
                if (gq < 3) {
                    sts32(kd + 1024, packu(v0.x, v0.y)); sts32(kd + 6272, packu(v0.z, v0.w)); sts32(kd + 11520, packu(v1.x, v1.y)); sts32(kd + 16768, packu(v1.z, v1.w));
                    if (t < 2) sts32(kd + 22016, packu(v2.x, v2.y));
                }
            } else {
                const uint4 u0 = ldg128(kp + 320 + lane * 2), u1 = ldg128(kp + 448 + lane * 2); const uint2 u2 = ldg64(kp + 576);
                sts32(kd + 512, packu(u0.x, u0.y)); sts32(kd + 5760, packu(u0.z, u0.w)); sts32(kd + 11008, packu(u1.x, u1.y)); sts32(kd + 16256, packu(u1.z, u1.w));
                if (t < 2) sts32(kd + 21504, packu(u2.x, u2.y));
            }
            fence_async_smem();
            bar_arrive(9, 512);
        } else {
            float avq[36], acc[36]; uint2 cs[9];
            if (m == 1) {
                pdl_wait();
                if (tid < 384 + 108) {
                    uint2 pc[18];
                    #pragma unroll
                    for (int j = 0; j < 18; j++) pc[j] = ldg64(g_cs + (g * 18 + j) * 216 + (tid - 384) * 2);
                    float a = 0.f, c = 0.f;
                    #pragma unroll
                    for (int j = 0; j < 18; j++) { a += __uint_as_float(pc[j].x); c += __uint_as_float(pc[j].y); }
                    asm volatile("st.shared.v2.f32 [%0], {%1, %2};" :: "r"(sm + KA_CS + (tid - 384) * 8), "f"(a), "f"(c) : "memory");
                }
                bar_arrive(6, 384);
            }
            bar_sync(5, 512);
            #pragma unroll
            for (int i = 9; i < 22; i++) {
                const int c = i < 17 ? (i + 1) / 2 : i - 17;
                mbar_wait(bFull + (i % 9) * 8, (i / 9) & 1);
                wg_fence();
                #pragma unroll
                for (int kk = 0; kk < 4; kk++)
                    wgmma_n72<0, 0>((i < 17 && !(i & 1)) ? acc : avq, dadv(da, c * 16384 + kk * 32), dadv(db, (i % 9) * 9216 + kk * 32), i > 10 || kk != 0);
                wg_commit();
                if (i > 9 && i <= 18) { wg_wait<1>(); if (lane == 0) mbar_arrive(bEmpty + ((i - 1) % 9) * 8); }
                if (i == 17) bar_arrive(3 + m, 256);
                if (i == 18) bar_sync(14 + m, 128);
            }
            #pragma unroll
            for (int j = 0; j < 9; j++) cs[j] = lds64(csa + 288 + 32 * j);
            ln_get();
            wg_wait<0>();
            reg_fence<36>(avq);
            #pragma unroll
            for (int r = 0; r < 2; r++) {
                uint32_t pv[9];
                const float2 ln = r ? ln1 : ln0;
                #pragma unroll
                for (int j = 0; j < 9; j++)
                    pv[j] = pack2(fmaf(-ln.x, __uint_as_float(cs[j].x), avq[4 * j + 2 * r]) * ln.y, fmaf(-ln.x, __uint_as_float(cs[j].y), avq[4 * j + 2 * r + 1]) * ln.y);
                sts128(rec + r * 1024 + ((5 ^ rot) << 4), pv[0], pv[1], pv[2], pv[3]);
                sts128(rec + r * 1024 + ((6 ^ rot) << 4), pv[4], pv[5], pv[6], pv[7]);
                sts128(rec + r * 1024 + ((7 ^ rot) << 4), pv[8], 0x00003f80u, 0u, 0u);
            }
            fence_async_smem();
            bar_sync(8, 512);
            ka_kv(sm + KA_REC + wg * 16384, g_kv + (g * 4 + wg) * KV_H, w4, lane);
            const uint32_t sm2 = __shfl_sync(~0u, sm, 1);
            const uint64_t da2 = mkdesc(sm2 + m * 8192, 16, 1024, 1), db2 = mkdesc(sm2 + KA_B, 16, 1024, 1);
            #pragma unroll
            for (int i = 22; i < 27; i++) mbar_wait(bFull + (i % 9) * 8, 0);
            #pragma unroll
            for (int j = 0; j < 9; j++) cs[j] = lds64(csa + 576 + 32 * j);
            bar_sync(7, 512);
            wg_fence();
            #pragma unroll
            for (int i = 22; i < 27; i++)
                #pragma unroll
                for (int kk = 0; kk < 4; kk++) wgmma_n72<0, 0>(acc, dadv(da2, (i - 22) * 16384 + kk * 32), dadv(db2, (i % 9) * 9216 + kk * 32), 1);
            wg_commit();
            wg_wait<0>();
            reg_fence<36>(acc);
            uint32_t ph[2][18];
            #pragma unroll
            for (int r = 0; r < 2; r++) {
                float a[18];
                const float2 ln = r ? ln1 : ln0;
                #pragma unroll
                for (int j = 0; j < 9; j++) { a[2 * j] = fmaf(-ln.x, __uint_as_float(cs[j].x), acc[4 * j + 2 * r]); a[2 * j + 1] = fmaf(-ln.x, __uint_as_float(cs[j].y), acc[4 * j + 2 * r + 1]); }
                dual_softmax(a, ln.y * LOG2E, ph[r]);
            }
            #pragma unroll
            for (int j = 0; j < 18; j++) asm volatile("" : "+r"(ph[0][j]), "+r"(ph[1][j]));
            uint32_t* og = reinterpret_cast<uint32_t*>(g_o + (mt * 2 + m) * (64 * D_) + g * 4608) + w4 * 64 + lane;
            asm volatile("" : "+l"(og));
            const uint64_t dk = mkdesc(sm2 + KA_REC, 1312, 128, 0);
            float oc[40];
            bar_sync(9, 512);
            wg_fence();
            #pragma unroll
            for (int j = 0; j < 9; j++) wgmma_rs_n80(oc, ph[0][2 * j], ph[1][2 * j], ph[0][2 * j + 1], ph[1][2 * j + 1], dadv(dk, j * 2624), j != 0);
            wg_commit();
            wg_wait<0>();
            reg_fence<40>(oc);
            const float r0 = rcp_full(oc[36] + 1e-6f), r1 = rcp_full(oc[38] + 1e-6f);
            #pragma unroll
            for (int j = 0; j < 9; j++) { og[j * 256] = pack2(oc[4 * j] * r0, oc[4 * j + 1] * r0); og[j * 256 + 32] = pack2(oc[4 * j + 2] * r1, oc[4 * j + 3] * r1); }
        }
    }
}

constexpr int K2PRE = 2, K2_B = 73728, K2_PIECE = 27648, K2_X = K2_B + 5 * K2_PIECE, K2_BAR = K2_X + 18432, K2_SMEM = K2_BAR + 128;
__global__ void __cluster_dims__(2, 1, 1) __launch_bounds__(288, 1) k2_attn(const __grid_constant__ CUtensorMap tmX, const bf16* __restrict__ b2) {
    extern __shared__ __align__(1024) char smem[];
    const uint32_t sm = smem_u32(smem);
    const uint32_t bFull = sm + K2_BAR, bX = bFull + 6 * 8;
    const int tid = threadIdx.x, lane = tid & 31, warp = __shfl_sync(~0u, tid >> 5, 0);
    const int ns = blockIdx.x & 3, mt = blockIdx.x >> 2;
    const int wg = warp >> 2, w4 = warp & 3, gq = lane >> 2, t = lane & 3;
    const bf16* wsrc = g_wo + ns * (2 * 72 * 576);
    unsigned short bb0, bb1;
    asm volatile("ld.global.nc.u16 %0, [%1];" : "=h"(bb0) : "l"(b2 + mt * 64 + w4 * 16 + gq));
    asm volatile("ld.global.nc.u16 %0, [%1];" : "=h"(bb1) : "l"(b2 + mt * 64 + w4 * 16 + gq + 8));
    auto load_w = [&](int i) {
        bulk_g2s(sm + K2_B + (i % 5) * K2_PIECE, wsrc + i * (K2_PIECE / 4), K2_PIECE / 2, bFull + i * 8);
        bulk_g2s(sm + K2_B + (i % 5) * K2_PIECE + K2_PIECE / 2, wsrc + 72 * 576 + i * (K2_PIECE / 4), K2_PIECE / 2, bFull + i * 8);
    };
    if (tid == 256) {
        #pragma unroll
        for (int i = 0; i < 7; i++) mbar_init(bFull + i * 8, 1);
        fence_mbar_init();
        #pragma unroll
        for (int i = 0; i < K2PRE; i++) load_w(i);
    }
    __syncthreads();
    if (warp == 8) {
        if (lane == 0) {
            pdl_wait();
            const bf16* osrc = g_o + mt * (64 * D_);
            #pragma unroll
            for (int i = 0; i < 6; i++) {
                bulk_g2s(sm + i * 12288, osrc + i * 6144, 12288, bFull + i * 8);
                if (i + 1 >= K2PRE && i < 4) load_w(i + 1);
            }
            pdl_trigger();
        }
        __syncwarp();
        bar_sync(3, 288);
        if (lane == 0) {
            load_w(5);
            tma2d(sm + K2_X, &tmX, bX, ns * 144, mt * 64);
            tma2d(sm + K2_X + 9216, &tmX, bX, ns * 144 + 72, mt * 64);
        }
    } else {
        if (tid == 0) {
            #pragma unroll
            for (int i = 0; i < 6; i++) mbar_expect(bFull + i * 8, K2_PIECE + 12288);
            mbar_expect(bX, 18432);
            prefetch_tm(&tmX);
        }
        __syncwarp();
        float acc[36];
        const uint32_t xs = sm + K2_X + wg * 9216;
        uint32_t xr[18];
        const int p = ns * 2 + wg;
        unsigned long long* sb = g_stats + (mt * 4 + w4) * 128 + gq * 2;
        unsigned long long* sw = sb + p * 16;
        const unsigned long long* sr = sb + t * 32;
        uint32_t* ndst = reinterpret_cast<uint32_t*>(g_hnT + (mt * D_ + p * 72) * 64) + w4 * 64 + lane;
        asm volatile("" : "+l"(sw), "+l"(sr), "+l"(ndst));
        const uint64_t da0 = mkdesc(sm, 1024, 128, 0), db0 = mkdesc(sm + K2_B + wg * (K2_PIECE / 2), 1152, 128, 0);
        #pragma unroll
        for (int i = 0; i < 6; i++) {
            mbar_wait(bFull + i * 8, 0);
            wg_fence();
            #pragma unroll
            for (int kk = 0; kk < 6; kk++)
                wgmma_n72<0, 0>(acc, dadv(da0, i * 12288 + kk * 2048), dadv(db0, (i % 5) * K2_PIECE + kk * 2304), (i | kk) != 0);
            wg_commit();
            if (i == 1) { wg_wait<1>(); bar_arrive(3, 288); }
            if (i == 5) {
                mbar_wait(bX, 0);
                #pragma unroll
                for (int j = 0; j < 9; j++) {
                    xr[2 * j] = lds32(xs + (w4 * 16 + gq) * 144 + j * 16 + t * 4); xr[2 * j + 1] = lds32(xs + (w4 * 16 + gq + 8) * 144 + j * 16 + t * 4);
                }
            }
        }
        wg_wait<0>();
        reg_fence<36>(acc);
        #pragma unroll
        for (int j = 0; j < 18; j++) { acc[2 * j] += bf_lo(xr[j]); acc[2 * j + 1] += bf_hi(xr[j]); }
        float m0 = 0.f, m1 = 0.f;
        #pragma unroll
        for (int j = 0; j < 9; j++) { m0 += acc[4 * j] + acc[4 * j + 1]; m1 += acc[4 * j + 2] + acc[4 * j + 3]; }
        m0 *= (1.f / 18); m1 *= (1.f / 18);
        float q0 = 0.f, q1 = 0.f, q2 = 0.f, q3 = 0.f;
        #pragma unroll
        for (int j = 0; j < 9; j++) {
            float e;
            e = acc[4 * j] - m0; q0 = fmaf(e, e, q0); e = acc[4 * j + 1] - m0; q2 = fmaf(e, e, q2);
            e = acc[4 * j + 2] - m1; q1 = fmaf(e, e, q1); e = acc[4 * j + 3] - m1; q3 = fmaf(e, e, q3);
        }
        q0 += q2; q1 += q3;
        #pragma unroll
        for (int o = 1; o < 4; o <<= 1) {
            const float a0 = __shfl_xor_sync(~0u, m0, o), a1 = __shfl_xor_sync(~0u, m1, o), b0 = __shfl_xor_sync(~0u, q0, o), b1 = __shfl_xor_sync(~0u, q1, o);
            q0 += b0 + (a0 - m0) * (a0 - m0) * (9.f * o); q1 += b1 + (a1 - m1) * (a1 - m1) * (9.f * o);
            m0 = 0.5f * (m0 + a0); m1 = 0.5f * (m1 + a1);
        }
        if (t == 0) {
            const unsigned long long r0 = ((unsigned long long)(__float_as_uint(q0) | 0x80000000u) << 32) | __float_as_uint(m0);
            const unsigned long long r1 = ((unsigned long long)(__float_as_uint(q1) | 0x80000000u) << 32) | __float_as_uint(m1);
            asm volatile("st.relaxed.gpu.global.v2.u64 [%0], {%1, %2};" :: "l"(sw), "l"(r0), "l"(r1) : "memory");
        }
        unsigned long long ra, rb, rc, rd;
        {
            int it = 0;
            while (true) {
                asm volatile("ld.relaxed.gpu.global.v2.u64 {%0, %1}, [%2];" : "=l"(ra), "=l"(rc) : "l"(sr) : "memory");
                asm volatile("ld.relaxed.gpu.global.v2.u64 {%0, %1}, [%2];" : "=l"(rb), "=l"(rd) : "l"(sr + 16) : "memory");
                const bool ok = (long long)(ra & rb & rc & rd) < 0;
                if (__all_sync(~0u, ok)) break;
                if (++it > (1 << 22)) __trap();
            }
        }
        float sc[2], mu[2];
        #pragma unroll
        for (int r = 0; r < 2; r++) {
            const unsigned long long u = r ? rc : ra, v = r ? rd : rb;
            const float ma = __uint_as_float((uint32_t)u), mb = __uint_as_float((uint32_t)v);
            float ms = ma + mb;
            ms += __shfl_xor_sync(~0u, ms, 1); ms += __shfl_xor_sync(~0u, ms, 2);
            const float mean = ms * 0.125f;
            float M2 = fabsf(__uint_as_float((uint32_t)(u >> 32))) + fabsf(__uint_as_float((uint32_t)(v >> 32))) + 72.f * ((ma - mean) * (ma - mean) + (mb - mean) * (mb - mean));
            M2 += __shfl_xor_sync(~0u, M2, 1); M2 += __shfl_xor_sync(~0u, M2, 2);
            const float var = M2 * (1.f / D_);
            const float r1 = rsqrtf(var + LN_EPS);
            const float var2 = var * r1 * r1;
            const float r2 = rsqrtf(var2 + LN_EPS);
            sc[r] = 0.5f * (r1 * r2); mu[r] = mean;
        }
        #pragma unroll
        for (int j = 0; j < 9; j++) {
            ndst[j * 256] = pack2((acc[4 * j] - mu[0]) * sc[0], (acc[4 * j + 1] - mu[0]) * sc[0]);
            ndst[j * 256 + 32] = pack2((acc[4 * j + 2] - mu[1]) * sc[1], (acc[4 * j + 3] - mu[1]) * sc[1]);
        }
        if (p == 1 && t < 2) g_ln[mt * 64 + w4 * 16 + gq + 8 * t] = 0ull;
        if (p == 0 && t < 2) {
            asm volatile("" : "+h"(bb0), "+h"(bb1));
            g_rc[mt * 64 + w4 * 16 + gq + 8 * t] = make_float2(1.f / (t ? sc[1] : sc[0]), (t ? mu[1] : mu[0]) + __uint_as_float((uint32_t)(t ? bb1 : bb0) << 16));
        }
    }
}

constexpr int PFT = 4, W2HEAD = 9;
constexpr int K3_STAGES = 6, K3_STAGE = 36864, K3_STAG = 6, K3_PRE = 2, K3_BAR = K3_STAGES * K3_STAGE, K3_SMEM = K3_BAR + 256;
DEVI uint32_t gelu2(float a0, float a1) {
    const float z0 = a0 * fmaf(a0 * a0, 0.2854192650904f, 1.5957691216057f), z1 = a1 * fmaf(a1 * a1, 0.2854192650904f, 1.5957691216057f);
    return pack2(fmaf(a0, tanh_fast(z0), a0), fmaf(a1, tanh_fast(z1), a1));
}
template<int NB> DEVI void k3_store(const float* q, uint32_t* dst) {
    #pragma unroll
    for (int j = 0; j < NB; j++) { dst[j * 256] = gelu2(q[4 * j], q[4 * j + 1]); dst[j * 256 + 32] = gelu2(q[4 * j + 2], q[4 * j + 3]); }
}
DEVI void k3_typeb(uint32_t sm_, int fc_, float bias0, float bias1, const bf16* __restrict__ b1) {
    const uint32_t sm = __shfl_sync(~0u, sm_, 0);
    const int fc = __shfl_sync(~0u, fc_, 0);
    const uint32_t bFull = sm + K3_BAR, bEmpty = bFull + K3_STAGES * 8;
    const int tid = threadIdx.x, lane = tid & 31, warp = __shfl_sync(~0u, tid >> 5, 0);
    const int wg = warp >> 2, w4 = warp & 3, gq = lane >> 2;
    const uint32_t st = sm + wg * 8192;
    const uint64_t da0 = mkdesc(st, 8192, 1024, 1);
    int s = 0, ps = 0; uint32_t ph = 0;
    {
            const int f2 = (fc + 2) * 64 + w4 * 16 + gq;
            const float bias2 = 0.5f * __bfloat162float(b1[f2]), bias3 = 0.5f * __bfloat162float(b1[f2 + 8]);
            float acc[48], acc2[24];
            const uint64_t da2 = mkdesc(sm + 16384, 8192, 1024, 1), db0 = mkdesc(sm + 24576, 128, 1024, 0), db2 = mkdesc(sm + 24576 + wg * 6144, 128, 1024, 0);
            #pragma unroll 1
            for (int i = 0; i < 32 - K3_STAG; i++) {
                mbar_wait(bFull + s * 8, ph);
                const uint32_t so = s * K3_STAGE;
                wg_fence();
                #pragma unroll
                for (int kk = 0; kk < 4; kk++) {
                    wgmma_n96<1, 1>(acc, dadv(da0, so + kk * 2048), dadv(db0, so + kk * 256), (i | kk) != 0);
                    wgmma_n48<1, 1>(acc2, dadv(da2, so + kk * 2048), dadv(db2, so + kk * 256), (i | kk) != 0);
                }
                wg_commit();
                wg_wait<1>();
                if (i > 0 && lane == 0) mbar_arrive(bEmpty + ps * 8);
                ps = s;
                if (++s == K3_STAGES) { s = 0; ph ^= 1; }
            }
            if (wg == 1) {
                wg_wait<0>();
                if (lane == 0) mbar_arrive(bEmpty + ps * 8);
                #pragma unroll
                for (int i = 32 - K3_STAG; i < 32; i++) mbar_wait(bFull + (i % K3_STAGES) * 8, (i / K3_STAGES) & 1);
                bar_sync(3, 256);
            }
            #pragma unroll
            for (int i = 32 - K3_STAG; i < 32; i++) {
                if (wg == 0) mbar_wait(bFull + (i % K3_STAGES) * 8, (i / K3_STAGES) & 1);
                const uint32_t so = (i % K3_STAGES) * K3_STAGE;
                wg_fence();
                #pragma unroll
                for (int kk = 0; kk < 4; kk++) {
                    wgmma_n96<1, 1>(acc, dadv(da0, so + kk * 2048), dadv(db0, so + kk * 256), 1);
                    wgmma_n48<1, 1>(acc2, dadv(da2, so + kk * 2048), dadv(db2, so + kk * 256), 1);
                }
                wg_commit();
                if (i == 32 - K3_STAG && wg == 0) { wg_wait<1>(); if (lane == 0) mbar_arrive(bEmpty + ps * 8); }
            }
            if (wg == 0) bar_arrive(3, 256);
            wg_wait<0>();
            reg_fence<48>(acc); reg_fence<24>(acc2);
            #pragma unroll
            for (int j = 0; j < 48; j++) acc[j] += (j & 2) ? bias1 : bias0;
            #pragma unroll
            for (int j = 0; j < 24; j++) acc2[j] += (j & 2) ? bias3 : bias2;
            k3_store<12>(acc, reinterpret_cast<uint32_t*>(g_u + ((fc + wg) * D_ + 480) * 64) + w4 * 64 + lane);
            k3_store<6>(acc2, reinterpret_cast<uint32_t*>(g_u + ((fc + 2) * D_ + 480 + wg * 48) * 64) + w4 * 64 + lane);
    }
}
__global__ void __cluster_dims__(2, 1, 1) __launch_bounds__(288, 1) k3_mix1(const __grid_constant__ CUtensorMap tmW1a, const __grid_constant__ CUtensorMap tmW1b,
                                                                             const bf16* __restrict__ b1, const bf16* __restrict__ w1, const bf16* __restrict__ w2) {
    extern __shared__ __align__(1024) char smem[];
    const uint32_t sm = smem_u32(smem);
    const uint32_t bFull = sm + K3_BAR, bEmpty = bFull + K3_STAGES * 8;
    const int tid = threadIdx.x, lane = tid & 31, warp = __shfl_sync(~0u, tid >> 5, 0);
    const int cl = blockIdx.x >> 1, rank = blockIdx.x & 1;
    bool tb = false; int fc, d0;
    if (cl < 36) { fc = 2 * cl; d0 = 160 * rank; }
    else if (cl < 60) { const int q = (cl - 36) >> 1, e = (cl - 36) & 1; tb = rank; fc = rank ? 6 * q + 3 * e : 6 * q + 4 * e; d0 = rank ? 480 : 320; }
    else { fc = 6 * (2 * (cl - 60) + rank) + 2; d0 = 320; }
    const CUtensorMap* tm = tb ? &tmW1b : &tmW1a;
    const uint32_t abytes = tb ? 24576 : 16384;
    if (tid == 256) {
        #pragma unroll
        for (int i = 0; i < K3_STAGES; i++) { mbar_init(bFull + i * 8, 1); mbar_init(bEmpty + i * 8, 8); }
        fence_mbar_init();
        #pragma unroll
        for (int i = 0; i < K3_STAGES; i++) mbar_expect(bFull + i * 8, K3_STAGE);
        #pragma unroll
        for (int i = 0; i < K3_PRE; i++) tma3d(sm + i * K3_STAGE, tm, bFull + i * 8, 0, i * 64, fc);
    }
    __syncthreads();
    if (warp == 8) {
        if (tid == 256) {
            pdl_wait();
            pdl_trigger();
            const bf16* hs = g_hnT + d0 * 64;
            #pragma unroll
            for (int i = 0; i < K3_STAGES; i++) {
                bulk_g2s(sm + i * K3_STAGE + abytes, hs + i * (D_ * 64), K3_STAGE - abytes, bFull + i * 8);
                if (i >= K3_PRE) tma3d(sm + i * K3_STAGE, tm, bFull + i * 8, 0, i * 64, fc);
            }
            int s = 0; uint32_t ph = 0;
            #pragma unroll 1
            for (int i = K3_STAGES; i < 32; i++) {
                mbar_wait(bEmpty + s * 8, ph);
                mbar_expect(bFull + s * 8, K3_STAGE);
                tma3d(sm + s * K3_STAGE, tm, bFull + s * 8, 0, i * 64, fc);
                bulk_g2s(sm + s * K3_STAGE + abytes, hs + i * (D_ * 64), K3_STAGE - abytes, bFull + s * 8);
                if (i == 18 && blockIdx.x < 128) l2_prefetch(w1 + (size_t)(2048 - 64 * PFT) * F_ + blockIdx.x * (2304 * PFT), 4608 * PFT);
                if (++s == K3_STAGES) { s = 0; ph ^= 1; }
            }
            if (blockIdx.x < 128) l2_prefetch(w2 + (size_t)(blockIdx.x & 1) * (2304 * S_) + (blockIdx.x >> 1) * (W2HEAD * 2048), W2HEAD * 4096);
        }
    } else {
        const int wg = warp >> 2, w4 = warp & 3, gq = lane >> 2;
        const int f0 = (fc + wg) * 64 + w4 * 16 + gq;
        const float bias0 = 0.5f * __bfloat162float(b1[f0]), bias1 = 0.5f * __bfloat162float(b1[f0 + 8]);
        uint32_t* dst = reinterpret_cast<uint32_t*>(g_u + ((fc + wg) * D_ + d0) * 64) + w4 * 64 + lane;
        const uint32_t st = sm + wg * 8192;
        const uint64_t da0 = mkdesc(st, 8192, 1024, 1);
        int s = 0, ps = 0; uint32_t ph = 0;
        if (!tb) {
            float acc[80];
            #pragma unroll
            for (int j = 0; j < 80; j++) acc[j] = (j & 2) ? bias1 : bias0;
            reg_fence<80>(acc);
            const uint64_t db0 = mkdesc(sm + 16384, 128, 1024, 0);
            #pragma unroll 1
            for (int i = 0; i < 32 - K3_STAG; i++) {
                mbar_wait(bFull + s * 8, ph);
                const uint64_t da = dadv(da0, s * K3_STAGE), db = dadv(db0, s * K3_STAGE);
                wg_fence();
                #pragma unroll
                for (int kk = 0; kk < 4; kk++)
                    wgmma_n160<1, 1>(acc, dadv(da, kk * 2048), dadv(db, kk * 256), 1);
                wg_commit();
                wg_wait<1>();
                if (i > 0 && lane == 0) mbar_arrive(bEmpty + ps * 8);
                ps = s;
                if (++s == K3_STAGES) { s = 0; ph ^= 1; }
            }
            if (wg == 1) {
                wg_wait<0>();
                if (lane == 0) mbar_arrive(bEmpty + ps * 8);
                #pragma unroll
                for (int i = 32 - K3_STAG; i < 32; i++) mbar_wait(bFull + (i % K3_STAGES) * 8, (i / K3_STAGES) & 1);
                bar_sync(3, 256);
            }
            #pragma unroll
            for (int i = 32 - K3_STAG; i < 32; i++) {
                if (wg == 0) mbar_wait(bFull + (i % K3_STAGES) * 8, (i / K3_STAGES) & 1);
                wg_fence();
                #pragma unroll
                for (int kk = 0; kk < 4; kk++)
                    wgmma_n160<1, 1>(acc, dadv(da0, (i % K3_STAGES) * K3_STAGE + kk * 2048), dadv(db0, (i % K3_STAGES) * K3_STAGE + kk * 256), 1);
                wg_commit();
                if (i == 32 - K3_STAG && wg == 0) { wg_wait<1>(); if (lane == 0) mbar_arrive(bEmpty + ps * 8); }
            }
            if (wg == 0) bar_arrive(3, 256);
            wg_wait<0>();
            reg_fence<80>(acc);
            k3_store<20>(acc, dst);
        } else {
            k3_typeb(sm, fc, bias0, bias1, b1);
        }
    }
}

constexpr int SLOTC = 700, SLOTP = 578, K4A0 = 1, K4_PD = 4;
constexpr int K4_STAGES = 5, K4_STAGE = 8192 + 36864, K4_STAG = 3, K4_BAR = K4_STAGES * K4_STAGE, K4_SMEM = K4_BAR + 256;
constexpr int K4_XS = (36 - K4_STAG - 1) % K4_STAGES;
__global__ void __cluster_dims__(2, 1, 1) __launch_bounds__(288, 1) k4_mix2(const __grid_constant__ CUtensorMap tmW2, const __grid_constant__ CUtensorMap tmOut) {
    extern __shared__ __align__(1024) char smem[];
    const uint32_t sm = smem_u32(smem);
    const uint32_t bFull = sm + K4_BAR, bEmpty = bFull + K4_STAGES * 8, bP = bEmpty + K4_STAGES * 8, bRdy = bP + 16, bH = bRdy + 8;
    const int tid = threadIdx.x, lane = tid & 31, warp = __shfl_sync(~0u, tid >> 5, 0);
    const int ks = blockIdx.x & 1, tm = (blockIdx.x >> 1) & 31, tn = blockIdx.x >> 6;
    const int k0 = ks * 36;
    if (tid == 256) {
        #pragma unroll
        for (int i = 0; i < K4_STAGES; i++) { mbar_init(bFull + i * 8, 1); mbar_init(bEmpty + i * 8, 8); }
        mbar_init(bP, 1); mbar_init(bP + 8, 1); mbar_init(bRdy, 8); mbar_init(bH, 1);
        fence_mbar_init();
        #pragma unroll
        for (int i = 0; i < K4A0; i++) tma3d(sm + i * K4_STAGE, &tmW2, bFull + i * 8, 0, (k0 + i) * 64, tm);
    }
    __syncthreads();
    cluster_arrive_relaxed();
    if (tid == 0) {
        #pragma unroll
        for (int i = K4A0; i < 2; i++) tma3d(sm + i * K4_STAGE, &tmW2, bFull + i * 8, 0, (k0 + i) * 64, tm);
    }
    if (tid == 32) {
        #pragma unroll
        for (int i = 0; i < K4_STAGES; i++) mbar_expect(bFull + i * 8, K4_STAGE);
    }
    if (tid == 128) { mbar_expect(bP, 9216); mbar_expect(bP + 8, 9216); prefetch_tm(&tmOut); }
    __syncwarp();
    if (warp == 8) {
        if (lane == 0) {
            pdl_wait();
            const bf16* us = g_u + ((size_t)k0 * D_ + tn * 288) * 64;
            uint32_t slot = clock() + SLOTC;
            #pragma unroll
            for (int i = 0; i < K4_STAGES; i++) {
                if (i >= 2) { tma3d(sm + i * K4_STAGE, &tmW2, bFull + i * 8, 0, (k0 + i) * 64, tm); while ((int)(clock() - slot) < 0) {} slot += SLOTP; }
                bulk_g2s(sm + i * K4_STAGE + 8192, us + (size_t)i * (D_ * 64), 36864, bFull + i * 8);
            }
            int s = 0; uint32_t ph = 0;
            #pragma unroll 1
            for (int i = K4_STAGES; i < 36; i++) {
                mbar_wait(bEmpty + s * 8, ph);
                mbar_expect(bFull + s * 8, K4_STAGE);
                tma3d(sm + s * K4_STAGE, &tmW2, bFull + s * 8, 0, (k0 + i) * 64, tm);
                if (i + K4_PD < 36 && ((i ^ tn) & 1)) tma3d_prefetch(&tmW2, 0, (k0 + i + K4_PD) * 64, tm);
                if (i < 32) { while ((int)(clock() - slot) < 0) {} slot += SLOTP; }
                bulk_g2s(sm + s * K4_STAGE + 8192, us + (size_t)i * (D_ * 64), 36864, bFull + s * 8);
                if (++s == K4_STAGES) { s = 0; ph ^= 1; }
            }
            static_assert(K4_STAG <= 3, "stage of step 31 is free");
            mbar_wait(bEmpty + s * 8, ph);
            mbar_expect(bH, 18432);
            bulk_g2s(sm + (31 % K4_STAGES) * K4_STAGE, g_hnT + (tm * D_ + tn * 288 + ks * 144) * 64, 18432, bH);
        }
        __syncwarp();
        cluster_wait();
        #pragma unroll
        for (int hh = 0; hh < 2; hh++) {
            bar_sync(4 + hh, 160);
            if (lane == 0) {
                tma2d_store(&tmOut, sm + K4_XS * K4_STAGE + 24576 + hh * 9216, tn * 288 + ks * 144 + hh * 72, tm * 64);
                bulk_commit();
            }
            __syncwarp();
        }
        if (lane == 0) { bulk_wait_read(); }
    } else {
        const int wg = warp >> 2, w4 = warp & 3, tw = tid & 127;
        const bool keep = wg == ks;
        float acc[72];
        const uint64_t da0 = mkdesc(sm, 8192, 1024, 1), db0 = mkdesc(sm + 8192 + wg * 18432, 128, 1024, 0);
        const uint32_t rdy = mapa(bRdy, ks ^ 1);
        cluster_wait();
        int s = 0, ps = 0; uint32_t ph = 0;
        #pragma unroll 1
        for (int i = 0; i < 36 - K4_STAG; i++) {
            mbar_wait(bFull + s * 8, ph);
            const uint64_t da = dadv(da0, s * K4_STAGE), db = dadv(db0, s * K4_STAGE);
            wg_fence();
            #pragma unroll
            for (int kk = 0; kk < 4; kk++)
                wgmma_n144<1, 1>(acc, dadv(da, kk * 2048), dadv(db, kk * 256), (i | kk) != 0);
            wg_commit();
            wg_wait<1>();
            if (i > 0 && lane == 0) mbar_arrive(bEmpty + ps * 8);
            ps = s;
            if (++s == K4_STAGES) { s = 0; ph ^= 1; }
        }
        const uint32_t xa = sm + K4_XS * K4_STAGE + tw * 16;
        const uint2 rc0 = ldg64(g_rc + tm * 64 + w4 * 16 + (lane >> 2)), rc1 = ldg64(g_rc + tm * 64 + w4 * 16 + (lane >> 2) + 8);
        float res[36];
        const uint32_t ya = sm + (31 % K4_STAGES) * K4_STAGE + 20480 + tw * 16;
        auto residual = [&](int hh) {
            uint32_t hp[20];
            mbar_wait(bH, 0);
            const uint32_t ha = sm + (31 % K4_STAGES) * K4_STAGE + hh * 9216 + (lane >> 4) * 1024 + w4 * 256 + (lane & 15) * 16;
            #pragma unroll
            for (int j = 0; j < 5; j++)
                asm volatile("ldmatrix.sync.aligned.m8n8.x4.shared.b16 {%0,%1,%2,%3}, [%4];" : "=r"(hp[4 * j]), "=r"(hp[4 * j + 1]), "=r"(hp[4 * j + 2]), "=r"(hp[4 * j + 3]) : "r"(ha + j * 2048) : "memory");
            #pragma unroll
            for (int j = 0; j < 18; j++) {
                const float is = __uint_as_float((j & 1) ? rc1.x : rc0.x), of = __uint_as_float((j & 1) ? rc1.y : rc0.y);
                res[2 * j] = fmaf(bf_lo(hp[j]), is, of); res[2 * j + 1] = fmaf(bf_hi(hp[j]), is, of);
            }
            reg_fence<36>(res);
        };
        auto partial = [&](int hh) {
            mbar_wait(bP + hh * 8, 0);
            uint32_t o[18];
            #pragma unroll
            for (int j = 0; j < 4; j++) { const uint4 v = lds128(xa + hh * 10240 + j * 2048); o[4 * j] = v.x; o[4 * j + 1] = v.y; o[4 * j + 2] = v.z; o[4 * j + 3] = v.w; }
            { const uint2 v = lds64(xa + hh * 10240 + 8192); o[16] = v.x; o[17] = v.y; }
            #pragma unroll
            for (int j = 0; j < 18; j++) { res[2 * j] += bf_lo(o[j]); res[2 * j + 1] += bf_hi(o[j]); }
        };
        if (!keep) {
            #pragma unroll
            for (int i = 36 - K4_STAG; i < 36; i++) {
                mbar_wait(bFull + (i % K4_STAGES) * 8, (i / K4_STAGES) & 1);
                wg_fence();
                #pragma unroll
                for (int kk = 0; kk < 4; kk++)
                    wgmma_n144<1, 1>(acc, dadv(da0, (i % K4_STAGES) * K4_STAGE + kk * 2048), dadv(db0, (i % K4_STAGES) * K4_STAGE + kk * 256), 1);
                wg_commit();
                if (i == 36 - K4_STAG) { wg_wait<1>(); if (lane == 0) mbar_arrive_remote(rdy); }
            }
            bar_arrive(3, 256);
            mbar_wait(bRdy, 0);
            wg_wait<0>();
            reg_fence<72>(acc);
            const uint32_t rd = mapa(xa, ks ^ 1), rb = mapa(bP, ks ^ 1);
            #pragma unroll
            for (int hh = 0; hh < 2; hh++) {
                const float* q = acc + hh * 36;
                #pragma unroll
                for (int j = 0; j < 4; j++)
                    asm volatile("st.async.shared::cluster.mbarrier::complete_tx::bytes.v4.b32 [%0], {%1,%2,%3,%4}, [%5];"
                                 :: "r"(rd + hh * 10240 + j * 2048), "r"(pack2(q[8 * j], q[8 * j + 1])), "r"(pack2(q[8 * j + 2], q[8 * j + 3])),
                                    "r"(pack2(q[8 * j + 4], q[8 * j + 5])), "r"(pack2(q[8 * j + 6], q[8 * j + 7])), "r"(rb + hh * 8) : "memory");
                asm volatile("st.async.shared::cluster.mbarrier::complete_tx::bytes.v2.b32 [%0], {%1,%2}, [%3];"
                             :: "r"(rd + hh * 10240 + 8192), "r"(pack2(q[32], q[33])), "r"(pack2(q[34], q[35])), "r"(rb + hh * 8) : "memory");
            }
            residual(1);
            partial(1);
            reg_fence<36>(res);
            bar_sync(1, 256);
            #pragma unroll
            for (int j = 0; j < 9; j++) {
                const uint4 v = lds128(ya + j * 2048);
                res[4 * j] += __uint_as_float(v.x); res[4 * j + 1] += __uint_as_float(v.y); res[4 * j + 2] += __uint_as_float(v.z); res[4 * j + 3] += __uint_as_float(v.w);
            }
        } else {
            wg_wait<0>();
            if (lane == 0) mbar_arrive_remote(rdy);
            #pragma unroll
            for (int i = 36 - K4_STAG; i < 36; i++) mbar_wait(bFull + (i % K4_STAGES) * 8, (i / K4_STAGES) & 1);
            bar_sync(3, 256);
            wg_fence();
            #pragma unroll
            for (int i = 36 - K4_STAG; i < 36; i++)
                #pragma unroll
                for (int kk = 0; kk < 4; kk++)
                    wgmma_n144<1, 1>(acc, dadv(da0, (i % K4_STAGES) * K4_STAGE + kk * 2048), dadv(db0, (i % K4_STAGES) * K4_STAGE + kk * 256), 1);
            wg_commit();
            residual(0);
            wg_wait<0>();
            reg_fence<72>(acc);
            #pragma unroll
            for (int j = 0; j < 9; j++)
                sts128(ya + j * 2048, __float_as_uint(acc[36 + 4 * j]), __float_as_uint(acc[37 + 4 * j]), __float_as_uint(acc[38 + 4 * j]), __float_as_uint(acc[39 + 4 * j]));
            bar_arrive(1, 256);
            #pragma unroll
            for (int j = 0; j < 36; j++) res[j] += acc[j];
            partial(0);
        }
        const int hh = keep ? 0 : 1;
        uint32_t o[18];
        #pragma unroll
        for (int j = 0; j < 18; j++) o[j] = pack2(res[2 * j], res[2 * j + 1]);
        const uint32_t ad = sm + K4_XS * K4_STAGE + 24576 + hh * 9216 + (w4 * 16 + ((lane >> 3) & 1) * 8 + (lane & 7)) * 144;
        #pragma unroll
        for (int j = 0; j < 4; j++) stsm4(ad + (lane >> 4) * 16 + j * 32, o[4 * j], o[4 * j + 1], o[4 * j + 2], o[4 * j + 3]);
        stsm2(ad + 128, o[16], o[17]);
        fence_async_smem();
        bar_arrive(4 + hh, 160);
    }
}

typedef CUresult (*EncFn)(CUtensorMap*, CUtensorMapDataType, cuuint32_t, void*, const cuuint64_t*, const cuuint64_t*, const cuuint32_t*,
                          const cuuint32_t*, CUtensorMapInterleave, CUtensorMapSwizzle, CUtensorMapL2promotion, CUtensorMapFloatOOBfill);

template <typename... KArgs, typename... Args>
static void launch(void (*kern)(KArgs...), dim3 grid, int block, int smem, bool pdl, Args... args) {
    cudaLaunchConfig_t cfg = {};
    cfg.gridDim = grid; cfg.blockDim = dim3(block); cfg.dynamicSmemBytes = smem; cfg.stream = cudaStreamPerThread;
    cudaLaunchAttribute at[1];
    at[0].id = cudaLaunchAttributeProgrammaticStreamSerialization; at[0].val.programmaticStreamSerializationAllowed = 1;
    cfg.attrs = at; cfg.numAttrs = pdl ? 1 : 0;
    cudaLaunchKernelEx(&cfg, kern, args...);
}

extern "C" void kernel_launch(void* const* d_in, const int* in_sizes, int n_in, void* d_out, int out_size) {
    const bf16* x = (const bf16*)d_in[0];
    const bf16* wqkv = (const bf16*)d_in[1];
    const bf16* wphi = (const bf16*)d_in[2];
    const bf16* wo = (const bf16*)d_in[3];
    const bf16* w1 = (const bf16*)d_in[5];
    const bf16* b1 = (const bf16*)d_in[6];
    const bf16* w2 = (const bf16*)d_in[7];
    const bf16* b2 = (const bf16*)d_in[8];
    static EncFn enc = nullptr;
    if (!enc) {
        void* fn = nullptr; cudaDriverEntryPointQueryResult qr;
        cudaGetDriverEntryPoint("cuTensorMapEncodeTiled", &fn, cudaEnableDefault, &qr);
        enc = (EncFn)fn;
        cudaFuncSetAttribute(ka_front, cudaFuncAttributeMaxDynamicSharedMemorySize, KA_SMEM);
        cudaFuncSetAttribute(k2_attn, cudaFuncAttributeMaxDynamicSharedMemorySize, K2_SMEM);
        cudaFuncSetAttribute(k3_mix1, cudaFuncAttributeMaxDynamicSharedMemorySize, K3_SMEM);
        cudaFuncSetAttribute(k4_mix2, cudaFuncAttributeMaxDynamicSharedMemorySize, K4_SMEM);
    }
    CUtensorMap tmW1, tmW1b, tmW2, tmOut, tmX, tmXA;
    const cuuint32_t es[3] = {1, 1, 1};
    {
        cuuint64_t dims[3] = {64, (cuuint64_t)S_, (cuuint64_t)(F_ / 64)}; cuuint64_t st[2] = {(cuuint64_t)F_ * 2, 128}; cuuint32_t box[3] = {64, 64, 2};
        enc(&tmW1, CU_TENSOR_MAP_DATA_TYPE_BFLOAT16, 3, (void*)w1, dims, st, box, es, CU_TENSOR_MAP_INTERLEAVE_NONE, CU_TENSOR_MAP_SWIZZLE_128B, CU_TENSOR_MAP_L2_PROMOTION_L2_128B, CU_TENSOR_MAP_FLOAT_OOB_FILL_NONE);
        box[2] = 3;
        enc(&tmW1b, CU_TENSOR_MAP_DATA_TYPE_BFLOAT16, 3, (void*)w1, dims, st, box, es, CU_TENSOR_MAP_INTERLEAVE_NONE, CU_TENSOR_MAP_SWIZZLE_128B, CU_TENSOR_MAP_L2_PROMOTION_L2_128B, CU_TENSOR_MAP_FLOAT_OOB_FILL_NONE);
    }
    {
        cuuint64_t dims[3] = {64, (cuuint64_t)F_, (cuuint64_t)(S_ / 64)}; cuuint64_t st[2] = {(cuuint64_t)S_ * 2, 128}; cuuint32_t box[3] = {64, 64, 1};
        enc(&tmW2, CU_TENSOR_MAP_DATA_TYPE_BFLOAT16, 3, (void*)w2, dims, st, box, es, CU_TENSOR_MAP_INTERLEAVE_NONE, CU_TENSOR_MAP_SWIZZLE_128B, CU_TENSOR_MAP_L2_PROMOTION_L2_128B, CU_TENSOR_MAP_FLOAT_OOB_FILL_NONE);
    }
    {
        cuuint64_t dims[2] = {(cuuint64_t)D_, (cuuint64_t)S_}; cuuint64_t st[1] = {(cuuint64_t)D_ * 2}; cuuint32_t box[2] = {72, 64};
        enc(&tmOut, CU_TENSOR_MAP_DATA_TYPE_BFLOAT16, 2, d_out, dims, st, box, es, CU_TENSOR_MAP_INTERLEAVE_NONE, CU_TENSOR_MAP_SWIZZLE_NONE, CU_TENSOR_MAP_L2_PROMOTION_NONE, CU_TENSOR_MAP_FLOAT_OOB_FILL_NONE);
        enc(&tmX, CU_TENSOR_MAP_DATA_TYPE_BFLOAT16, 2, (void*)x, dims, st, box, es, CU_TENSOR_MAP_INTERLEAVE_NONE, CU_TENSOR_MAP_SWIZZLE_NONE, CU_TENSOR_MAP_L2_PROMOTION_NONE, CU_TENSOR_MAP_FLOAT_OOB_FILL_NONE);
    }
    {
        cuuint64_t dims[3] = {64, (cuuint64_t)S_, 9}; cuuint64_t st[2] = {(cuuint64_t)D_ * 2, 128}; cuuint32_t box[3] = {64, 128, 1};
        enc(&tmXA, CU_TENSOR_MAP_DATA_TYPE_BFLOAT16, 3, (void*)x, dims, st, box, es, CU_TENSOR_MAP_INTERLEAVE_NONE, CU_TENSOR_MAP_SWIZZLE_128B, CU_TENSOR_MAP_L2_PROMOTION_L2_128B, CU_TENSOR_MAP_FLOAT_OOB_FILL_NONE);
    }
    launch(k0_prep, dim3(9, 8, 4), 256, 0, false, x, wqkv, wphi);
    launch(ka_front, 132, 640, KA_SMEM, true, tmXA, x, wo, w1, b1);
    launch(k2_attn, 128, 288, K2_SMEM, true, tmX, b2);
    launch(k3_mix1, 132, 288, K3_SMEM, true, tmW1, tmW1b, b1, w1, w2);
    launch(k4_mix2, 128, 288, K4_SMEM, true, tmW2, tmOut);
}
```

```cpp
#include <cuda_runtime.h>
#include <cuda.h>
#include <cuda_bf16.h>
#include <stdint.h>

typedef __nv_bfloat16 bf16;
#define DEVI __device__ __forceinline__

constexpr int S_ = 2048, D_ = 576, F_ = 4608;
constexpr float LN_EPS = 1e-5f;
constexpr float LOG2E = 1.4426950408889634f;

__device__ __align__(1024) bf16 g_o[S_ * D_];
__device__ __align__(1024) bf16 g_wqkv[8 * 27 * 72 * 64];
__device__ __align__(16) float g_cs[8 * 18 * 216];
__device__ __align__(1024) bf16 g_wo[8 * 72 * 72 * 8];
constexpr int KV_H = 960;
__device__ __align__(1024) float g_kv[32 * KV_H];
__device__ __align__(1024) unsigned long long g_stats[S_ * 8];
__device__ __align__(16) unsigned long long g_ln[S_];
__device__ __align__(16) float2 g_rc[S_];
__device__ __align__(1024) bf16 g_hnT[D_ * S_];
__device__ __align__(1024) bf16 g_u[D_ * F_];
constexpr int CNT_S = 64;
__device__ __align__(256) unsigned int g_cnt[8 * CNT_S];

DEVI uint32_t smem_u32(const void* p) { return (uint32_t)__cvta_generic_to_shared(p); }
DEVI void mbar_init(uint32_t bar, int cnt) { asm volatile("mbarrier.init.shared::cta.b64 [%0], %1;" :: "r"(bar), "r"(cnt) : "memory"); }
DEVI void mbar_expect(uint32_t bar, uint32_t bytes) { asm volatile("mbarrier.arrive.expect_tx.shared::cta.b64 _, [%0], %1;" :: "r"(bar), "r"(bytes) : "memory"); }
DEVI void mbar_wait(uint32_t bar, uint32_t parity) {
    asm volatile("{\n.reg .pred p;\n.reg .u32 it;\n"
                 "mbarrier.try_wait.parity.shared::cta.b64 p, [%0], %1;\n@p bra MW_DONE;\n"
                 "mov.u32 it, 0;\n"
                 "MW_LOOP:\nmbarrier.try_wait.parity.shared::cta.b64 p, [%0], %1;\n@p bra MW_DONE;\n"
                 "add.u32 it, it, 1;\nsetp.lt.u32 p, it, 4194304;\n@p bra MW_LOOP;\ntrap;\n"
                 "MW_DONE:\n}" :: "r"(bar), "r"(parity) : "memory");
}
DEVI void mbar_arrive(uint32_t bar) { asm volatile("mbarrier.arrive.shared::cta.b64 _, [%0];" :: "r"(bar) : "memory"); }
DEVI uint32_t mapa(uint32_t addr, uint32_t cta) { uint32_t r; asm volatile("mapa.shared::cluster.u32 %0, %1, %2;" : "=r"(r) : "r"(addr), "r"(cta)); return r; }
DEVI void mbar_arrive_remote(uint32_t raddr) { asm volatile("mbarrier.arrive.shared::cluster.b64 _, [%0];" :: "r"(raddr) : "memory"); }
DEVI void fence_mbar_init() { asm volatile("fence.mbarrier_init.release.cluster;" ::: "memory"); }
DEVI void fence_async_smem() { asm volatile("fence.proxy.async.shared::cta;" ::: "memory"); }
DEVI void cluster_arrive_relaxed() { asm volatile("barrier.cluster.arrive.relaxed.aligned;" ::: "memory"); }
DEVI void cluster_wait() { asm volatile("barrier.cluster.wait.aligned;" ::: "memory"); }
DEVI void bar_sync(int id, int n) { asm volatile("bar.sync %0, %1;" :: "r"(id), "r"(n) : "memory"); }
DEVI void bar_arrive(int id, int n) { asm volatile("bar.arrive %0, %1;" :: "r"(id), "r"(n) : "memory"); }
DEVI void pdl_wait() { asm volatile("griddepcontrol.wait;" ::: "memory"); }
DEVI void pdl_trigger() { asm volatile("griddepcontrol.launch_dependents;" ::: "memory"); }
DEVI void bulk_g2s(uint32_t dst, const void* src, uint32_t bytes, uint32_t bar) {
    asm volatile("cp.async.bulk.shared::cluster.global.mbarrier::complete_tx::bytes [%0], [%1], %2, [%3];" :: "r"(dst), "l"(src), "r"(bytes), "r"(bar) : "memory");
}
DEVI void bulk_s2g(void* dst, uint32_t src, uint32_t bytes) {
    asm volatile("cp.async.bulk.global.shared::cta.bulk_group [%0], [%1], %2;" :: "l"(dst), "r"(src), "r"(bytes) : "memory");
}
DEVI void l2_prefetch(const void* p, uint32_t bytes) { asm volatile("cp.async.bulk.prefetch.L2.global [%0], %1;" :: "l"(p), "r"(bytes) : "memory"); }
DEVI void bulk_commit() { asm volatile("cp.async.bulk.commit_group;" ::: "memory"); }
DEVI void bulk_wait_read() { asm volatile("cp.async.bulk.wait_group.read 0;" ::: "memory"); }
DEVI void tma2d(uint32_t dst, const CUtensorMap* tm, uint32_t bar, int c0, int c1) {
    asm volatile("cp.async.bulk.tensor.2d.shared::cluster.global.mbarrier::complete_tx::bytes [%0], [%1, {%3, %4}], [%2];" :: "r"(dst), "l"(tm), "r"(bar), "r"(c0), "r"(c1) : "memory");
}
DEVI void tma3d(uint32_t dst, const CUtensorMap* tm, uint32_t bar, int c0, int c1, int c2) {
    asm volatile("cp.async.bulk.tensor.3d.shared::cluster.global.mbarrier::complete_tx::bytes [%0], [%1, {%3, %4, %5}], [%2];" :: "r"(dst), "l"(tm), "r"(bar), "r"(c0), "r"(c1), "r"(c2) : "memory");
}
DEVI void tma3d_prefetch(const CUtensorMap* tm, int c0, int c1, int c2) {
    asm volatile("cp.async.bulk.prefetch.tensor.3d.L2.global [%0, {%1, %2, %3}];" :: "l"(tm), "r"(c0), "r"(c1), "r"(c2) : "memory");
}
DEVI void tma2d_store(const CUtensorMap* tm, uint32_t src, int c0, int c1) {
    asm volatile("cp.async.bulk.tensor.2d.global.shared::cta.bulk_group [%0, {%2, %3}], [%1];" :: "l"(tm), "r"(src), "r"(c0), "r"(c1) : "memory");
}
DEVI void prefetch_tm(const CUtensorMap* tm) { asm volatile("prefetch.tensormap [%0];" :: "l"(tm) : "memory"); }
DEVI uint64_t mkdesc(uint32_t addr, uint32_t lbo, uint32_t sbo, uint64_t swz) {
    return (uint64_t)((addr & 0x3FFFF) >> 4) | ((uint64_t)(lbo >> 4) << 16) | ((uint64_t)(sbo >> 4) << 32) | (swz << 62);
}
DEVI uint64_t dadv(uint64_t d, uint32_t bytes) { return (d & 0xffffffff00000000ull) | (uint64_t)((uint32_t)d + (bytes >> 4)); }
DEVI void wg_fence() { asm volatile("wgmma.fence.sync.aligned;" ::: "memory"); }
DEVI void wg_commit() { asm volatile("wgmma.commit_group.sync.aligned;" ::: "memory"); }
template<int N> DEVI void wg_wait() { asm volatile("wgmma.wait_group.sync.aligned %0;" :: "n"(N) : "memory"); }
template<int N> DEVI void reg_fence(float* d) {
    #pragma unroll
    for (int i = 0; i < N; i++) asm volatile("" : "+f"(d[i]) :: "memory");
}
DEVI uint32_t pack2(float lo, float hi) { uint32_t r; asm("cvt.rn.bf16x2.f32 %0, %1, %2;" : "=r"(r) : "f"(hi), "f"(lo)); return r; }
DEVI float bf_lo(uint32_t v) { return __uint_as_float(v << 16); }
DEVI float bf_hi(uint32_t v) { return __uint_as_float(v & 0xffff0000u); }
DEVI float ex2(float x) { float r; asm("ex2.approx.ftz.f32 %0, %1;" : "=f"(r) : "f"(x)); return r; }
DEVI float rcp(float x) { float r; asm("rcp.approx.ftz.f32 %0, %1;" : "=f"(r) : "f"(x)); return r; }
DEVI float rcp_full(float x) { float r; asm("rcp.approx.f32 %0, %1;" : "=f"(r) : "f"(x)); return r; }
DEVI float tanh_fast(float x) { float r; asm("tanh.approx.f32 %0, %1;" : "=f"(r) : "f"(x)); return r; }
DEVI void mma16816(float* c, uint32_t a0, uint32_t a1, uint32_t a2, uint32_t a3, uint32_t b0, uint32_t b1) {
    asm("mma.sync.aligned.m16n8k16.row.col.f32.bf16.bf16.f32 {%0,%1,%2,%3}, {%4,%5,%6,%7}, {%8,%9}, {%0,%1,%2,%3};"
        : "+f"(c[0]), "+f"(c[1]), "+f"(c[2]), "+f"(c[3]) : "r"(a0), "r"(a1), "r"(a2), "r"(a3), "r"(b0), "r"(b1));
}
DEVI void mma1688(float* c, uint32_t a0, uint32_t a1, uint32_t b0) {
    asm("mma.sync.aligned.m16n8k8.row.col.f32.bf16.bf16.f32 {%0,%1,%2,%3}, {%4,%5}, {%6}, {%0,%1,%2,%3};"
        : "+f"(c[0]), "+f"(c[1]), "+f"(c[2]), "+f"(c[3]) : "r"(a0), "r"(a1), "r"(b0));
}
DEVI void ldsm4t(uint32_t addr, uint32_t& r0, uint32_t& r1, uint32_t& r2, uint32_t& r3) {
    asm volatile("ldmatrix.sync.aligned.m8n8.x4.trans.shared.b16 {%0,%1,%2,%3}, [%4];" : "=r"(r0), "=r"(r1), "=r"(r2), "=r"(r3) : "r"(addr) : "memory");
}
DEVI void stsm4(uint32_t addr, uint32_t r0, uint32_t r1, uint32_t r2, uint32_t r3) {
    asm volatile("stmatrix.sync.aligned.m8n8.x4.shared.b16 [%0], {%1,%2,%3,%4};" :: "r"(addr), "r"(r0), "r"(r1), "r"(r2), "r"(r3) : "memory");
}
DEVI void stsm2(uint32_t addr, uint32_t r0, uint32_t r1) {
    asm volatile("stmatrix.sync.aligned.m8n8.x2.shared.b16 [%0], {%1,%2};" :: "r"(addr), "r"(r0), "r"(r1) : "memory");
}
DEVI void sts128(uint32_t addr, uint32_t r0, uint32_t r1, uint32_t r2, uint32_t r3) {
    asm volatile("st.shared.v4.b32 [%0], {%1,%2,%3,%4};" :: "r"(addr), "r"(r0), "r"(r1), "r"(r2), "r"(r3) : "memory");
}
DEVI void sts32(uint32_t addr, uint32_t r0) { asm volatile("st.shared.b32 [%0], %1;" :: "r"(addr), "r"(r0) : "memory"); }
DEVI void wgmma_rs_n80(float* d, uint32_t a0, uint32_t a1, uint32_t a2, uint32_t a3, uint64_t db, int sd) {
  asm volatile("{\n.reg .pred p;\nsetp.ne.b32 p, %45, 0;\n"
    "wgmma.mma_async.sync.aligned.m64n80k16.f32.bf16.bf16 {%0, %1, %2, %3, %4, %5, %6, %7, %8, %9, %10, %11, %12, %13, %14, %15, %16, %17, %18, %19, %20, %21, %22, %23, %24, %25, %26, %27, %28, %29, %30, %31, %32, %33, %34, %35, %36, %37, %38, %39}, {%40, %41, %42, %43}, %44, p, 1, 1, 0;\n}\n"
    : "+f"(d[0]), "+f"(d[1]), "+f"(d[2]), "+f"(d[3]), "+f"(d[4]), "+f"(d[5]), "+f"(d[6]), "+f"(d[7]), "+f"(d[8]), "+f"(d[9]), "+f"(d[10]), "+f"(d[11]), "+f"(d[12]), "+f"(d[13]), "+f"(d[14]), "+f"(d[15]), "+f"(d[16]), "+f"(d[17]), "+f"(d[18]), "+f"(d[19]), "+f"(d[20]), "+f"(d[21]), "+f"(d[22]), "+f"(d[23]), "+f"(d[24]), "+f"(d[25]), "+f"(d[26]), "+f"(d[27]), "+f"(d[28]), "+f"(d[29]), "+f"(d[30]), "+f"(d[31]), "+f"(d[32]), "+f"(d[33]), "+f"(d[34]), "+f"(d[35]), "+f"(d[36]), "+f"(d[37]), "+f"(d[38]), "+f"(d[39]) : "r"(a0), "r"(a1), "r"(a2), "r"(a3), "l"(db), "r"(sd));
}
template<int TA, int TB> DEVI void wgmma_n40(float* d, uint64_t da, uint64_t db, int sd) {
  asm volatile("{\n.reg .pred p;\nsetp.ne.b32 p, %22, 0;\n"
    "wgmma.mma_async.sync.aligned.m64n40k16.f32.bf16.bf16 {%0, %1, %2, %3, %4, %5, %6, %7, %8, %9, %10, %11, %12, %13, %14, %15, %16, %17, %18, %19}, %20, %21, p, 1, 1, %23, %24;\n}\n"
    : "+f"(d[0]), "+f"(d[1]), "+f"(d[2]), "+f"(d[3]), "+f"(d[4]), "+f"(d[5]), "+f"(d[6]), "+f"(d[7]), "+f"(d[8]), "+f"(d[9]), "+f"(d[10]), "+f"(d[11]), "+f"(d[12]), "+f"(d[13]), "+f"(d[14]), "+f"(d[15]), "+f"(d[16]), "+f"(d[17]), "+f"(d[18]), "+f"(d[19]) : "l"(da), "l"(db), "r"(sd), "n"(TA), "n"(TB));
}
template<int TA, int TB> DEVI void wgmma_n48(float* d, uint64_t da, uint64_t db, int sd) {
  asm volatile("{\n.reg .pred p;\nsetp.ne.b32 p, %26, 0;\n"
    "wgmma.mma_async.sync.aligned.m64n48k16.f32.bf16.bf16 {%0, %1, %2, %3, %4, %5, %6, %7, %8, %9, %10, %11, %12, %13, %14, %15, %16, %17, %18, %19, %20, %21, %22, %23}, %24, %25, p, 1, 1, %27, %28;\n}\n"
    : "+f"(d[0]), "+f"(d[1]), "+f"(d[2]), "+f"(d[3]), "+f"(d[4]), "+f"(d[5]), "+f"(d[6]), "+f"(d[7]), "+f"(d[8]), "+f"(d[9]), "+f"(d[10]), "+f"(d[11]), "+f"(d[12]), "+f"(d[13]), "+f"(d[14]), "+f"(d[15]), "+f"(d[16]), "+f"(d[17]), "+f"(d[18]), "+f"(d[19]), "+f"(d[20]), "+f"(d[21]), "+f"(d[22]), "+f"(d[23]) : "l"(da), "l"(db), "r"(sd), "n"(TA), "n"(TB));
}
template<int TA, int TB> DEVI void wgmma_n72(float* d, uint64_t da, uint64_t db, int sd) {
  asm volatile("{\n.reg .pred p;\nsetp.ne.b32 p, %38, 0;\n"
    "wgmma.mma_async.sync.aligned.m64n72k16.f32.bf16.bf16 {%0, %1, %2, %3, %4, %5, %6, %7, %8, %9, %10, %11, %12, %13, %14, %15, %16, %17, %18, %19, %20, %21, %22, %23, %24, %25, %26, %27, %28, %29, %30, %31, %32, %33, %34, %35}, %36, %37, p, 1, 1, %39, %40;\n}\n"
    : "+f"(d[0]), "+f"(d[1]), "+f"(d[2]), "+f"(d[3]), "+f"(d[4]), "+f"(d[5]), "+f"(d[6]), "+f"(d[7]), "+f"(d[8]), "+f"(d[9]), "+f"(d[10]), "+f"(d[11]), "+f"(d[12]), "+f"(d[13]), "+f"(d[14]), "+f"(d[15]), "+f"(d[16]), "+f"(d[17]), "+f"(d[18]), "+f"(d[19]), "+f"(d[20]), "+f"(d[21]), "+f"(d[22]), "+f"(d[23]), "+f"(d[24]), "+f"(d[25]), "+f"(d[26]), "+f"(d[27]), "+f"(d[28]), "+f"(d[29]), "+f"(d[30]), "+f"(d[31]), "+f"(d[32]), "+f"(d[33]), "+f"(d[34]), "+f"(d[35]) : "l"(da), "l"(db), "r"(sd), "n"(TA), "n"(TB));
}
template<int TA, int TB> DEVI void wgmma_n96(float* d, uint64_t da, uint64_t db, int sd) {
  asm volatile("{\n.reg .pred p;\nsetp.ne.b32 p, %50, 0;\n"
    "wgmma.mma_async.sync.aligned.m64n96k16.f32.bf16.bf16 {%0, %1, %2, %3, %4, %5, %6, %7, %8, %9, %10, %11, %12, %13, %14, %15, %16, %17, %18, %19, %20, %21, %22, %23, %24, %25, %26, %27, %28, %29, %30, %31, %32, %33, %34, %35, %36, %37, %38, %39, %40, %41, %42, %43, %44, %45, %46, %47}, %48, %49, p, 1, 1, %51, %52;\n}\n"
    : "+f"(d[0]), "+f"(d[1]), "+f"(d[2]), "+f"(d[3]), "+f"(d[4]), "+f"(d[5]), "+f"(d[6]), "+f"(d[7]), "+f"(d[8]), "+f"(d[9]), "+f"(d[10]), "+f"(d[11]), "+f"(d[12]), "+f"(d[13]), "+f"(d[14]), "+f"(d[15]), "+f"(d[16]), "+f"(d[17]), "+f"(d[18]), "+f"(d[19]), "+f"(d[20]), "+f"(d[21]), "+f"(d[22]), "+f"(d[23]), "+f"(d[24]), "+f"(d[25]), "+f"(d[26]), "+f"(d[27]), "+f"(d[28]), "+f"(d[29]), "+f"(d[30]), "+f"(d[31]), "+f"(d[32]), "+f"(d[33]), "+f"(d[34]), "+f"(d[35]), "+f"(d[36]), "+f"(d[37]), "+f"(d[38]), "+f"(d[39]), "+f"(d[40]), "+f"(d[41]), "+f"(d[42]), "+f"(d[43]), "+f"(d[44]), "+f"(d[45]), "+f"(d[46]), "+f"(d[47]) : "l"(da), "l"(db), "r"(sd), "n"(TA), "n"(TB));
}
template<int TA, int TB> DEVI void wgmma_n144(float* d, uint64_t da, uint64_t db, int sd) {
  asm volatile("{\n.reg .pred p;\nsetp.ne.b32 p, %74, 0;\n"
    "wgmma.mma_async.sync.aligned.m64n144k16.f32.bf16.bf16 {%0, %1, %2, %3, %4, %5, %6, %7, %8, %9, %10, %11, %12, %13, %14, %15, %16, %17, %18, %19, %20, %21, %22, %23, %24, %25, %26, %27, %28, %29, %30, %31, %32, %33, %34, %35, %36, %37, %38, %39, %40, %41, %42, %43, %44, %45, %46, %47, %48, %49, %50, %51, %52, %53, %54, %55, %56, %57, %58, %59, %60, %61, %62, %63, %64, %65, %66, %67, %68, %69, %70, %71}, %72, %73, p, 1, 1, %75, %76;\n}\n"
    : "+f"(d[0]), "+f"(d[1]), "+f"(d[2]), "+f"(d[3]), "+f"(d[4]), "+f"(d[5]), "+f"(d[6]), "+f"(d[7]), "+f"(d[8]), "+f"(d[9]), "+f"(d[10]), "+f"(d[11]), "+f"(d[12]), "+f"(d[13]), "+f"(d[14]), "+f"(d[15]), "+f"(d[16]), "+f"(d[17]), "+f"(d[18]), "+f"(d[19]), "+f"(d[20]), "+f"(d[21]), "+f"(d[22]), "+f"(d[23]), "+f"(d[24]), "+f"(d[25]), "+f"(d[26]), "+f"(d[27]), "+f"(d[28]), "+f"(d[29]), "+f"(d[30]), "+f"(d[31]), "+f"(d[32]), "+f"(d[33]), "+f"(d[34]), "+f"(d[35]), "+f"(d[36]), "+f"(d[37]), "+f"(d[38]), "+f"(d[39]), "+f"(d[40]), "+f"(d[41]), "+f"(d[42]), "+f"(d[43]), "+f"(d[44]), "+f"(d[45]), "+f"(d[46]), "+f"(d[47]), "+f"(d[48]), "+f"(d[49]), "+f"(d[50]), "+f"(d[51]), "+f"(d[52]), "+f"(d[53]), "+f"(d[54]), "+f"(d[55]), "+f"(d[56]), "+f"(d[57]), "+f"(d[58]), "+f"(d[59]), "+f"(d[60]), "+f"(d[61]), "+f"(d[62]), "+f"(d[63]), "+f"(d[64]), "+f"(d[65]), "+f"(d[66]), "+f"(d[67]), "+f"(d[68]), "+f"(d[69]), "+f"(d[70]), "+f"(d[71]) : "l"(da), "l"(db), "r"(sd), "n"(TA), "n"(TB));
}
template<int TA, int TB> DEVI void wgmma_n160(float* d, uint64_t da, uint64_t db, int sd) {
  asm volatile("{\n.reg .pred p;\nsetp.ne.b32 p, %82, 0;\n"
    "wgmma.mma_async.sync.aligned.m64n160k16.f32.bf16.bf16 {%0, %1, %2, %3, %4, %5, %6, %7, %8, %9, %10, %11, %12, %13, %14, %15, %16, %17, %18, %19, %20, %21, %22, %23, %24, %25, %26, %27, %28, %29, %30, %31, %32, %33, %34, %35, %36, %37, %38, %39, %40, %41, %42, %43, %44, %45, %46, %47, %48, %49, %50, %51, %52, %53, %54, %55, %56, %57, %58, %59, %60, %61, %62, %63, %64, %65, %66, %67, %68, %69, %70, %71, %72, %73, %74, %75, %76, %77, %78, %79}, %80, %81, p, 1, 1, %83, %84;\n}\n"
    : "+f"(d[0]), "+f"(d[1]), "+f"(d[2]), "+f"(d[3]), "+f"(d[4]), "+f"(d[5]), "+f"(d[6]), "+f"(d[7]), "+f"(d[8]), "+f"(d[9]), "+f"(d[10]), "+f"(d[11]), "+f"(d[12]), "+f"(d[13]), "+f"(d[14]), "+f"(d[15]), "+f"(d[16]), "+f"(d[17]), "+f"(d[18]), "+f"(d[19]), "+f"(d[20]), "+f"(d[21]), "+f"(d[22]), "+f"(d[23]), "+f"(d[24]), "+f"(d[25]), "+f"(d[26]), "+f"(d[27]), "+f"(d[28]), "+f"(d[29]), "+f"(d[30]), "+f"(d[31]), "+f"(d[32]), "+f"(d[33]), "+f"(d[34]), "+f"(d[35]), "+f"(d[36]), "+f"(d[37]), "+f"(d[38]), "+f"(d[39]), "+f"(d[40]), "+f"(d[41]), "+f"(d[42]), "+f"(d[43]), "+f"(d[44]), "+f"(d[45]), "+f"(d[46]), "+f"(d[47]), "+f"(d[48]), "+f"(d[49]), "+f"(d[50]), "+f"(d[51]), "+f"(d[52]), "+f"(d[53]), "+f"(d[54]), "+f"(d[55]), "+f"(d[56]), "+f"(d[57]), "+f"(d[58]), "+f"(d[59]), "+f"(d[60]), "+f"(d[61]), "+f"(d[62]), "+f"(d[63]), "+f"(d[64]), "+f"(d[65]), "+f"(d[66]), "+f"(d[67]), "+f"(d[68]), "+f"(d[69]), "+f"(d[70]), "+f"(d[71]), "+f"(d[72]), "+f"(d[73]), "+f"(d[74]), "+f"(d[75]), "+f"(d[76]), "+f"(d[77]), "+f"(d[78]), "+f"(d[79]) : "l"(da), "l"(db), "r"(sd), "n"(TA), "n"(TB));
}

__host__ __device__ constexpr int ka_seq(int p, int c) { return p == 0 ? c : c >= 5 ? 2 * c - 2 + p : p == 1 ? 17 + c : 22 + c; }
__global__ void __launch_bounds__(256, 3) k0_prep(const bf16* __restrict__ x, const bf16* __restrict__ wqkv, const bf16* __restrict__ wphi) {
    __shared__ __align__(16) uint32_t s_in[64 * 36 + 64];
    pdl_trigger();
    const int tid = threadIdx.x, lane = tid & 31, warp = __shfl_sync(~0u, tid >> 5, 0);
    const int c = blockIdx.x, g = blockIdx.y, p = blockIdx.z;
    const bool fold = p == 0 || p == 2;
    const int b = (p * 8 + g) * 9 + c;
    if (p == 3) {
        const int j = b - 216;
        const uint4 z = make_uint4(0u, 0u, 0u, 0u);
        if (j < 32) reinterpret_cast<uint4*>(g_stats)[j * 256 + tid] = z;
        else if (j < 62) reinterpret_cast<uint4*>(g_kv)[(j - 32) * 256 + tid] = z;
        else if (j == 66 && tid < 8) g_cnt[tid * CNT_S] = 0u;
        return;
    }
    constexpr int ld = 1728;
    const bf16* src = wqkv + ((p == 2 ? 0 : p + 1) * 576 + c * 64 * ld + g * 72);
    const uint32_t si = smem_u32(s_in);
    #pragma unroll
    for (int j = 0; j < 3; j++) {
        const int i = tid + j * 256, r = (i * 7282) >> 16;
        if (j < 2 || tid < 64) asm volatile("cp.async.cg.shared.global [%0], [%1], 16;" :: "r"(si + i * 16 + (r >> 3) * 32), "l"(src + (r * (ld - 72) + i * 8)) : "memory");
    }
    const int t = warp & 3, half = warp >> 2, g8 = lane >> 2, c4 = lane & 3;
    uint32_t af[3][3];
    if (fold) {
        const unsigned short* ph = reinterpret_cast<const unsigned short*>(wphi) + (g * 4 + t) * 324;
        unsigned short lo[3][3], hi[3][3];
        #pragma unroll
        for (int fb = 0; fb < 3; fb++)
            #pragma unroll
            for (int db = 0; db < 3; db++) {
                const int o = min(2 * c4 + 8 * db, 16) * 18 + min(g8 + 8 * fb, 17);
                lo[fb][db] = __ldg(ph + o); hi[fb][db] = __ldg(ph + o + 18);
            }
        #pragma unroll
        for (int fb = 0; fb < 3; fb++)
            #pragma unroll
            for (int db = 0; db < 3; db++) af[fb][db] = (uint32_t)lo[fb][db] | ((uint32_t)hi[fb][db] << 16);
    } else {
        const uint32_t v = (g8 == 2 * c4 ? 0x3f80u : 0u) | (g8 == 2 * c4 + 1 ? 0x3f800000u : 0u);
        #pragma unroll
        for (int fb = 0; fb < 3; fb++)
            #pragma unroll
            for (int db = 0; db < 3; db++) af[fb][db] = fb == db ? v : 0u;
    }
    bf16* dst = g_wqkv + (g * 27 + ka_seq(p, c)) * 4608;
    float* csd = g_cs + (g * 18 + c * 2 + half) * 216 + p * 72 + 2 * t;
    asm volatile("cp.async.wait_all;" ::: "memory");
    __syncthreads();
    if (tid < 96 && b < 192) asm volatile("prefetch.global.L2 [%0];" :: "l"(x + b * 6144 + tid * 64));
    uint32_t ov[3][4];
    const uint32_t* wr = &s_in[(half * 32 + (g8 >> 1) * 8 + (g8 & 1)) * 36 + (half * 4 + (g8 >> 1)) * 8 + t * 9 + c4];
    #pragma unroll
    for (int j = 0; j < 4; j++) {
        const uint32_t b0 = wr[j * 72], b1 = wr[j * 72 + 4], b2 = c4 == 0 ? wr[j * 72 + 8] : 0u;
        float c0[4] = {0.f, 0.f, 0.f, 0.f}, c1[4] = {0.f, 0.f, 0.f, 0.f};
        mma16816(c0, af[0][0], af[1][0], af[0][1], af[1][1], b0, b1);
        mma1688(c0, af[0][2], af[1][2], b2);
        mma16816(c1, af[2][0], 0u, af[2][1], 0u, b0, b1);
        mma1688(c1, af[2][2], 0u, b2);
        ov[0][j] = pack2(c0[0], c0[1]); ov[1][j] = pack2(c0[2], c0[3]); ov[2][j] = pack2(c1[0], c1[1]);
    }
    {
        const int nl = 2 * t + (g8 & 1);
        uint4* o = reinterpret_cast<uint4*>(dst) + ((g8 >> 1) * 8 + nl) * 8 + ((half * 4 + c4) ^ nl);
        o[0] = make_uint4(ov[0][0], ov[0][1], ov[0][2], ov[0][3]);
        o[256] = make_uint4(ov[1][0], ov[1][1], ov[1][2], ov[1][3]);
        if (g8 < 2) o[512] = make_uint4(ov[2][0], ov[2][1], ov[2][2], ov[2][3]);
    }
    {
        float cs0[4] = {0.f, 0.f, 0.f, 0.f}, cs1[4] = {0.f, 0.f, 0.f, 0.f};
        mma16816(cs0, ov[0][0], ov[1][0], ov[0][1], ov[1][1], 0x3f803f80u, 0x3f803f80u);
        mma16816(cs1, ov[2][0], 0u, ov[2][1], 0u, 0x3f803f80u, 0x3f803f80u);
        mma16816(cs0, ov[0][2], ov[1][2], ov[0][3], ov[1][3], 0x3f803f80u, 0x3f803f80u);
        mma16816(cs1, ov[2][2], 0u, ov[2][3], 0u, 0x3f803f80u, 0x3f803f80u);
        const int f = g8 + 8 * c4;
        if (f < 18) csd[8 * (f >> 1) + (f & 1)] = c4 == 0 ? cs0[0] : c4 == 1 ? cs0[2] : cs1[0];
    }
}

DEVI void dual_softmax(const float* a, float scale, uint32_t* o) {
    float mx = a[0], mn = a[0];
    #pragma unroll
    for (int j = 1; j < 18; j++) { mx = fmaxf(mx, a[j]); mn = fminf(mn, a[j]); }
    const float mxs = -mx * scale, mns = mn * scale;
    float ep[18], en[18], sp = 0.f, sn = 0.f;
    #pragma unroll
    for (int j = 0; j < 18; j++) {
        ep[j] = ex2(fmaf(a[j], scale, mxs)); sp += ep[j];
        en[j] = ex2(fmaf(a[j], -scale, mns)); sn += en[j];
    }
    const float rp = rcp(sp), rn = rcp(sn);
    #pragma unroll
    for (int j = 0; j < 9; j++) {
        o[j] = pack2(ep[2 * j] * rp, ep[2 * j + 1] * rp);
        o[9 + j] = pack2(en[2 * j] * rn, en[2 * j + 1] * rn);
    }
}

DEVI uint4 ldg128(const void* p) { uint4 v; asm volatile("ld.global.cg.v4.u32 {%0,%1,%2,%3}, [%4];" : "=r"(v.x), "=r"(v.y), "=r"(v.z), "=r"(v.w) : "l"(p)); return v; }
DEVI uint2 ldg64(const void* p) { uint2 v; asm volatile("ld.global.cg.v2.u32 {%0,%1}, [%2];" : "=r"(v.x), "=r"(v.y) : "l"(p)); return v; }
DEVI uint4 lds128(uint32_t a) { uint4 v; asm volatile("ld.shared.v4.u32 {%0,%1,%2,%3}, [%4];" : "=r"(v.x), "=r"(v.y), "=r"(v.z), "=r"(v.w) : "r"(a) : "memory"); return v; }
DEVI uint2 lds64(uint32_t a) { uint2 v; asm volatile("ld.shared.v2.u32 {%0,%1}, [%2];" : "=r"(v.x), "=r"(v.y) : "r"(a) : "memory"); return v; }
DEVI uint32_t packu(uint32_t lo, uint32_t hi) { return pack2(__uint_as_float(lo), __uint_as_float(hi)); }
DEVI void spin_ge(const unsigned int* p, unsigned int n) {
    uint32_t f; int it = 0;
    do {
        asm volatile("ld.acquire.gpu.global.u32 %0, [%1];" : "=r"(f) : "l"(p) : "memory");
        if (++it > (1 << 22)) __trap();
    } while (f < n);
}
constexpr int KA_PRE = 3, KA_REC = 5 * 16384, KA_B = 147456, KA_CS = KA_B + 9 * 9216, KA_LN = KA_CS + 864, KA_BAR = KA_LN + 1024, KA_SMEM = KA_BAR + 160;
static_assert(KA_SMEM <= 232448, "smem");
DEVI void ka_kv(uint32_t recs, float* kvh, int w4, int lane) {
    float ck[2][20];
    const uint64_t dr = mkdesc(recs, 8192, 1024, 1);
    wg_fence();
    #pragma unroll
    for (int ks = 0; ks < 4; ks++)
        #pragma unroll
        for (int hh = 0; hh < 2; hh++) wgmma_n40<1, 1>(ck[hh], dadv(dr, hh * 8192 + ks * 2048), dadv(dr, hh * 8192 + ks * 2048), ks != 0);
    wg_commit();
    wg_wait<0>();
    reg_fence<20>(ck[0]); reg_fence<20>(ck[1]);
    if (w4 >= 2) {
        #pragma unroll
        for (int e = 1; e >= 0; e--) {
            const int nt = 2 * w4 + e - 5;
            if (nt >= 0 && (nt < 2 || lane < 12)) {
                float* p = kvh + nt * 320;
                float q[10];
                #pragma unroll
                for (int j = 0; j < 10; j++) q[j] = ck[0][(j >> 1) * 4 + 2 * e + (j & 1)] + ck[1][(j >> 1) * 4 + 2 * e + (j & 1)];
                asm volatile("red.global.add.v4.f32 [%0], {%1, %2, %3, %4};" :: "l"(p + lane * 4), "f"(q[0]), "f"(q[1]), "f"(q[2]), "f"(q[3]) : "memory");
                asm volatile("red.global.add.v4.f32 [%0], {%1, %2, %3, %4};" :: "l"(p + 128 + lane * 4), "f"(q[4]), "f"(q[5]), "f"(q[6]), "f"(q[7]) : "memory");
                if ((lane & 3) < 2) asm volatile("red.global.add.v2.f32 [%0], {%1, %2};" :: "l"(p + 256 + lane * 2), "f"(q[8]), "f"(q[9]) : "memory");
            }
        }
        __syncwarp();
        bar_arrive(2, 288);
    }
}
DEVI int gpc_pos() {
    unsigned smid, nsm;
    asm volatile("mov.u32 %0, %%smid;" : "=r"(smid));
    asm volatile("mov.u32 %0, %%nsmid;" : "=r"(nsm));
    if (nsm != 132) return blockIdx.x;
    const int tpc = smid >> 1, o = smid & 1;
    if (smid == 13 || smid == 15) return 124 + tpc;
    if (tpc < 32) return (tpc & 7) * 16 + (tpc >> 3) * 2 + o;
    if (tpc < 60) { const int j = tpc - 32, r = j / 7; return (1 + j - r * 7) * 16 + 8 + r * 2 + o; }
    if (tpc < 62) return o ? 68 + tpc : (tpc - 54) * 16 + 1;
    return 8 + (tpc - 62) * 2 + o;
}
__global__ void __launch_bounds__(640, 1) ka_front(const __grid_constant__ CUtensorMap tmXA, const bf16* __restrict__ x, const bf16* __restrict__ wo, const bf16* __restrict__ w1, const bf16* __restrict__ b1) {
    extern __shared__ __align__(1024) char smem[];
    const uint32_t sm = smem_u32(smem);
    const uint32_t bFull = sm + KA_BAR, bEmpty = bFull + 9 * 8, bLn = bEmpty + 9 * 8;
    const int tid = threadIdx.x, lane = tid & 31, warp = __shfl_sync(~0u, tid >> 5, 0);
    const int pos = gpc_pos();
    if (pos >= 128) {
        const int ns = pos - 128;
        if (tid == 0) {
            #pragma unroll
            for (int q = 0; q < 6; q++) mbar_init(bFull + q * 8, 1);
            fence_mbar_init();
            #pragma unroll
            for (int q = 0; q < 6; q++) mbar_expect(bFull + q * 8, 96 * 288);
        }
        __syncthreads();
        if (tid < 576) {
            const int h = tid / 18, d = tid - h * 18, r = (h >> 2) * 72 + (d >> 1) * 8 + 2 * (h & 3) + (d & 1);
            bulk_g2s(sm + r * 304, wo + tid * 576 + ns * 144, 288, bFull + (r / 96) * 8);
        }
        #pragma unroll 1
        for (int q = 0; q < 6; q++) {
            const uint32_t ob = sm + 175104 + (q & 1) * 27648;
            mbar_wait(bFull + q * 8, 0);
            if (tid == 0) asm volatile("cp.async.bulk.wait_group.read 1;" ::: "memory");
            __syncthreads();
            if (warp < 18) {
                #pragma unroll
                for (int rb = 0; rb < 3; rb++) {
                    uint32_t r0, r1, r2, r3;
                    ldsm4t(sm + (q * 96 + rb * 32 + lane) * 304 + warp * 16, r0, r1, r2, r3);
                    stsm4(ob + (warp / 9) * 13824 + ((rb * 4 + (lane >> 3)) * 72 + (warp % 9) * 8 + (lane & 7)) * 16, r0, r1, r2, r3);
                }
            }
            fence_async_smem();
            __syncthreads();
            if (tid == 0) {
                bulk_s2g(g_wo + (ns * 2) * (72 * 576) + q * 6912, ob, 13824);
                bulk_s2g(g_wo + (ns * 2 + 1) * (72 * 576) + q * 6912, ob + 13824, 13824);
                bulk_commit();
            }
        }
        if (tid == 0) {
            asm volatile("cp.async.bulk.wait_group 0;\nfence.proxy.async.global;\nfence.acq_rel.gpu;" ::: "memory");
            pdl_wait();
            pdl_trigger();
        }
        return;
    }
    const int g = ((pos >> 4) & 1) * 4 + (pos & 3), mt = (pos >> 5) * 4 + ((pos >> 2) & 3);
    if (warp >= 16) {
        asm volatile("setmaxnreg.dec.sync.aligned.u32 32;");
        if (warp == 16) {
            if (lane == 0) {
                #pragma unroll
                for (int c = 0; c < 9; c++) { mbar_init(bFull + c * 8, 1); mbar_init(bEmpty + c * 8, 8); }
                mbar_init(bLn, 64);
                fence_mbar_init();
            }
            __syncwarp();
            bar_arrive(0, 640);
        } else {
            bar_sync(0, 640);
            if (tid == 544) {
                #pragma unroll
                for (int c = 0; c < 9; c++) mbar_expect(bFull + c * 8, 16384 + 9216);
            }
            __syncwarp();
        }
        if (tid == 512) {
            #pragma unroll
            for (int c = 0; c < KA_PRE; c++) tma3d(sm + c * 16384, &tmXA, bFull + c * 8, 0, mt * 128, c);
            pdl_wait();
            const bf16* wsrc = g_wqkv + g * (27 * 4608);
            const uint32_t sb = sm + KA_B;
            #pragma unroll
            for (int c = 0; c < 9; c++) {
                bulk_g2s(sb + c * 9216, wsrc + c * 4608, 9216, bFull + c * 8);
                const int xc = c + KA_PRE - 2;
                if (c >= 2 && xc < 9) tma3d(sm + xc * 16384, &tmXA, bFull + xc * 8, 0, mt * 128, xc);
            }
            pdl_trigger();
            #pragma unroll 1
            for (int p = 1; p < 3; p++) {
                #pragma unroll
                for (int c = 0; c < 9; c++) {
                    mbar_wait(bEmpty + c * 8, p - 1); mbar_expect(bFull + c * 8, 9216);
                    bulk_g2s(sb + c * 9216, wsrc + (p * 9 + c) * 4608, 9216, bFull + c * 8);
                }
            }
            l2_prefetch(w1 + pos * 13824, 27648);
            if (pos == 0) l2_prefetch(b1, 9216);
        } else if (warp == 17) {
            bar_sync(2, 288);
            if (lane == 0) {
                asm volatile("red.release.gpu.global.add.u32 [%0], 1;" :: "l"(g_cnt + g * CNT_S) : "memory");
                spin_ge(g_cnt + g * CNT_S, 16);
            }
            __syncwarp();
            bar_arrive(1, 288);
        } else if (warp >= 18) {
            const int m = warp - 18;
            {
                const unsigned long long* lp = g_ln + mt * 128 + m * 64 + (lane >> 3) * 16 + (lane & 7);
                unsigned long long r0, r1; int it = 0;
                __nanosleep(700);
                while (true) {
                    asm volatile("ld.relaxed.gpu.global.u64 %0, [%1];" : "=l"(r0) : "l"(lp) : "memory");
                    asm volatile("ld.relaxed.gpu.global.u64 %0, [%1];" : "=l"(r1) : "l"(lp + 8) : "memory");
                    if (__all_sync(~0u, (long long)(r0 & r1) < 0)) break;
                    if (++it > (1 << 22)) __trap();
                }
                sts128(sm + KA_LN + (m * 32 + lane) * 16, (uint32_t)r0, (uint32_t)(r0 >> 32), (uint32_t)r1, (uint32_t)(r1 >> 32));
                mbar_arrive(bLn);
            }
        }
    } else {
        const int xrow = mt * 128 + g * 16 + warp;
        uint4 xv[3];
        {
            const uint4* xr = reinterpret_cast<const uint4*>(x + xrow * D_);
            xv[0] = ldg128(xr + lane); xv[1] = ldg128(xr + lane + 32); xv[2] = ldg128(xr + 64 + (lane & 7));
        }
        asm volatile("setmaxnreg.inc.sync.aligned.u32 112;");
        bar_sync(0, 640);
        const int wg = warp >> 2, m = wg & 1, w4 = warp & 3, gq = lane >> 2, t = lane & 3;
        {
            const uint32_t w[12] = {xv[0].x, xv[0].y, xv[0].z, xv[0].w, xv[1].x, xv[1].y, xv[1].z, xv[1].w, xv[2].x, xv[2].y, xv[2].z, xv[2].w};
            float s = 0.f, s2 = 0.f;
            #pragma unroll
            for (int i = 0; i < 12; i++) { if (i < 8) s += bf_lo(w[i]) + bf_hi(w[i]); else s2 += bf_lo(w[i]) + bf_hi(w[i]); }
            if (lane < 8) s += s2;
            #pragma unroll
            for (int o = 16; o; o >>= 1) s += __shfl_xor_sync(~0u, s, o);
            const float mean = s * (1.f / D_);
            float q = 0.f, q2 = 0.f;
            #pragma unroll
            for (int i = 0; i < 12; i++) {
                const float e0 = bf_lo(w[i]) - mean, e1 = bf_hi(w[i]) - mean;
                if (i < 8) q += e0 * e0 + e1 * e1; else q2 += e0 * e0 + e1 * e1;
            }
            if (lane < 8) q += q2;
            #pragma unroll
            for (int o = 16; o; o >>= 1) q += __shfl_xor_sync(~0u, q, o);
            const unsigned long long lrec = ((unsigned long long)(__float_as_uint(rsqrtf(q * (1.f / D_) + LN_EPS)) | 0x80000000u) << 32) | __float_as_uint(mean);
            if (lane == 0) asm volatile("st.relaxed.gpu.global.u64 [%0], %1;" :: "l"(g_ln + xrow), "l"(lrec) : "memory");
        }
        float2 ln0, ln1;
        auto ln_get = [&]() {
            mbar_wait(bLn, 0);
            const uint4 v = lds128(sm + KA_LN + (m * 32 + w4 * 8 + gq) * 16);
            ln0 = make_float2(__uint_as_float(v.x), fabsf(__uint_as_float(v.y))); ln1 = make_float2(__uint_as_float(v.z), fabsf(__uint_as_float(v.w)));
        };
        const uint64_t da = mkdesc(sm + m * 8192, 16, 1024, 1), db = mkdesc(sm + KA_B, 16, 1024, 1);
        const uint32_t csa = sm + KA_CS + 8 * t;
        const int rot = (gq + 2 * t) & 7;
        const uint32_t rec = sm + KA_REC + t * 16384 + m * 8192 + (w4 * 16 + rot) * 128;
        const uint32_t kvb = sm + KA_REC;
        if (wg < 2) {
            float acc[36]; uint2 cs[9];
            #pragma unroll
            for (int c = 0; c < 9; c++) {
                mbar_wait(bFull + c * 8, 0);
                wg_fence();
                #pragma unroll
                for (int kk = 0; kk < 4; kk++) wgmma_n72<0, 0>(acc, dadv(da, c * 16384 + kk * 32), dadv(db, c * 9216 + kk * 32), (c | kk) != 0);
                wg_commit();
                if (c > 0) { wg_wait<1>(); if (lane == 0) mbar_arrive(bEmpty + (c - 1) * 8); }
            }
            wg_wait<0>();
            reg_fence<36>(acc);
            bar_arrive(5, 512);
            if (lane == 0) mbar_arrive(bEmpty + 8 * 8);
            bar_sync(6, 384);
            #pragma unroll
            for (int j = 0; j < 9; j++) cs[j] = lds64(csa + 32 * j);
            ln_get();
            uint32_t ph[2][18];
            #pragma unroll
            for (int r = 0; r < 2; r++) {
                float a[18];
                const float2 ln = r ? ln1 : ln0;
                #pragma unroll
                for (int j = 0; j < 9; j++) { a[2 * j] = fmaf(-ln.x, __uint_as_float(cs[j].x), acc[4 * j + 2 * r]); a[2 * j + 1] = fmaf(-ln.x, __uint_as_float(cs[j].y), acc[4 * j + 2 * r + 1]); }
                dual_softmax(a, ln.y * LOG2E, ph[r]);
            }
            #pragma unroll
            for (int j = 0; j < 18; j++) asm volatile("" : "+r"(ph[0][j]), "+r"(ph[1][j]));
            bar_sync(3 + m, 256);
            #pragma unroll
            for (int r = 0; r < 2; r++) {
                #pragma unroll
                for (int j = 0; j < 4; j++) sts128(rec + r * 1024 + ((j ^ rot) << 4), ph[r][4 * j], ph[r][4 * j + 1], ph[r][4 * j + 2], ph[r][4 * j + 3]);
                sts128(rec + r * 1024 + ((4 ^ rot) << 4), ph[r][16], ph[r][17], 0u, 0u);
            }
            fence_async_smem();
            bar_sync(8, 512);
            ka_kv(sm + KA_REC + wg * 16384, g_kv + (g * 4 + wg) * KV_H, w4, lane);
            bar_arrive(7, 512);
            bar_sync(11, 256);
            #pragma unroll
            for (int j = 0; j < 6; j++) if (j < 5 || tid < 196) sts128(kvb + (j * 256 + tid) * 16, 0u, 0u, 0u, 0u);
            const float* kp = g_kv + (g * 4 + w4) * KV_H + lane * 2;
            const uint32_t kd = kvb + t * 1312 + ((gq >> 1) * 8 + 2 * w4 + (gq & 1)) * 16 + w4 * 4;
            bar_sync(1, 288);
            if (m == 0) {
                const uint4 u0 = ldg128(kp + lane * 2), u1 = ldg128(kp + 128 + lane * 2); const uint2 u2 = ldg64(kp + 256);
                const uint4 v0 = ldg128(kp + 640 + lane * 2), v1 = ldg128(kp + 768 + lane * 2); const uint2 v2 = ldg64(kp + 896);
                sts32(kd, packu(u0.x, u0.y)); sts32(kd + 5248, packu(u0.z, u0.w)); sts32(kd + 10496, packu(u1.x, u1.y)); sts32(kd + 15744, packu(u1.z, u1.w));
                if (t < 2) sts32(kd + 20992, packu(u2.x, u2.y));
                if (gq < 3) {
                    sts32(kd + 1024, packu(v0.x, v0.y)); sts32(kd + 6272, packu(v0.z, v0.w)); sts32(kd + 11520, packu(v1.x, v1.y)); sts32(kd + 16768, packu(v1.z, v1.w));
                    if (t < 2) sts32(kd + 22016, packu(v2.x, v2.y));
                }
            } else {
                const uint4 u0 = ldg128(kp + 320 + lane * 2), u1 = ldg128(kp + 448 + lane * 2); const uint2 u2 = ldg64(kp + 576);
                sts32(kd + 512, packu(u0.x, u0.y)); sts32(kd + 5760, packu(u0.z, u0.w)); sts32(kd + 11008, packu(u1.x, u1.y)); sts32(kd + 16256, packu(u1.z, u1.w));
                if (t < 2) sts32(kd + 21504, packu(u2.x, u2.y));
            }
            fence_async_smem();
            bar_arrive(9, 512);
        } else {
            float avq[36], acc[36]; uint2 cs[9];
            if (m == 1) {
                pdl_wait();
                if (tid < 384 + 108) {
                    uint2 pc[18];
                    #pragma unroll
                    for (int j = 0; j < 18; j++) pc[j] = ldg64(g_cs + (g * 18 + j) * 216 + (tid - 384) * 2);
                    float a = 0.f, c = 0.f;
                    #pragma unroll
                    for (int j = 0; j < 18; j++) { a += __uint_as_float(pc[j].x); c += __uint_as_float(pc[j].y); }
                    asm volatile("st.shared.v2.f32 [%0], {%1, %2};" :: "r"(sm + KA_CS + (tid - 384) * 8), "f"(a), "f"(c) : "memory");
                }
                bar_arrive(6, 384);
            }
            bar_sync(5, 512);
            #pragma unroll
            for (int i = 9; i < 22; i++) {
                const int c = i < 17 ? (i + 1) / 2 : i - 17;
                mbar_wait(bFull + (i % 9) * 8, (i / 9) & 1);
                wg_fence();
                #pragma unroll
                for (int kk = 0; kk < 4; kk++)
                    wgmma_n72<0, 0>((i < 17 && !(i & 1)) ? acc : avq, dadv(da, c * 16384 + kk * 32), dadv(db, (i % 9) * 9216 + kk * 32), i > 10 || kk != 0);
                wg_commit();
                if (i > 9 && i <= 18) { wg_wait<1>(); if (lane == 0) mbar_arrive(bEmpty + ((i - 1) % 9) * 8); }
                if (i == 17) bar_arrive(3 + m, 256);
                if (i == 18) bar_sync(14 + m, 128);
            }
            #pragma unroll
            for (int j = 0; j < 9; j++) cs[j] = lds64(csa + 288 + 32 * j);
            ln_get();
            wg_wait<0>();
            reg_fence<36>(avq);
            #pragma unroll
            for (int r = 0; r < 2; r++) {
                uint32_t pv[9];
                const float2 ln = r ? ln1 : ln0;
                #pragma unroll
                for (int j = 0; j < 9; j++)
                    pv[j] = pack2(fmaf(-ln.x, __uint_as_float(cs[j].x), avq[4 * j + 2 * r]) * ln.y, fmaf(-ln.x, __uint_as_float(cs[j].y), avq[4 * j + 2 * r + 1]) * ln.y);
                sts128(rec + r * 1024 + ((5 ^ rot) << 4), pv[0], pv[1], pv[2], pv[3]);
                sts128(rec + r * 1024 + ((6 ^ rot) << 4), pv[4], pv[5], pv[6], pv[7]);
                sts128(rec + r * 1024 + ((7 ^ rot) << 4), pv[8], 0x00003f80u, 0u, 0u);
            }
            fence_async_smem();
            bar_sync(8, 512);
            ka_kv(sm + KA_REC + wg * 16384, g_kv + (g * 4 + wg) * KV_H, w4, lane);
            const uint32_t sm2 = __shfl_sync(~0u, sm, 1);
            const uint64_t da2 = mkdesc(sm2 + m * 8192, 16, 1024, 1), db2 = mkdesc(sm2 + KA_B, 16, 1024, 1);
            #pragma unroll
            for (int i = 22; i < 27; i++) mbar_wait(bFull + (i % 9) * 8, 0);
            #pragma unroll
            for (int j = 0; j < 9; j++) cs[j] = lds64(csa + 576 + 32 * j);
            bar_sync(7, 512);
            wg_fence();
            #pragma unroll
            for (int i = 22; i < 27; i++)
                #pragma unroll
                for (int kk = 0; kk < 4; kk++) wgmma_n72<0, 0>(acc, dadv(da2, (i - 22) * 16384 + kk * 32), dadv(db2, (i % 9) * 9216 + kk * 32), 1);
            wg_commit();
            wg_wait<0>();
            reg_fence<36>(acc);
            uint32_t ph[2][18];
            #pragma unroll
            for (int r = 0; r < 2; r++) {
                float a[18];
                const float2 ln = r ? ln1 : ln0;
                #pragma unroll
                for (int j = 0; j < 9; j++) { a[2 * j] = fmaf(-ln.x, __uint_as_float(cs[j].x), acc[4 * j + 2 * r]); a[2 * j + 1] = fmaf(-ln.x, __uint_as_float(cs[j].y), acc[4 * j + 2 * r + 1]); }
                dual_softmax(a, ln.y * LOG2E, ph[r]);
            }
            #pragma unroll
            for (int j = 0; j < 18; j++) asm volatile("" : "+r"(ph[0][j]), "+r"(ph[1][j]));
            uint32_t* og = reinterpret_cast<uint32_t*>(g_o + (mt * 2 + m) * (64 * D_) + g * 4608) + w4 * 64 + lane;
            asm volatile("" : "+l"(og));
            const uint64_t dk = mkdesc(sm2 + KA_REC, 1312, 128, 0);
            float oc[40];
            bar_sync(9, 512);
            wg_fence();
            #pragma unroll
            for (int j = 0; j < 9; j++) wgmma_rs_n80(oc, ph[0][2 * j], ph[1][2 * j], ph[0][2 * j + 1], ph[1][2 * j + 1], dadv(dk, j * 2624), j != 0);
            wg_commit();
            wg_wait<0>();
            reg_fence<40>(oc);
            const float r0 = rcp_full(oc[36] + 1e-6f), r1 = rcp_full(oc[38] + 1e-6f);
            #pragma unroll
            for (int j = 0; j < 9; j++) { og[j * 256] = pack2(oc[4 * j] * r0, oc[4 * j + 1] * r0); og[j * 256 + 32] = pack2(oc[4 * j + 2] * r1, oc[4 * j + 3] * r1); }
        }
    }
}

constexpr int K2PRE = 2, K2_B = 73728, K2_PIECE = 27648, K2_X = K2_B + 5 * K2_PIECE, K2_BAR = K2_X + 18432, K2_SMEM = K2_BAR + 128;
__global__ void __cluster_dims__(2, 1, 1) __launch_bounds__(288, 1) k2_attn(const __grid_constant__ CUtensorMap tmX, const bf16* __restrict__ b2) {
    extern __shared__ __align__(1024) char smem[];
    const uint32_t sm = smem_u32(smem);
    const uint32_t bFull = sm + K2_BAR, bX = bFull + 6 * 8;
    const int tid = threadIdx.x, lane = tid & 31, warp = __shfl_sync(~0u, tid >> 5, 0);
    const int ns = blockIdx.x & 3, mt = blockIdx.x >> 2;
    const int wg = warp >> 2, w4 = warp & 3, gq = lane >> 2, t = lane & 3;
    const bf16* wsrc = g_wo + ns * (2 * 72 * 576);
    unsigned short bb0, bb1;
    asm volatile("ld.global.nc.u16 %0, [%1];" : "=h"(bb0) : "l"(b2 + mt * 64 + w4 * 16 + gq));
    asm volatile("ld.global.nc.u16 %0, [%1];" : "=h"(bb1) : "l"(b2 + mt * 64 + w4 * 16 + gq + 8));
    auto load_w = [&](int i) {
        bulk_g2s(sm + K2_B + (i % 5) * K2_PIECE, wsrc + i * (K2_PIECE / 4), K2_PIECE / 2, bFull + i * 8);
        bulk_g2s(sm + K2_B + (i % 5) * K2_PIECE + K2_PIECE / 2, wsrc + 72 * 576 + i * (K2_PIECE / 4), K2_PIECE / 2, bFull + i * 8);
    };
    if (tid == 256) {
        #pragma unroll
        for (int i = 0; i < 7; i++) mbar_init(bFull + i * 8, 1);
        fence_mbar_init();
        #pragma unroll
        for (int i = 0; i < K2PRE; i++) load_w(i);
    }
    __syncthreads();
    if (warp == 8) {
        if (lane == 0) {
            pdl_wait();
            const bf16* osrc = g_o + mt * (64 * D_);
            #pragma unroll
            for (int i = 0; i < 6; i++) {
                bulk_g2s(sm + i * 12288, osrc + i * 6144, 12288, bFull + i * 8);
                if (i + 1 >= K2PRE && i < 4) load_w(i + 1);
            }
            pdl_trigger();
        }
        __syncwarp();
        bar_sync(3, 288);
        if (lane == 0) {
            load_w(5);
            tma2d(sm + K2_X, &tmX, bX, ns * 144, mt * 64);
            tma2d(sm + K2_X + 9216, &tmX, bX, ns * 144 + 72, mt * 64);
        }
    } else {
        if (tid == 0) {
            #pragma unroll
            for (int i = 0; i < 6; i++) mbar_expect(bFull + i * 8, K2_PIECE + 12288);
            mbar_expect(bX, 18432);
            prefetch_tm(&tmX);
        }
        __syncwarp();
        float acc[36];
        const uint32_t xs = sm + K2_X + wg * 9216;
        uint32_t xr[20];
        const int p = ns * 2 + wg;
        unsigned long long* sb = g_stats + (mt * 4 + w4) * 128 + gq * 2;
        unsigned long long* sw = sb + p * 16;
        const unsigned long long* sr = sb + t * 32;
        uint32_t* ndst = reinterpret_cast<uint32_t*>(g_hnT + (mt * D_ + p * 72) * 64) + w4 * 64 + lane;
        asm volatile("" : "+l"(sw), "+l"(sr), "+l"(ndst));
        const uint64_t da0 = mkdesc(sm, 1024, 128, 0), db0 = mkdesc(sm + K2_B + wg * (K2_PIECE / 2), 1152, 128, 0);
        #pragma unroll
        for (int i = 0; i < 6; i++) {
            mbar_wait(bFull + i * 8, 0);
            wg_fence();
            #pragma unroll
            for (int kk = 0; kk < 6; kk++)
                wgmma_n72<0, 0>(acc, dadv(da0, i * 12288 + kk * 2048), dadv(db0, (i % 5) * K2_PIECE + kk * 2304), (i | kk) != 0);
            wg_commit();
            if (i == 1) { wg_wait<1>(); bar_arrive(3, 288); }
            if (i == 5) {
                mbar_wait(bX, 0);
                #pragma unroll
                for (int j = 0; j < 5; j++)
                    asm volatile("ldmatrix.sync.aligned.m8n8.x4.shared.b16 {%0,%1,%2,%3}, [%4];" : "=r"(xr[4 * j]), "=r"(xr[4 * j + 1]), "=r"(xr[4 * j + 2]), "=r"(xr[4 * j + 3])
                                 : "r"(xs + (w4 * 16 + (lane & 15)) * 144 + (j < 4 ? (lane >> 4) * 16 : 0) + j * 32) : "memory");
            }
        }
        wg_wait<0>();
        reg_fence<36>(acc);
        #pragma unroll
        for (int j = 0; j < 18; j++) { acc[2 * j] += bf_lo(xr[j]); acc[2 * j + 1] += bf_hi(xr[j]); }
        float m0 = 0.f, m1 = 0.f;
        #pragma unroll
        for (int j = 0; j < 9; j++) { m0 += acc[4 * j] + acc[4 * j + 1]; m1 += acc[4 * j + 2] + acc[4 * j + 3]; }
        m0 *= (1.f / 18); m1 *= (1.f / 18);
        float q0 = 0.f, q1 = 0.f, q2 = 0.f, q3 = 0.f;
        #pragma unroll
        for (int j = 0; j < 9; j++) {
            float e;
            e = acc[4 * j] - m0; q0 = fmaf(e, e, q0); e = acc[4 * j + 1] - m0; q2 = fmaf(e, e, q2);
            e = acc[4 * j + 2] - m1; q1 = fmaf(e, e, q1); e = acc[4 * j + 3] - m1; q3 = fmaf(e, e, q3);
        }
        q0 += q2; q1 += q3;
        #pragma unroll
        for (int o = 1; o < 4; o <<= 1) {
            const float a0 = __shfl_xor_sync(~0u, m0, o), a1 = __shfl_xor_sync(~0u, m1, o), b0 = __shfl_xor_sync(~0u, q0, o), b1 = __shfl_xor_sync(~0u, q1, o);
            q0 += b0 + (a0 - m0) * (a0 - m0) * (9.f * o); q1 += b1 + (a1 - m1) * (a1 - m1) * (9.f * o);
            m0 = 0.5f * (m0 + a0); m1 = 0.5f * (m1 + a1);
        }
        if (t == 0) {
            const unsigned long long r0 = ((unsigned long long)(__float_as_uint(q0) | 0x80000000u) << 32) | __float_as_uint(m0);
            const unsigned long long r1 = ((unsigned long long)(__float_as_uint(q1) | 0x80000000u) << 32) | __float_as_uint(m1);
            asm volatile("st.relaxed.gpu.global.v2.u64 [%0], {%1, %2};" :: "l"(sw), "l"(r0), "l"(r1) : "memory");
        }
        unsigned long long ra, rb, rc, rd;
        {
            int it = 0;
            while (true) {
                asm volatile("ld.relaxed.gpu.global.v2.u64 {%0, %1}, [%2];" : "=l"(ra), "=l"(rc) : "l"(sr) : "memory");
                asm volatile("ld.relaxed.gpu.global.v2.u64 {%0, %1}, [%2];" : "=l"(rb), "=l"(rd) : "l"(sr + 16) : "memory");
                const bool ok = (long long)(ra & rb & rc & rd) < 0;
                if (__all_sync(~0u, ok)) break;
                if (++it > (1 << 22)) __trap();
            }
        }
        float sc[2], mu[2];
        #pragma unroll
        for (int r = 0; r < 2; r++) {
            const unsigned long long u = r ? rc : ra, v = r ? rd : rb;
            const float ma = __uint_as_float((uint32_t)u), mb = __uint_as_float((uint32_t)v);
            float ms = ma + mb;
            ms += __shfl_xor_sync(~0u, ms, 1); ms += __shfl_xor_sync(~0u, ms, 2);
            const float mean = ms * 0.125f;
            float M2 = fabsf(__uint_as_float((uint32_t)(u >> 32))) + fabsf(__uint_as_float((uint32_t)(v >> 32))) + 72.f * ((ma - mean) * (ma - mean) + (mb - mean) * (mb - mean));
            M2 += __shfl_xor_sync(~0u, M2, 1); M2 += __shfl_xor_sync(~0u, M2, 2);
            const float var = M2 * (1.f / D_);
            const float r1 = rsqrtf(var + LN_EPS);
            const float var2 = var * r1 * r1;
            const float r2 = rsqrtf(var2 + LN_EPS);
            sc[r] = 0.5f * (r1 * r2); mu[r] = mean;
        }
        const float of0 = -mu[0] * sc[0], of1 = -mu[1] * sc[1];
        #pragma unroll
        for (int j = 0; j < 9; j++) {
            ndst[j * 256] = pack2(fmaf(acc[4 * j], sc[0], of0), fmaf(acc[4 * j + 1], sc[0], of0));
            ndst[j * 256 + 32] = pack2(fmaf(acc[4 * j + 2], sc[1], of1), fmaf(acc[4 * j + 3], sc[1], of1));
        }
        if (p == 1 && t < 2) g_ln[mt * 64 + w4 * 16 + gq + 8 * t] = 0ull;
        if (p == 0 && t < 2) {
            asm volatile("" : "+h"(bb0), "+h"(bb1));
            g_rc[mt * 64 + w4 * 16 + gq + 8 * t] = make_float2(1.f / (t ? sc[1] : sc[0]), (t ? mu[1] : mu[0]) + __uint_as_float((uint32_t)(t ? bb1 : bb0) << 16));
        }
    }
}

constexpr int PFT = 4, W2HEAD = 9;
constexpr int K3_STAGES = 6, K3_STAGE = 36864, K3_STAG = 6, K3_PRE = 2, K3_BAR = K3_STAGES * K3_STAGE, K3_SMEM = K3_BAR + 256;
DEVI uint32_t gelu2(float a0, float a1) {
    const float z0 = a0 * fmaf(a0 * a0, 0.2854192650904f, 1.5957691216057f), z1 = a1 * fmaf(a1 * a1, 0.2854192650904f, 1.5957691216057f);
    return pack2(fmaf(a0, tanh_fast(z0), a0), fmaf(a1, tanh_fast(z1), a1));
}
template<int NB> DEVI void k3_store(const float* q, uint32_t* dst) {
    #pragma unroll
    for (int j = 0; j < NB; j++) { dst[j * 256] = gelu2(q[4 * j], q[4 * j + 1]); dst[j * 256 + 32] = gelu2(q[4 * j + 2], q[4 * j + 3]); }
}
DEVI void k3_typeb(uint32_t sm_, int fc_, float bias0, float bias1, const bf16* __restrict__ b1) {
    const uint32_t sm = __shfl_sync(~0u, sm_, 0);
    const int fc = __shfl_sync(~0u, fc_, 0);
    const uint32_t bFull = sm + K3_BAR, bEmpty = bFull + K3_STAGES * 8;
    const int tid = threadIdx.x, lane = tid & 31, warp = __shfl_sync(~0u, tid >> 5, 0);
    const int wg = warp >> 2, w4 = warp & 3, gq = lane >> 2;
    const uint32_t st = sm + wg * 8192;
    const uint64_t da0 = mkdesc(st, 8192, 1024, 1);
    int s = 0, ps = 0; uint32_t ph = 0;
    {
            const int f2 = (fc + 2) * 64 + w4 * 16 + gq;
            const float bias2 = 0.5f * __bfloat162float(b1[f2]), bias3 = 0.5f * __bfloat162float(b1[f2 + 8]);
            float acc[48], acc2[24];
            const uint64_t da2 = mkdesc(sm + 16384, 8192, 1024, 1), db0 = mkdesc(sm + 24576, 128, 1024, 0), db2 = mkdesc(sm + 24576 + wg * 6144, 128, 1024, 0);
            #pragma unroll 1
            for (int i = 0; i < 32 - K3_STAG; i++) {
                mbar_wait(bFull + s * 8, ph);
                const uint32_t so = s * K3_STAGE;
                wg_fence();
                #pragma unroll
                for (int kk = 0; kk < 4; kk++) {
                    wgmma_n96<1, 1>(acc, dadv(da0, so + kk * 2048), dadv(db0, so + kk * 256), (i | kk) != 0);
                    wgmma_n48<1, 1>(acc2, dadv(da2, so + kk * 2048), dadv(db2, so + kk * 256), (i | kk) != 0);
                }
                wg_commit();
                wg_wait<1>();
                if (i > 0 && lane == 0) mbar_arrive(bEmpty + ps * 8);
                ps = s;
                if (++s == K3_STAGES) { s = 0; ph ^= 1; }
            }
            if (wg == 1) {
                wg_wait<0>();
                if (lane == 0) mbar_arrive(bEmpty + ps * 8);
                #pragma unroll
                for (int i = 32 - K3_STAG; i < 32; i++) mbar_wait(bFull + (i % K3_STAGES) * 8, (i / K3_STAGES) & 1);
                bar_sync(3, 256);
            }
            #pragma unroll
            for (int i = 32 - K3_STAG; i < 32; i++) {
                if (wg == 0) mbar_wait(bFull + (i % K3_STAGES) * 8, (i / K3_STAGES) & 1);
                const uint32_t so = (i % K3_STAGES) * K3_STAGE;
                wg_fence();
                #pragma unroll
                for (int kk = 0; kk < 4; kk++) {
                    wgmma_n96<1, 1>(acc, dadv(da0, so + kk * 2048), dadv(db0, so + kk * 256), 1);
                    wgmma_n48<1, 1>(acc2, dadv(da2, so + kk * 2048), dadv(db2, so + kk * 256), 1);
                }
                wg_commit();
                if (i == 32 - K3_STAG && wg == 0) { wg_wait<1>(); if (lane == 0) mbar_arrive(bEmpty + ps * 8); }
            }
            if (wg == 0) bar_arrive(3, 256);
            wg_wait<0>();
            reg_fence<48>(acc); reg_fence<24>(acc2);
            #pragma unroll
            for (int j = 0; j < 48; j++) acc[j] += (j & 2) ? bias1 : bias0;
            #pragma unroll
            for (int j = 0; j < 24; j++) acc2[j] += (j & 2) ? bias3 : bias2;
            k3_store<12>(acc, reinterpret_cast<uint32_t*>(g_u + ((fc + wg) * D_ + 480) * 64) + w4 * 64 + lane);
            k3_store<6>(acc2, reinterpret_cast<uint32_t*>(g_u + ((fc + 2) * D_ + 480 + wg * 48) * 64) + w4 * 64 + lane);
    }
}
__global__ void __cluster_dims__(2, 1, 1) __launch_bounds__(288, 1) k3_mix1(const __grid_constant__ CUtensorMap tmW1a, const __grid_constant__ CUtensorMap tmW1b,
                                                                             const bf16* __restrict__ b1, const bf16* __restrict__ w1, const bf16* __restrict__ w2) {
    extern __shared__ __align__(1024) char smem[];
    const uint32_t sm = smem_u32(smem);
    const uint32_t bFull = sm + K3_BAR, bEmpty = bFull + K3_STAGES * 8;
    const int tid = threadIdx.x, lane = tid & 31, warp = __shfl_sync(~0u, tid >> 5, 0);
    const int cl = blockIdx.x >> 1, rank = blockIdx.x & 1;
    bool tb = false; int fc, d0;
    if (cl < 36) { fc = 2 * cl; d0 = 160 * rank; }
    else if (cl < 60) { const int q = (cl - 36) >> 1, e = (cl - 36) & 1; tb = rank; fc = rank ? 6 * q + 3 * e : 6 * q + 4 * e; d0 = rank ? 480 : 320; }
    else { fc = 6 * (2 * (cl - 60) + rank) + 2; d0 = 320; }
    const CUtensorMap* tm = tb ? &tmW1b : &tmW1a;
    const uint32_t abytes = tb ? 24576 : 16384;
    if (tid == 256) {
        #pragma unroll
        for (int i = 0; i < K3_STAGES; i++) { mbar_init(bFull + i * 8, 1); mbar_init(bEmpty + i * 8, 8); }
        fence_mbar_init();
        #pragma unroll
        for (int i = 0; i < K3_STAGES; i++) mbar_expect(bFull + i * 8, K3_STAGE);
        #pragma unroll
        for (int i = 0; i < K3_PRE; i++) tma3d(sm + i * K3_STAGE, tm, bFull + i * 8, 0, i * 64, fc);
    }
    __syncthreads();
    if (warp == 8) {
        if (tid == 256) {
            pdl_wait();
            pdl_trigger();
            const bf16* hs = g_hnT + d0 * 64;
            #pragma unroll
            for (int i = 0; i < K3_STAGES; i++) {
                bulk_g2s(sm + i * K3_STAGE + abytes, hs + i * (D_ * 64), K3_STAGE - abytes, bFull + i * 8);
                if (i >= K3_PRE) tma3d(sm + i * K3_STAGE, tm, bFull + i * 8, 0, i * 64, fc);
            }
            int s = 0; uint32_t ph = 0;
            #pragma unroll 1
            for (int i = K3_STAGES; i < 32; i++) {
                mbar_wait(bEmpty + s * 8, ph);
                mbar_expect(bFull + s * 8, K3_STAGE);
                tma3d(sm + s * K3_STAGE, tm, bFull + s * 8, 0, i * 64, fc);
                bulk_g2s(sm + s * K3_STAGE + abytes, hs + i * (D_ * 64), K3_STAGE - abytes, bFull + s * 8);
                if (i == 18 && blockIdx.x < 128) l2_prefetch(w1 + (size_t)(2048 - 64 * PFT) * F_ + blockIdx.x * (2304 * PFT), 4608 * PFT);
                if (++s == K3_STAGES) { s = 0; ph ^= 1; }
            }
            if (blockIdx.x < 128) l2_prefetch(w2 + (size_t)(blockIdx.x & 1) * (2304 * S_) + (blockIdx.x >> 1) * (W2HEAD * 2048), W2HEAD * 4096);
        }
    } else {
        const int wg = warp >> 2, w4 = warp & 3, gq = lane >> 2;
        const int f0 = (fc + wg) * 64 + w4 * 16 + gq;
        const float bias0 = 0.5f * __bfloat162float(b1[f0]), bias1 = 0.5f * __bfloat162float(b1[f0 + 8]);
        uint32_t* dst = reinterpret_cast<uint32_t*>(g_u + ((fc + wg) * D_ + d0) * 64) + w4 * 64 + lane;
        const uint32_t st = sm + wg * 8192;
        const uint64_t da0 = mkdesc(st, 8192, 1024, 1);
        int s = 0, ps = 0; uint32_t ph = 0;
        if (!tb) {
            float acc[80];
            #pragma unroll
            for (int j = 0; j < 80; j++) acc[j] = (j & 2) ? bias1 : bias0;
            reg_fence<80>(acc);
            const uint64_t db0 = mkdesc(sm + 16384, 128, 1024, 0);
            #pragma unroll 1
            for (int i = 0; i < 32 - K3_STAG; i++) {
                mbar_wait(bFull + s * 8, ph);
                const uint64_t da = dadv(da0, s * K3_STAGE), db = dadv(db0, s * K3_STAGE);
                wg_fence();
                #pragma unroll
                for (int kk = 0; kk < 4; kk++)
                    wgmma_n160<1, 1>(acc, dadv(da, kk * 2048), dadv(db, kk * 256), 1);
                wg_commit();
                wg_wait<1>();
                if (i > 0 && lane == 0) mbar_arrive(bEmpty + ps * 8);
                ps = s;
                if (++s == K3_STAGES) { s = 0; ph ^= 1; }
            }
            if (wg == 1) {
                wg_wait<0>();
                if (lane == 0) mbar_arrive(bEmpty + ps * 8);
                #pragma unroll
                for (int i = 32 - K3_STAG; i < 32; i++) mbar_wait(bFull + (i % K3_STAGES) * 8, (i / K3_STAGES) & 1);
                bar_sync(3, 256);
            }
            #pragma unroll
            for (int i = 32 - K3_STAG; i < 32; i++) {
                if (wg == 0) mbar_wait(bFull + (i % K3_STAGES) * 8, (i / K3_STAGES) & 1);
                wg_fence();
                #pragma unroll
                for (int kk = 0; kk < 4; kk++)
                    wgmma_n160<1, 1>(acc, dadv(da0, (i % K3_STAGES) * K3_STAGE + kk * 2048), dadv(db0, (i % K3_STAGES) * K3_STAGE + kk * 256), 1);
                wg_commit();
                if (i == 32 - K3_STAG && wg == 0) { wg_wait<1>(); if (lane == 0) mbar_arrive(bEmpty + ps * 8); }
            }
            if (wg == 0) bar_arrive(3, 256);
            wg_wait<0>();
            reg_fence<80>(acc);
            k3_store<20>(acc, dst);
        } else {
            k3_typeb(sm, fc, bias0, bias1, b1);
        }
    }
}

constexpr int SLOTC = 700, SLOTP = 578, K4A0 = 1, K4_PD = 4;
constexpr int K4_STAGES = 5, K4_STAGE = 8192 + 36864, K4_STAG = 3, K4_BAR = K4_STAGES * K4_STAGE, K4_SMEM = K4_BAR + 256;
constexpr int K4_XS = (36 - K4_STAG - 1) % K4_STAGES;
__global__ void __cluster_dims__(2, 1, 1) __launch_bounds__(288, 1) k4_mix2(const __grid_constant__ CUtensorMap tmW2, const __grid_constant__ CUtensorMap tmOut) {
    extern __shared__ __align__(1024) char smem[];
    const uint32_t sm = smem_u32(smem);
    const uint32_t bFull = sm + K4_BAR, bEmpty = bFull + K4_STAGES * 8, bP = bEmpty + K4_STAGES * 8, bRdy = bP + 16, bH = bRdy + 8;
    const int tid = threadIdx.x, lane = tid & 31, warp = __shfl_sync(~0u, tid >> 5, 0);
    const int ks = blockIdx.x & 1, tm = (blockIdx.x >> 1) & 31, tn = blockIdx.x >> 6;
    const int k0 = ks * 36;
    if (tid == 256) {
        #pragma unroll
        for (int i = 0; i < K4_STAGES; i++) { mbar_init(bFull + i * 8, 1); mbar_init(bEmpty + i * 8, 8); }
        mbar_init(bP, 1); mbar_init(bP + 8, 1); mbar_init(bRdy, 8); mbar_init(bH, 1);
        fence_mbar_init();
        #pragma unroll
        for (int i = 0; i < K4A0; i++) tma3d(sm + i * K4_STAGE, &tmW2, bFull + i * 8, 0, (k0 + i) * 64, tm);
    }
    __syncthreads();
    cluster_arrive_relaxed();
    if (tid == 0) {
        #pragma unroll
        for (int i = K4A0; i < 2; i++) tma3d(sm + i * K4_STAGE, &tmW2, bFull + i * 8, 0, (k0 + i) * 64, tm);
    }
    if (tid == 32) {
        #pragma unroll
        for (int i = 0; i < K4_STAGES; i++) mbar_expect(bFull + i * 8, K4_STAGE);
    }
    if (tid == 128) { mbar_expect(bP, 9216); mbar_expect(bP + 8, 9216); prefetch_tm(&tmOut); }
    __syncwarp();
    if (warp == 8) {
        if (lane == 0) {
            pdl_wait();
            const bf16* us = g_u + ((size_t)k0 * D_ + tn * 288) * 64;
            uint32_t slot = clock() + SLOTC;
            #pragma unroll
            for (int i = 0; i < K4_STAGES; i++) {
                if (i >= 2) { tma3d(sm + i * K4_STAGE, &tmW2, bFull + i * 8, 0, (k0 + i) * 64, tm); while ((int)(clock() - slot) < 0) {} slot += SLOTP; }
                bulk_g2s(sm + i * K4_STAGE + 8192, us + (size_t)i * (D_ * 64), 36864, bFull + i * 8);
            }
            int s = 0; uint32_t ph = 0;
            #pragma unroll 1
            for (int i = K4_STAGES; i < 36; i++) {
                mbar_wait(bEmpty + s * 8, ph);
                mbar_expect(bFull + s * 8, K4_STAGE);
                tma3d(sm + s * K4_STAGE, &tmW2, bFull + s * 8, 0, (k0 + i) * 64, tm);
                if (i + K4_PD < 36 && ((i ^ tn) & 1)) tma3d_prefetch(&tmW2, 0, (k0 + i + K4_PD) * 64, tm);
                if (i < 32) { while ((int)(clock() - slot) < 0) {} slot += SLOTP; }
                bulk_g2s(sm + s * K4_STAGE + 8192, us + (size_t)i * (D_ * 64), 36864, bFull + s * 8);
                if (++s == K4_STAGES) { s = 0; ph ^= 1; }
            }
            static_assert(K4_STAG <= 3, "stage of step 31 is free");
            mbar_wait(bEmpty + s * 8, ph);
            mbar_expect(bH, 18432);
            bulk_g2s(sm + (31 % K4_STAGES) * K4_STAGE, g_hnT + (tm * D_ + tn * 288 + ks * 144) * 64, 18432, bH);
        }
        __syncwarp();
        cluster_wait();
        #pragma unroll
        for (int hh = 0; hh < 2; hh++) {
            bar_sync(4 + hh, 160);
            if (lane == 0) {
                tma2d_store(&tmOut, sm + K4_XS * K4_STAGE + 24576 + hh * 9216, tn * 288 + ks * 144 + hh * 72, tm * 64);
                bulk_commit();
            }
            __syncwarp();
        }
        if (lane == 0) { bulk_wait_read(); }
    } else {
        const int wg = warp >> 2, w4 = warp & 3, tw = tid & 127;
        const bool keep = wg == ks;
        float acc[72];
        const uint64_t da0 = mkdesc(sm, 8192, 1024, 1), db0 = mkdesc(sm + 8192 + wg * 18432, 128, 1024, 0);
        const uint32_t rdy = mapa(bRdy, ks ^ 1);
        cluster_wait();
        int s = 0, ps = 0; uint32_t ph = 0;
        #pragma unroll 1
        for (int i = 0; i < 36 - K4_STAG; i++) {
            mbar_wait(bFull + s * 8, ph);
            const uint64_t da = dadv(da0, s * K4_STAGE), db = dadv(db0, s * K4_STAGE);
            wg_fence();
            #pragma unroll
            for (int kk = 0; kk < 4; kk++)
                wgmma_n144<1, 1>(acc, dadv(da, kk * 2048), dadv(db, kk * 256), (i | kk) != 0);
            wg_commit();
            wg_wait<1>();
            if (i > 0 && lane == 0) mbar_arrive(bEmpty + ps * 8);
            ps = s;
            if (++s == K4_STAGES) { s = 0; ph ^= 1; }
        }
        const uint32_t xa = sm + K4_XS * K4_STAGE + tw * 16;
        const uint2 rc0 = ldg64(g_rc + tm * 64 + w4 * 16 + (lane >> 2)), rc1 = ldg64(g_rc + tm * 64 + w4 * 16 + (lane >> 2) + 8);
        float res[36];
        const uint32_t ya = sm + (31 % K4_STAGES) * K4_STAGE + 20480 + tw * 16;
        auto residual = [&](int hh) {
            uint32_t hp[20];
            mbar_wait(bH, 0);
            const uint32_t ha = sm + (31 % K4_STAGES) * K4_STAGE + hh * 9216 + (lane >> 4) * 1024 + w4 * 256 + (lane & 15) * 16;
            #pragma unroll
            for (int j = 0; j < 5; j++)
                asm volatile("ldmatrix.sync.aligned.m8n8.x4.shared.b16 {%0,%1,%2,%3}, [%4];" : "=r"(hp[4 * j]), "=r"(hp[4 * j + 1]), "=r"(hp[4 * j + 2]), "=r"(hp[4 * j + 3]) : "r"(ha + j * 2048) : "memory");
            #pragma unroll
            for (int j = 0; j < 18; j++) {
                const float is = __uint_as_float((j & 1) ? rc1.x : rc0.x), of = __uint_as_float((j & 1) ? rc1.y : rc0.y);
                res[2 * j] = fmaf(bf_lo(hp[j]), is, of); res[2 * j + 1] = fmaf(bf_hi(hp[j]), is, of);
            }
            reg_fence<36>(res);
        };
        auto partial = [&](int hh) {
            mbar_wait(bP + hh * 8, 0);
            uint32_t o[18];
            #pragma unroll
            for (int j = 0; j < 4; j++) { const uint4 v = lds128(xa + hh * 10240 + j * 2048); o[4 * j] = v.x; o[4 * j + 1] = v.y; o[4 * j + 2] = v.z; o[4 * j + 3] = v.w; }
            { const uint2 v = lds64(xa + hh * 10240 + 8192); o[16] = v.x; o[17] = v.y; }
            #pragma unroll
            for (int j = 0; j < 18; j++) { res[2 * j] += bf_lo(o[j]); res[2 * j + 1] += bf_hi(o[j]); }
        };
        if (!keep) {
            #pragma unroll
            for (int i = 36 - K4_STAG; i < 36; i++) {
                mbar_wait(bFull + (i % K4_STAGES) * 8, (i / K4_STAGES) & 1);
                wg_fence();
                #pragma unroll
                for (int kk = 0; kk < 4; kk++)
                    wgmma_n144<1, 1>(acc, dadv(da0, (i % K4_STAGES) * K4_STAGE + kk * 2048), dadv(db0, (i % K4_STAGES) * K4_STAGE + kk * 256), 1);
                wg_commit();
                if (i == 36 - K4_STAG) { wg_wait<1>(); if (lane == 0) mbar_arrive_remote(rdy); }
            }
            bar_arrive(3, 256);
            mbar_wait(bRdy, 0);
            wg_wait<0>();
            reg_fence<72>(acc);
            const uint32_t rd = mapa(xa, ks ^ 1), rb = mapa(bP, ks ^ 1);
            #pragma unroll
            for (int hh = 0; hh < 2; hh++) {
                const float* q = acc + hh * 36;
                #pragma unroll
                for (int j = 0; j < 4; j++)
                    asm volatile("st.async.shared::cluster.mbarrier::complete_tx::bytes.v4.b32 [%0], {%1,%2,%3,%4}, [%5];"
                                 :: "r"(rd + hh * 10240 + j * 2048), "r"(pack2(q[8 * j], q[8 * j + 1])), "r"(pack2(q[8 * j + 2], q[8 * j + 3])),
                                    "r"(pack2(q[8 * j + 4], q[8 * j + 5])), "r"(pack2(q[8 * j + 6], q[8 * j + 7])), "r"(rb + hh * 8) : "memory");
                asm volatile("st.async.shared::cluster.mbarrier::complete_tx::bytes.v2.b32 [%0], {%1,%2}, [%3];"
                             :: "r"(rd + hh * 10240 + 8192), "r"(pack2(q[32], q[33])), "r"(pack2(q[34], q[35])), "r"(rb + hh * 8) : "memory");
            }
            residual(1);
            partial(1);
            reg_fence<36>(res);
            bar_sync(1, 256);
            #pragma unroll
            for (int j = 0; j < 9; j++) {
                const uint4 v = lds128(ya + j * 2048);
                res[4 * j] += __uint_as_float(v.x); res[4 * j + 1] += __uint_as_float(v.y); res[4 * j + 2] += __uint_as_float(v.z); res[4 * j + 3] += __uint_as_float(v.w);
            }
        } else {
            wg_wait<0>();
            if (lane == 0) mbar_arrive_remote(rdy);
            #pragma unroll
            for (int i = 36 - K4_STAG; i < 36; i++) mbar_wait(bFull + (i % K4_STAGES) * 8, (i / K4_STAGES) & 1);
            bar_sync(3, 256);
            wg_fence();
            #pragma unroll
            for (int i = 36 - K4_STAG; i < 36; i++)
                #pragma unroll
                for (int kk = 0; kk < 4; kk++)
                    wgmma_n144<1, 1>(acc, dadv(da0, (i % K4_STAGES) * K4_STAGE + kk * 2048), dadv(db0, (i % K4_STAGES) * K4_STAGE + kk * 256), 1);
            wg_commit();
            residual(0);
            wg_wait<0>();
            reg_fence<72>(acc);
            #pragma unroll
            for (int j = 0; j < 9; j++)
                sts128(ya + j * 2048, __float_as_uint(acc[36 + 4 * j]), __float_as_uint(acc[37 + 4 * j]), __float_as_uint(acc[38 + 4 * j]), __float_as_uint(acc[39 + 4 * j]));
            bar_arrive(1, 256);
            #pragma unroll
            for (int j = 0; j < 36; j++) res[j] += acc[j];
            partial(0);
        }
        const int hh = keep ? 0 : 1;
        uint32_t o[18];
        #pragma unroll
        for (int j = 0; j < 18; j++) o[j] = pack2(res[2 * j], res[2 * j + 1]);
        const uint32_t ad = sm + K4_XS * K4_STAGE + 24576 + hh * 9216 + (w4 * 16 + ((lane >> 3) & 1) * 8 + (lane & 7)) * 144;
        #pragma unroll
        for (int j = 0; j < 4; j++) stsm4(ad + (lane >> 4) * 16 + j * 32, o[4 * j], o[4 * j + 1], o[4 * j + 2], o[4 * j + 3]);
        stsm2(ad + 128, o[16], o[17]);
        fence_async_smem();
        bar_arrive(4 + hh, 160);
    }
}

typedef CUresult (*EncFn)(CUtensorMap*, CUtensorMapDataType, cuuint32_t, void*, const cuuint64_t*, const cuuint64_t*, const cuuint32_t*,
                          const cuuint32_t*, CUtensorMapInterleave, CUtensorMapSwizzle, CUtensorMapL2promotion, CUtensorMapFloatOOBfill);

template <typename... KArgs, typename... Args>
static void launch(void (*kern)(KArgs...), dim3 grid, int block, int smem, bool pdl, Args... args) {
    cudaLaunchConfig_t cfg = {};
    cfg.gridDim = grid; cfg.blockDim = dim3(block); cfg.dynamicSmemBytes = smem; cfg.stream = cudaStreamPerThread;
    cudaLaunchAttribute at[1];
    at[0].id = cudaLaunchAttributeProgrammaticStreamSerialization; at[0].val.programmaticStreamSerializationAllowed = 1;
    cfg.attrs = at; cfg.numAttrs = pdl ? 1 : 0;
    cudaLaunchKernelEx(&cfg, kern, args...);
}

extern "C" void kernel_launch(void* const* d_in, const int* in_sizes, int n_in, void* d_out, int out_size) {
    const bf16* x = (const bf16*)d_in[0];
    const bf16* wqkv = (const bf16*)d_in[1];
    const bf16* wphi = (const bf16*)d_in[2];
    const bf16* wo = (const bf16*)d_in[3];
    const bf16* w1 = (const bf16*)d_in[5];
    const bf16* b1 = (const bf16*)d_in[6];
    const bf16* w2 = (const bf16*)d_in[7];
    const bf16* b2 = (const bf16*)d_in[8];
    static EncFn enc = nullptr;
    if (!enc) {
        void* fn = nullptr; cudaDriverEntryPointQueryResult qr;
        cudaGetDriverEntryPoint("cuTensorMapEncodeTiled", &fn, cudaEnableDefault, &qr);
        enc = (EncFn)fn;
        cudaFuncSetAttribute(ka_front, cudaFuncAttributeMaxDynamicSharedMemorySize, KA_SMEM);
        cudaFuncSetAttribute(k2_attn, cudaFuncAttributeMaxDynamicSharedMemorySize, K2_SMEM);
        cudaFuncSetAttribute(k3_mix1, cudaFuncAttributeMaxDynamicSharedMemorySize, K3_SMEM);
        cudaFuncSetAttribute(k4_mix2, cudaFuncAttributeMaxDynamicSharedMemorySize, K4_SMEM);
    }
    CUtensorMap tmW1, tmW1b, tmW2, tmOut, tmX, tmXA;
    const cuuint32_t es[3] = {1, 1, 1};
    {
        cuuint64_t dims[3] = {64, (cuuint64_t)S_, (cuuint64_t)(F_ / 64)}; cuuint64_t st[2] = {(cuuint64_t)F_ * 2, 128}; cuuint32_t box[3] = {64, 64, 2};
        enc(&tmW1, CU_TENSOR_MAP_DATA_TYPE_BFLOAT16, 3, (void*)w1, dims, st, box, es, CU_TENSOR_MAP_INTERLEAVE_NONE, CU_TENSOR_MAP_SWIZZLE_128B, CU_TENSOR_MAP_L2_PROMOTION_L2_128B, CU_TENSOR_MAP_FLOAT_OOB_FILL_NONE);
        box[2] = 3;
        enc(&tmW1b, CU_TENSOR_MAP_DATA_TYPE_BFLOAT16, 3, (void*)w1, dims, st, box, es, CU_TENSOR_MAP_INTERLEAVE_NONE, CU_TENSOR_MAP_SWIZZLE_128B, CU_TENSOR_MAP_L2_PROMOTION_L2_128B, CU_TENSOR_MAP_FLOAT_OOB_FILL_NONE);
    }
    {
        cuuint64_t dims[3] = {64, (cuuint64_t)F_, (cuuint64_t)(S_ / 64)}; cuuint64_t st[2] = {(cuuint64_t)S_ * 2, 128}; cuuint32_t box[3] = {64, 64, 1};
        enc(&tmW2, CU_TENSOR_MAP_DATA_TYPE_BFLOAT16, 3, (void*)w2, dims, st, box, es, CU_TENSOR_MAP_INTERLEAVE_NONE, CU_TENSOR_MAP_SWIZZLE_128B, CU_TENSOR_MAP_L2_PROMOTION_L2_128B, CU_TENSOR_MAP_FLOAT_OOB_FILL_NONE);
    }
    {
        cuuint64_t dims[2] = {(cuuint64_t)D_, (cuuint64_t)S_}; cuuint64_t st[1] = {(cuuint64_t)D_ * 2}; cuuint32_t box[2] = {72, 64};
        enc(&tmOut, CU_TENSOR_MAP_DATA_TYPE_BFLOAT16, 2, d_out, dims, st, box, es, CU_TENSOR_MAP_INTERLEAVE_NONE, CU_TENSOR_MAP_SWIZZLE_NONE, CU_TENSOR_MAP_L2_PROMOTION_NONE, CU_TENSOR_MAP_FLOAT_OOB_FILL_NONE);
        enc(&tmX, CU_TENSOR_MAP_DATA_TYPE_BFLOAT16, 2, (void*)x, dims, st, box, es, CU_TENSOR_MAP_INTERLEAVE_NONE, CU_TENSOR_MAP_SWIZZLE_NONE, CU_TENSOR_MAP_L2_PROMOTION_NONE, CU_TENSOR_MAP_FLOAT_OOB_FILL_NONE);
    }
    {
        cuuint64_t dims[3] = {64, (cuuint64_t)S_, 9}; cuuint64_t st[2] = {(cuuint64_t)D_ * 2, 128}; cuuint32_t box[3] = {64, 128, 1};
        enc(&tmXA, CU_TENSOR_MAP_DATA_TYPE_BFLOAT16, 3, (void*)x, dims, st, box, es, CU_TENSOR_MAP_INTERLEAVE_NONE, CU_TENSOR_MAP_SWIZZLE_128B, CU_TENSOR_MAP_L2_PROMOTION_L2_128B, CU_TENSOR_MAP_FLOAT_OOB_FILL_NONE);
    }
    launch(k0_prep, dim3(9, 8, 4), 256, 0, false, x, wqkv, wphi);
    launch(ka_front, 132, 640, KA_SMEM, true, tmXA, x, wo, w1, b1);
    launch(k2_attn, 128, 288, K2_SMEM, true, tmX, b2);
    launch(k3_mix1, 132, 288, K3_SMEM, true, tmW1, tmW1b, b1, w1, w2);
    launch(k4_mix2, 128, 288, K4_SMEM, true, tmW2, tmOut);
}
```

```cpp
#include <cuda_runtime.h>
#include <cuda.h>
#include <cuda_bf16.h>
#include <stdint.h>

typedef __nv_bfloat16 bf16;
#define DEVI __device__ __forceinline__

constexpr int S_ = 2048, D_ = 576, F_ = 4608;
constexpr float LN_EPS = 1e-5f;
constexpr float LOG2E = 1.4426950408889634f;

__device__ __align__(1024) bf16 g_o[S_ * D_];
__device__ __align__(1024) bf16 g_wqkv[8 * 27 * 72 * 64];
__device__ __align__(16) float g_cs[8 * 18 * 216];
__device__ __align__(1024) bf16 g_wo[8 * 72 * 72 * 8];
constexpr int KV_H = 960;
__device__ __align__(1024) float g_kv[32 * KV_H];
__device__ __align__(1024) unsigned long long g_stats[S_ * 8];
__device__ __align__(16) unsigned long long g_ln[S_];
__device__ __align__(16) float2 g_rc[S_];
__device__ __align__(1024) bf16 g_hnT[D_ * S_];
__device__ __align__(1024) bf16 g_u[D_ * F_];
constexpr int CNT_S = 64;
__device__ __align__(256) unsigned int g_cnt[8 * CNT_S];
__device__ __align__(256) unsigned long long g_claim;

DEVI uint32_t smem_u32(const void* p) { return (uint32_t)__cvta_generic_to_shared(p); }
DEVI void mbar_init(uint32_t bar, int cnt) { asm volatile("mbarrier.init.shared::cta.b64 [%0], %1;" :: "r"(bar), "r"(cnt) : "memory"); }
DEVI void mbar_expect(uint32_t bar, uint32_t bytes) { asm volatile("mbarrier.arrive.expect_tx.shared::cta.b64 _, [%0], %1;" :: "r"(bar), "r"(bytes) : "memory"); }
DEVI void mbar_wait(uint32_t bar, uint32_t parity) {
    asm volatile("{\n.reg .pred p;\n.reg .u32 it;\n"
                 "mbarrier.try_wait.parity.shared::cta.b64 p, [%0], %1;\n@p bra MW_DONE;\n"
                 "mov.u32 it, 0;\n"
                 "MW_LOOP:\nmbarrier.try_wait.parity.shared::cta.b64 p, [%0], %1;\n@p bra MW_DONE;\n"
                 "add.u32 it, it, 1;\nsetp.lt.u32 p, it, 4194304;\n@p bra MW_LOOP;\ntrap;\n"
                 "MW_DONE:\n}" :: "r"(bar), "r"(parity) : "memory");
}
DEVI void mbar_arrive(uint32_t bar) { asm volatile("mbarrier.arrive.shared::cta.b64 _, [%0];" :: "r"(bar) : "memory"); }
DEVI uint32_t mapa(uint32_t addr, uint32_t cta) { uint32_t r; asm volatile("mapa.shared::cluster.u32 %0, %1, %2;" : "=r"(r) : "r"(addr), "r"(cta)); return r; }
DEVI void mbar_arrive_remote(uint32_t raddr) { asm volatile("mbarrier.arrive.shared::cluster.b64 _, [%0];" :: "r"(raddr) : "memory"); }
DEVI void fence_mbar_init() { asm volatile("fence.mbarrier_init.release.cluster;" ::: "memory"); }
DEVI void fence_async_smem() { asm volatile("fence.proxy.async.shared::cta;" ::: "memory"); }
DEVI void cluster_arrive_relaxed() { asm volatile("barrier.cluster.arrive.relaxed.aligned;" ::: "memory"); }
DEVI void cluster_wait() { asm volatile("barrier.cluster.wait.aligned;" ::: "memory"); }
DEVI void bar_sync(int id, int n) { asm volatile("bar.sync %0, %1;" :: "r"(id), "r"(n) : "memory"); }
DEVI void bar_arrive(int id, int n) { asm volatile("bar.arrive %0, %1;" :: "r"(id), "r"(n) : "memory"); }
DEVI void pdl_wait() { asm volatile("griddepcontrol.wait;" ::: "memory"); }
DEVI void pdl_trigger() { asm volatile("griddepcontrol.launch_dependents;" ::: "memory"); }
DEVI void bulk_g2s(uint32_t dst, const void* src, uint32_t bytes, uint32_t bar) {
    asm volatile("cp.async.bulk.shared::cluster.global.mbarrier::complete_tx::bytes [%0], [%1], %2, [%3];" :: "r"(dst), "l"(src), "r"(bytes), "r"(bar) : "memory");
}
DEVI void bulk_s2g(void* dst, uint32_t src, uint32_t bytes) {
    asm volatile("cp.async.bulk.global.shared::cta.bulk_group [%0], [%1], %2;" :: "l"(dst), "r"(src), "r"(bytes) : "memory");
}
DEVI void l2_prefetch(const void* p, uint32_t bytes) { asm volatile("cp.async.bulk.prefetch.L2.global [%0], %1;" :: "l"(p), "r"(bytes) : "memory"); }
DEVI void bulk_commit() { asm volatile("cp.async.bulk.commit_group;" ::: "memory"); }
DEVI void bulk_wait_read() { asm volatile("cp.async.bulk.wait_group.read 0;" ::: "memory"); }
DEVI void tma2d(uint32_t dst, const CUtensorMap* tm, uint32_t bar, int c0, int c1) {
    asm volatile("cp.async.bulk.tensor.2d.shared::cluster.global.mbarrier::complete_tx::bytes [%0], [%1, {%3, %4}], [%2];" :: "r"(dst), "l"(tm), "r"(bar), "r"(c0), "r"(c1) : "memory");
}
DEVI void tma3d(uint32_t dst, const CUtensorMap* tm, uint32_t bar, int c0, int c1, int c2) {
    asm volatile("cp.async.bulk.tensor.3d.shared::cluster.global.mbarrier::complete_tx::bytes [%0], [%1, {%3, %4, %5}], [%2];" :: "r"(dst), "l"(tm), "r"(bar), "r"(c0), "r"(c1), "r"(c2) : "memory");
}
DEVI void tma3d_prefetch(const CUtensorMap* tm, int c0, int c1, int c2) {
    asm volatile("cp.async.bulk.prefetch.tensor.3d.L2.global [%0, {%1, %2, %3}];" :: "l"(tm), "r"(c0), "r"(c1), "r"(c2) : "memory");
}
DEVI void tma2d_store(const CUtensorMap* tm, uint32_t src, int c0, int c1) {
    asm volatile("cp.async.bulk.tensor.2d.global.shared::cta.bulk_group [%0, {%2, %3}], [%1];" :: "l"(tm), "r"(src), "r"(c0), "r"(c1) : "memory");
}
DEVI void prefetch_tm(const CUtensorMap* tm) { asm volatile("prefetch.tensormap [%0];" :: "l"(tm) : "memory"); }
DEVI uint64_t mkdesc(uint32_t addr, uint32_t lbo, uint32_t sbo, uint64_t swz) {
    return (uint64_t)((addr & 0x3FFFF) >> 4) | ((uint64_t)(lbo >> 4) << 16) | ((uint64_t)(sbo >> 4) << 32) | (swz << 62);
}
DEVI uint64_t dadv(uint64_t d, uint32_t bytes) { return (d & 0xffffffff00000000ull) | (uint64_t)((uint32_t)d + (bytes >> 4)); }
DEVI void wg_fence() { asm volatile("wgmma.fence.sync.aligned;" ::: "memory"); }
DEVI void wg_commit() { asm volatile("wgmma.commit_group.sync.aligned;" ::: "memory"); }
template<int N> DEVI void wg_wait() { asm volatile("wgmma.wait_group.sync.aligned %0;" :: "n"(N) : "memory"); }
template<int N> DEVI void reg_fence(float* d) {
    #pragma unroll
    for (int i = 0; i < N; i++) asm volatile("" : "+f"(d[i]) :: "memory");
}
DEVI uint32_t pack2(float lo, float hi) { uint32_t r; asm("cvt.rn.bf16x2.f32 %0, %1, %2;" : "=r"(r) : "f"(hi), "f"(lo)); return r; }
DEVI float bf_lo(uint32_t v) { return __uint_as_float(v << 16); }
DEVI float bf_hi(uint32_t v) { return __uint_as_float(v & 0xffff0000u); }
DEVI float ex2(float x) { float r; asm("ex2.approx.ftz.f32 %0, %1;" : "=f"(r) : "f"(x)); return r; }
DEVI float rcp(float x) { float r; asm("rcp.approx.ftz.f32 %0, %1;" : "=f"(r) : "f"(x)); return r; }
DEVI float rcp_full(float x) { float r; asm("rcp.approx.f32 %0, %1;" : "=f"(r) : "f"(x)); return r; }
DEVI float tanh_fast(float x) { float r; asm("tanh.approx.f32 %0, %1;" : "=f"(r) : "f"(x)); return r; }
DEVI void mma16816(float* c, uint32_t a0, uint32_t a1, uint32_t a2, uint32_t a3, uint32_t b0, uint32_t b1) {
    asm("mma.sync.aligned.m16n8k16.row.col.f32.bf16.bf16.f32 {%0,%1,%2,%3}, {%4,%5,%6,%7}, {%8,%9}, {%0,%1,%2,%3};"
        : "+f"(c[0]), "+f"(c[1]), "+f"(c[2]), "+f"(c[3]) : "r"(a0), "r"(a1), "r"(a2), "r"(a3), "r"(b0), "r"(b1));
}
DEVI void mma1688(float* c, uint32_t a0, uint32_t a1, uint32_t b0) {
    asm("mma.sync.aligned.m16n8k8.row.col.f32.bf16.bf16.f32 {%0,%1,%2,%3}, {%4,%5}, {%6}, {%0,%1,%2,%3};"
        : "+f"(c[0]), "+f"(c[1]), "+f"(c[2]), "+f"(c[3]) : "r"(a0), "r"(a1), "r"(b0));
}
DEVI void ldsm4t(uint32_t addr, uint32_t& r0, uint32_t& r1, uint32_t& r2, uint32_t& r3) {
    asm volatile("ldmatrix.sync.aligned.m8n8.x4.trans.shared.b16 {%0,%1,%2,%3}, [%4];" : "=r"(r0), "=r"(r1), "=r"(r2), "=r"(r3) : "r"(addr) : "memory");
}
DEVI void stsm4(uint32_t addr, uint32_t r0, uint32_t r1, uint32_t r2, uint32_t r3) {
    asm volatile("stmatrix.sync.aligned.m8n8.x4.shared.b16 [%0], {%1,%2,%3,%4};" :: "r"(addr), "r"(r0), "r"(r1), "r"(r2), "r"(r3) : "memory");
}
DEVI void stsm2(uint32_t addr, uint32_t r0, uint32_t r1) {
    asm volatile("stmatrix.sync.aligned.m8n8.x2.shared.b16 [%0], {%1,%2};" :: "r"(addr), "r"(r0), "r"(r1) : "memory");
}
DEVI void sts128(uint32_t addr, uint32_t r0, uint32_t r1, uint32_t r2, uint32_t r3) {
    asm volatile("st.shared.v4.b32 [%0], {%1,%2,%3,%4};" :: "r"(addr), "r"(r0), "r"(r1), "r"(r2), "r"(r3) : "memory");
}
DEVI void sts32(uint32_t addr, uint32_t r0) { asm volatile("st.shared.b32 [%0], %1;" :: "r"(addr), "r"(r0) : "memory"); }
DEVI void wgmma_rs_n80(float* d, uint32_t a0, uint32_t a1, uint32_t a2, uint32_t a3, uint64_t db, int sd) {
  asm volatile("{\n.reg .pred p;\nsetp.ne.b32 p, %45, 0;\n"
    "wgmma.mma_async.sync.aligned.m64n80k16.f32.bf16.bf16 {%0, %1, %2, %3, %4, %5, %6, %7, %8, %9, %10, %11, %12, %13, %14, %15, %16, %17, %18, %19, %20, %21, %22, %23, %24, %25, %26, %27, %28, %29, %30, %31, %32, %33, %34, %35, %36, %37, %38, %39}, {%40, %41, %42, %43}, %44, p, 1, 1, 0;\n}\n"
    : "+f"(d[0]), "+f"(d[1]), "+f"(d[2]), "+f"(d[3]), "+f"(d[4]), "+f"(d[5]), "+f"(d[6]), "+f"(d[7]), "+f"(d[8]), "+f"(d[9]), "+f"(d[10]), "+f"(d[11]), "+f"(d[12]), "+f"(d[13]), "+f"(d[14]), "+f"(d[15]), "+f"(d[16]), "+f"(d[17]), "+f"(d[18]), "+f"(d[19]), "+f"(d[20]), "+f"(d[21]), "+f"(d[22]), "+f"(d[23]), "+f"(d[24]), "+f"(d[25]), "+f"(d[26]), "+f"(d[27]), "+f"(d[28]), "+f"(d[29]), "+f"(d[30]), "+f"(d[31]), "+f"(d[32]), "+f"(d[33]), "+f"(d[34]), "+f"(d[35]), "+f"(d[36]), "+f"(d[37]), "+f"(d[38]), "+f"(d[39]) : "r"(a0), "r"(a1), "r"(a2), "r"(a3), "l"(db), "r"(sd));
}
template<int TA, int TB> DEVI void wgmma_n40(float* d, uint64_t da, uint64_t db, int sd) {
  asm volatile("{\n.reg .pred p;\nsetp.ne.b32 p, %22, 0;\n"
    "wgmma.mma_async.sync.aligned.m64n40k16.f32.bf16.bf16 {%0, %1, %2, %3, %4, %5, %6, %7, %8, %9, %10, %11, %12, %13, %14, %15, %16, %17, %18, %19}, %20, %21, p, 1, 1, %23, %24;\n}\n"
    : "+f"(d[0]), "+f"(d[1]), "+f"(d[2]), "+f"(d[3]), "+f"(d[4]), "+f"(d[5]), "+f"(d[6]), "+f"(d[7]), "+f"(d[8]), "+f"(d[9]), "+f"(d[10]), "+f"(d[11]), "+f"(d[12]), "+f"(d[13]), "+f"(d[14]), "+f"(d[15]), "+f"(d[16]), "+f"(d[17]), "+f"(d[18]), "+f"(d[19]) : "l"(da), "l"(db), "r"(sd), "n"(TA), "n"(TB));
}
template<int TA, int TB> DEVI void wgmma_n48(float* d, uint64_t da, uint64_t db, int sd) {
  asm volatile("{\n.reg .pred p;\nsetp.ne.b32 p, %26, 0;\n"
    "wgmma.mma_async.sync.aligned.m64n48k16.f32.bf16.bf16 {%0, %1, %2, %3, %4, %5, %6, %7, %8, %9, %10, %11, %12, %13, %14, %15, %16, %17, %18, %19, %20, %21, %22, %23}, %24, %25, p, 1, 1, %27, %28;\n}\n"
    : "+f"(d[0]), "+f"(d[1]), "+f"(d[2]), "+f"(d[3]), "+f"(d[4]), "+f"(d[5]), "+f"(d[6]), "+f"(d[7]), "+f"(d[8]), "+f"(d[9]), "+f"(d[10]), "+f"(d[11]), "+f"(d[12]), "+f"(d[13]), "+f"(d[14]), "+f"(d[15]), "+f"(d[16]), "+f"(d[17]), "+f"(d[18]), "+f"(d[19]), "+f"(d[20]), "+f"(d[21]), "+f"(d[22]), "+f"(d[23]) : "l"(da), "l"(db), "r"(sd), "n"(TA), "n"(TB));
}
template<int TA, int TB> DEVI void wgmma_n72(float* d, uint64_t da, uint64_t db, int sd) {
  asm volatile("{\n.reg .pred p;\nsetp.ne.b32 p, %38, 0;\n"
    "wgmma.mma_async.sync.aligned.m64n72k16.f32.bf16.bf16 {%0, %1, %2, %3, %4, %5, %6, %7, %8, %9, %10, %11, %12, %13, %14, %15, %16, %17, %18, %19, %20, %21, %22, %23, %24, %25, %26, %27, %28, %29, %30, %31, %32, %33, %34, %35}, %36, %37, p, 1, 1, %39, %40;\n}\n"
    : "+f"(d[0]), "+f"(d[1]), "+f"(d[2]), "+f"(d[3]), "+f"(d[4]), "+f"(d[5]), "+f"(d[6]), "+f"(d[7]), "+f"(d[8]), "+f"(d[9]), "+f"(d[10]), "+f"(d[11]), "+f"(d[12]), "+f"(d[13]), "+f"(d[14]), "+f"(d[15]), "+f"(d[16]), "+f"(d[17]), "+f"(d[18]), "+f"(d[19]), "+f"(d[20]), "+f"(d[21]), "+f"(d[22]), "+f"(d[23]), "+f"(d[24]), "+f"(d[25]), "+f"(d[26]), "+f"(d[27]), "+f"(d[28]), "+f"(d[29]), "+f"(d[30]), "+f"(d[31]), "+f"(d[32]), "+f"(d[33]), "+f"(d[34]), "+f"(d[35]) : "l"(da), "l"(db), "r"(sd), "n"(TA), "n"(TB));
}
template<int TA, int TB> DEVI void wgmma_n96(float* d, uint64_t da, uint64_t db, int sd) {
  asm volatile("{\n.reg .pred p;\nsetp.ne.b32 p, %50, 0;\n"
    "wgmma.mma_async.sync.aligned.m64n96k16.f32.bf16.bf16 {%0, %1, %2, %3, %4, %5, %6, %7, %8, %9, %10, %11, %12, %13, %14, %15, %16, %17, %18, %19, %20, %21, %22, %23, %24, %25, %26, %27, %28, %29, %30, %31, %32, %33, %34, %35, %36, %37, %38, %39, %40, %41, %42, %43, %44, %45, %46, %47}, %48, %49, p, 1, 1, %51, %52;\n}\n"
    : "+f"(d[0]), "+f"(d[1]), "+f"(d[2]), "+f"(d[3]), "+f"(d[4]), "+f"(d[5]), "+f"(d[6]), "+f"(d[7]), "+f"(d[8]), "+f"(d[9]), "+f"(d[10]), "+f"(d[11]), "+f"(d[12]), "+f"(d[13]), "+f"(d[14]), "+f"(d[15]), "+f"(d[16]), "+f"(d[17]), "+f"(d[18]), "+f"(d[19]), "+f"(d[20]), "+f"(d[21]), "+f"(d[22]), "+f"(d[23]), "+f"(d[24]), "+f"(d[25]), "+f"(d[26]), "+f"(d[27]), "+f"(d[28]), "+f"(d[29]), "+f"(d[30]), "+f"(d[31]), "+f"(d[32]), "+f"(d[33]), "+f"(d[34]), "+f"(d[35]), "+f"(d[36]), "+f"(d[37]), "+f"(d[38]), "+f"(d[39]), "+f"(d[40]), "+f"(d[41]), "+f"(d[42]), "+f"(d[43]), "+f"(d[44]), "+f"(d[45]), "+f"(d[46]), "+f"(d[47]) : "l"(da), "l"(db), "r"(sd), "n"(TA), "n"(TB));
}
template<int TA, int TB> DEVI void wgmma_n144(float* d, uint64_t da, uint64_t db, int sd) {
  asm volatile("{\n.reg .pred p;\nsetp.ne.b32 p, %74, 0;\n"
    "wgmma.mma_async.sync.aligned.m64n144k16.f32.bf16.bf16 {%0, %1, %2, %3, %4, %5, %6, %7, %8, %9, %10, %11, %12, %13, %14, %15, %16, %17, %18, %19, %20, %21, %22, %23, %24, %25, %26, %27, %28, %29, %30, %31, %32, %33, %34, %35, %36, %37, %38, %39, %40, %41, %42, %43, %44, %45, %46, %47, %48, %49, %50, %51, %52, %53, %54, %55, %56, %57, %58, %59, %60, %61, %62, %63, %64, %65, %66, %67, %68, %69, %70, %71}, %72, %73, p, 1, 1, %75, %76;\n}\n"
    : "+f"(d[0]), "+f"(d[1]), "+f"(d[2]), "+f"(d[3]), "+f"(d[4]), "+f"(d[5]), "+f"(d[6]), "+f"(d[7]), "+f"(d[8]), "+f"(d[9]), "+f"(d[10]), "+f"(d[11]), "+f"(d[12]), "+f"(d[13]), "+f"(d[14]), "+f"(d[15]), "+f"(d[16]), "+f"(d[17]), "+f"(d[18]), "+f"(d[19]), "+f"(d[20]), "+f"(d[21]), "+f"(d[22]), "+f"(d[23]), "+f"(d[24]), "+f"(d[25]), "+f"(d[26]), "+f"(d[27]), "+f"(d[28]), "+f"(d[29]), "+f"(d[30]), "+f"(d[31]), "+f"(d[32]), "+f"(d[33]), "+f"(d[34]), "+f"(d[35]), "+f"(d[36]), "+f"(d[37]), "+f"(d[38]), "+f"(d[39]), "+f"(d[40]), "+f"(d[41]), "+f"(d[42]), "+f"(d[43]), "+f"(d[44]), "+f"(d[45]), "+f"(d[46]), "+f"(d[47]), "+f"(d[48]), "+f"(d[49]), "+f"(d[50]), "+f"(d[51]), "+f"(d[52]), "+f"(d[53]), "+f"(d[54]), "+f"(d[55]), "+f"(d[56]), "+f"(d[57]), "+f"(d[58]), "+f"(d[59]), "+f"(d[60]), "+f"(d[61]), "+f"(d[62]), "+f"(d[63]), "+f"(d[64]), "+f"(d[65]), "+f"(d[66]), "+f"(d[67]), "+f"(d[68]), "+f"(d[69]), "+f"(d[70]), "+f"(d[71]) : "l"(da), "l"(db), "r"(sd), "n"(TA), "n"(TB));
}
template<int TA, int TB> DEVI void wgmma_n160(float* d, uint64_t da, uint64_t db, int sd) {
  asm volatile("{\n.reg .pred p;\nsetp.ne.b32 p, %82, 0;\n"
    "wgmma.mma_async.sync.aligned.m64n160k16.f32.bf16.bf16 {%0, %1, %2, %3, %4, %5, %6, %7, %8, %9, %10, %11, %12, %13, %14, %15, %16, %17, %18, %19, %20, %21, %22, %23, %24, %25, %26, %27, %28, %29, %30, %31, %32, %33, %34, %35, %36, %37, %38, %39, %40, %41, %42, %43, %44, %45, %46, %47, %48, %49, %50, %51, %52, %53, %54, %55, %56, %57, %58, %59, %60, %61, %62, %63, %64, %65, %66, %67, %68, %69, %70, %71, %72, %73, %74, %75, %76, %77, %78, %79}, %80, %81, p, 1, 1, %83, %84;\n}\n"
    : "+f"(d[0]), "+f"(d[1]), "+f"(d[2]), "+f"(d[3]), "+f"(d[4]), "+f"(d[5]), "+f"(d[6]), "+f"(d[7]), "+f"(d[8]), "+f"(d[9]), "+f"(d[10]), "+f"(d[11]), "+f"(d[12]), "+f"(d[13]), "+f"(d[14]), "+f"(d[15]), "+f"(d[16]), "+f"(d[17]), "+f"(d[18]), "+f"(d[19]), "+f"(d[20]), "+f"(d[21]), "+f"(d[22]), "+f"(d[23]), "+f"(d[24]), "+f"(d[25]), "+f"(d[26]), "+f"(d[27]), "+f"(d[28]), "+f"(d[29]), "+f"(d[30]), "+f"(d[31]), "+f"(d[32]), "+f"(d[33]), "+f"(d[34]), "+f"(d[35]), "+f"(d[36]), "+f"(d[37]), "+f"(d[38]), "+f"(d[39]), "+f"(d[40]), "+f"(d[41]), "+f"(d[42]), "+f"(d[43]), "+f"(d[44]), "+f"(d[45]), "+f"(d[46]), "+f"(d[47]), "+f"(d[48]), "+f"(d[49]), "+f"(d[50]), "+f"(d[51]), "+f"(d[52]), "+f"(d[53]), "+f"(d[54]), "+f"(d[55]), "+f"(d[56]), "+f"(d[57]), "+f"(d[58]), "+f"(d[59]), "+f"(d[60]), "+f"(d[61]), "+f"(d[62]), "+f"(d[63]), "+f"(d[64]), "+f"(d[65]), "+f"(d[66]), "+f"(d[67]), "+f"(d[68]), "+f"(d[69]), "+f"(d[70]), "+f"(d[71]), "+f"(d[72]), "+f"(d[73]), "+f"(d[74]), "+f"(d[75]), "+f"(d[76]), "+f"(d[77]), "+f"(d[78]), "+f"(d[79]) : "l"(da), "l"(db), "r"(sd), "n"(TA), "n"(TB));
}

__host__ __device__ constexpr int ka_seq(int p, int c) { return p == 0 ? c : c >= 5 ? 2 * c - 2 + p : p == 1 ? 17 + c : 22 + c; }
__global__ void __launch_bounds__(256, 3) k0_prep(const bf16* __restrict__ x, const bf16* __restrict__ wqkv, const bf16* __restrict__ wphi) {
    __shared__ __align__(16) uint32_t s_in[64 * 36 + 64];
    pdl_trigger();
    const int tid = threadIdx.x, lane = tid & 31, warp = __shfl_sync(~0u, tid >> 5, 0);
    const int c = blockIdx.x, g = blockIdx.y, p = blockIdx.z;
    const bool fold = p == 0 || p == 2;
    const int b = (p * 8 + g) * 9 + c;
    if (p == 3) {
        const int j = b - 216;
        const uint4 z = make_uint4(0u, 0u, 0u, 0u);
        if (j < 32) reinterpret_cast<uint4*>(g_stats)[j * 256 + tid] = z;
        else if (j < 62) reinterpret_cast<uint4*>(g_kv)[(j - 32) * 256 + tid] = z;
        else if (j == 66 && tid < 8) g_cnt[tid * CNT_S] = 0u;
        return;
    }
    constexpr int ld = 1728;
    const bf16* src = wqkv + ((p == 2 ? 0 : p + 1) * 576 + c * 64 * ld + g * 72);
    const uint32_t si = smem_u32(s_in);
    #pragma unroll
    for (int j = 0; j < 3; j++) {
        const int i = tid + j * 256, r = (i * 7282) >> 16;
        if (j < 2 || tid < 64) asm volatile("cp.async.cg.shared.global [%0], [%1], 16;" :: "r"(si + i * 16 + (r >> 3) * 32), "l"(src + (r * (ld - 72) + i * 8)) : "memory");
    }
    const int t = warp & 3, half = warp >> 2, g8 = lane >> 2, c4 = lane & 3;
    uint32_t af[3][3];
    if (fold) {
        const unsigned short* ph = reinterpret_cast<const unsigned short*>(wphi) + (g * 4 + t) * 324;
        unsigned short lo[3][3], hi[3][3];
        #pragma unroll
        for (int fb = 0; fb < 3; fb++)
            #pragma unroll
            for (int db = 0; db < 3; db++) {
                const int o = min(2 * c4 + 8 * db, 16) * 18 + min(g8 + 8 * fb, 17);
                lo[fb][db] = __ldg(ph + o); hi[fb][db] = __ldg(ph + o + 18);
            }
        #pragma unroll
        for (int fb = 0; fb < 3; fb++)
            #pragma unroll
            for (int db = 0; db < 3; db++) af[fb][db] = (uint32_t)lo[fb][db] | ((uint32_t)hi[fb][db] << 16);
    } else {
        const uint32_t v = (g8 == 2 * c4 ? 0x3f80u : 0u) | (g8 == 2 * c4 + 1 ? 0x3f800000u : 0u);
        #pragma unroll
        for (int fb = 0; fb < 3; fb++)
            #pragma unroll
            for (int db = 0; db < 3; db++) af[fb][db] = fb == db ? v : 0u;
    }
    bf16* dst = g_wqkv + (g * 27 + ka_seq(p, c)) * 4608;
    float* csd = g_cs + (g * 18 + c * 2 + half) * 216 + p * 72 + 2 * t;
    asm volatile("cp.async.wait_all;" ::: "memory");
    __syncthreads();
    if (tid < 96 && b < 192) asm volatile("prefetch.global.L2 [%0];" :: "l"(x + b * 6144 + tid * 64));
    uint32_t ov[3][4];
    const uint32_t* wr = &s_in[(half * 32 + (g8 >> 1) * 8 + (g8 & 1)) * 36 + (half * 4 + (g8 >> 1)) * 8 + t * 9 + c4];
    #pragma unroll
    for (int j = 0; j < 4; j++) {
        const uint32_t b0 = wr[j * 72], b1 = wr[j * 72 + 4], b2 = c4 == 0 ? wr[j * 72 + 8] : 0u;
        float c0[4] = {0.f, 0.f, 0.f, 0.f}, c1[4] = {0.f, 0.f, 0.f, 0.f};
        mma16816(c0, af[0][0], af[1][0], af[0][1], af[1][1], b0, b1);
        mma1688(c0, af[0][2], af[1][2], b2);
        mma16816(c1, af[2][0], 0u, af[2][1], 0u, b0, b1);
        mma1688(c1, af[2][2], 0u, b2);
        ov[0][j] = pack2(c0[0], c0[1]); ov[1][j] = pack2(c0[2], c0[3]); ov[2][j] = pack2(c1[0], c1[1]);
    }
    {
        const int nl = 2 * t + (g8 & 1);
        uint4* o = reinterpret_cast<uint4*>(dst) + ((g8 >> 1) * 8 + nl) * 8 + ((half * 4 + c4) ^ nl);
        o[0] = make_uint4(ov[0][0], ov[0][1], ov[0][2], ov[0][3]);
        o[256] = make_uint4(ov[1][0], ov[1][1], ov[1][2], ov[1][3]);
        if (g8 < 2) o[512] = make_uint4(ov[2][0], ov[2][1], ov[2][2], ov[2][3]);
    }
    {
        float cs0[4] = {0.f, 0.f, 0.f, 0.f}, cs1[4] = {0.f, 0.f, 0.f, 0.f};
        mma16816(cs0, ov[0][0], ov[1][0], ov[0][1], ov[1][1], 0x3f803f80u, 0x3f803f80u);
        mma16816(cs1, ov[2][0], 0u, ov[2][1], 0u, 0x3f803f80u, 0x3f803f80u);
        mma16816(cs0, ov[0][2], ov[1][2], ov[0][3], ov[1][3], 0x3f803f80u, 0x3f803f80u);
        mma16816(cs1, ov[2][2], 0u, ov[2][3], 0u, 0x3f803f80u, 0x3f803f80u);
        const int f = g8 + 8 * c4;
        if (f < 18) csd[8 * (f >> 1) + (f & 1)] = c4 == 0 ? cs0[0] : c4 == 1 ? cs0[2] : cs1[0];
    }
}

DEVI void dual_softmax(const float* a, float scale, uint32_t* o) {
    float mx = a[0], mn = a[0];
    #pragma unroll
    for (int j = 1; j < 18; j++) { mx = fmaxf(mx, a[j]); mn = fminf(mn, a[j]); }
    const float mxs = -mx * scale, mns = mn * scale;
    float ep[18], en[18], sp = 0.f, sn = 0.f;
    #pragma unroll
    for (int j = 0; j < 18; j++) {
        ep[j] = ex2(fmaf(a[j], scale, mxs)); sp += ep[j];
        en[j] = ex2(fmaf(a[j], -scale, mns)); sn += en[j];
    }
    const float rp = rcp(sp), rn = rcp(sn);
    #pragma unroll
    for (int j = 0; j < 9; j++) {
        o[j] = pack2(ep[2 * j] * rp, ep[2 * j + 1] * rp);
        o[9 + j] = pack2(en[2 * j] * rn, en[2 * j + 1] * rn);
    }
}

DEVI uint4 ldg128(const void* p) { uint4 v; asm volatile("ld.global.cg.v4.u32 {%0,%1,%2,%3}, [%4];" : "=r"(v.x), "=r"(v.y), "=r"(v.z), "=r"(v.w) : "l"(p)); return v; }
DEVI uint2 ldg64(const void* p) { uint2 v; asm volatile("ld.global.cg.v2.u32 {%0,%1}, [%2];" : "=r"(v.x), "=r"(v.y) : "l"(p)); return v; }
DEVI uint4 lds128(uint32_t a) { uint4 v; asm volatile("ld.shared.v4.u32 {%0,%1,%2,%3}, [%4];" : "=r"(v.x), "=r"(v.y), "=r"(v.z), "=r"(v.w) : "r"(a) : "memory"); return v; }
DEVI uint2 lds64(uint32_t a) { uint2 v; asm volatile("ld.shared.v2.u32 {%0,%1}, [%2];" : "=r"(v.x), "=r"(v.y) : "r"(a) : "memory"); return v; }
DEVI uint32_t packu(uint32_t lo, uint32_t hi) { return pack2(__uint_as_float(lo), __uint_as_float(hi)); }
DEVI void spin_ge(const unsigned int* p, unsigned int n) {
    uint32_t f; int it = 0;
    do {
        asm volatile("ld.acquire.gpu.global.u32 %0, [%1];" : "=r"(f) : "l"(p) : "memory");
        if (++it > (1 << 22)) __trap();
    } while (f < n);
}
constexpr int KA_PRE = 3, KA_REC = 5 * 16384, KA_B = 147456, KA_CS = KA_B + 9 * 9216, KA_LN = KA_CS + 864, KA_BAR = KA_LN + 1024, KA_SMEM = KA_BAR + 160;
static_assert(KA_SMEM <= 232448, "smem");
DEVI void ka_kv(uint32_t recs, float* kvh, int w4, int lane) {
    float ck[2][20];
    const uint64_t dr = mkdesc(recs, 8192, 1024, 1);
    wg_fence();
    #pragma unroll
    for (int ks = 0; ks < 4; ks++)
        #pragma unroll
        for (int hh = 0; hh < 2; hh++) wgmma_n40<1, 1>(ck[hh], dadv(dr, hh * 8192 + ks * 2048), dadv(dr, hh * 8192 + ks * 2048), ks != 0);
    wg_commit();
    wg_wait<0>();
    reg_fence<20>(ck[0]); reg_fence<20>(ck[1]);
    if (w4 >= 2) {
        #pragma unroll
        for (int e = 1; e >= 0; e--) {
            const int nt = 2 * w4 + e - 5;
            if (nt >= 0 && (nt < 2 || lane < 12)) {
                float* p = kvh + nt * 320;
                float q[10];
                #pragma unroll
                for (int j = 0; j < 10; j++) q[j] = ck[0][(j >> 1) * 4 + 2 * e + (j & 1)] + ck[1][(j >> 1) * 4 + 2 * e + (j & 1)];
                asm volatile("red.global.add.v4.f32 [%0], {%1, %2, %3, %4};" :: "l"(p + lane * 4), "f"(q[0]), "f"(q[1]), "f"(q[2]), "f"(q[3]) : "memory");
                asm volatile("red.global.add.v4.f32 [%0], {%1, %2, %3, %4};" :: "l"(p + 128 + lane * 4), "f"(q[4]), "f"(q[5]), "f"(q[6]), "f"(q[7]) : "memory");
                if ((lane & 3) < 2) asm volatile("red.global.add.v2.f32 [%0], {%1, %2};" :: "l"(p + 256 + lane * 2), "f"(q[8]), "f"(q[9]) : "memory");
            }
        }
        __syncwarp();
        bar_arrive(2, 288);
    }
}
DEVI int gpc_pos() {
    unsigned smid, nsm;
    asm volatile("mov.u32 %0, %%smid;" : "=r"(smid));
    asm volatile("mov.u32 %0, %%nsmid;" : "=r"(nsm));
    if (nsm != 132) return blockIdx.x;
    const int tpc = smid >> 1, o = smid & 1;
    if (smid == 13 || smid == 15) return 124 + tpc;
    if (tpc < 32) return (tpc & 7) * 16 + (tpc >> 3) * 2 + o;
    if (tpc < 60) { const int j = tpc - 32, r = j / 7; return (1 + j - r * 7) * 16 + 8 + r * 2 + o; }
    if (tpc < 62) return o ? 68 + tpc : (tpc - 54) * 16 + 1;
    return 8 + (tpc - 62) * 2 + o;
}
__global__ void __launch_bounds__(640, 1) ka_front(const __grid_constant__ CUtensorMap tmXA, const bf16* __restrict__ x, const bf16* __restrict__ wo, const bf16* __restrict__ w1, const bf16* __restrict__ b1) {
    extern __shared__ __align__(1024) char smem[];
    const uint32_t sm = smem_u32(smem);
    const uint32_t bFull = sm + KA_BAR, bEmpty = bFull + 9 * 8, bLn = bEmpty + 9 * 8;
    const int tid = threadIdx.x, lane = tid & 31, warp = __shfl_sync(~0u, tid >> 5, 0);
    const int pos = gpc_pos();
    if (pos >= 128) {
        const int ns = pos - 128;
        if (tid == 0) {
            #pragma unroll
            for (int q = 0; q < 6; q++) mbar_init(bFull + q * 8, 1);
            fence_mbar_init();
            #pragma unroll
            for (int q = 0; q < 6; q++) mbar_expect(bFull + q * 8, 96 * 288);
        }
        __syncthreads();
        if (tid < 576) {
            const int h = tid / 18, d = tid - h * 18, r = (h >> 2) * 72 + (d >> 1) * 8 + 2 * (h & 3) + (d & 1);
            bulk_g2s(sm + r * 304, wo + tid * 576 + ns * 144, 288, bFull + (r / 96) * 8);
        }
        #pragma unroll 1
        for (int q = 0; q < 6; q++) {
            const uint32_t ob = sm + 175104 + (q & 1) * 27648;
            mbar_wait(bFull + q * 8, 0);
            if (tid == 0) asm volatile("cp.async.bulk.wait_group.read 1;" ::: "memory");
            __syncthreads();
            if (warp < 18) {
                #pragma unroll
                for (int rb = 0; rb < 3; rb++) {
                    uint32_t r0, r1, r2, r3;
                    ldsm4t(sm + (q * 96 + rb * 32 + lane) * 304 + warp * 16, r0, r1, r2, r3);
                    stsm4(ob + (warp / 9) * 13824 + ((rb * 4 + (lane >> 3)) * 72 + (warp % 9) * 8 + (lane & 7)) * 16, r0, r1, r2, r3);
                }
            }
            fence_async_smem();
            __syncthreads();
            if (tid == 0) {
                bulk_s2g(g_wo + (ns * 2) * (72 * 576) + q * 6912, ob, 13824);
                bulk_s2g(g_wo + (ns * 2 + 1) * (72 * 576) + q * 6912, ob + 13824, 13824);
                bulk_commit();
            }
        }
        if (tid == 0) {
            asm volatile("cp.async.bulk.wait_group 0;\nfence.proxy.async.global;\nfence.acq_rel.gpu;" ::: "memory");
            pdl_wait();
            pdl_trigger();
        }
        return;
    }
    const int g = ((pos >> 4) & 1) * 4 + (pos & 3), mt = (pos >> 5) * 4 + ((pos >> 2) & 3);
    if (warp >= 16) {
        asm volatile("setmaxnreg.dec.sync.aligned.u32 32;");
        if (warp == 16) {
            if (lane == 0) {
                #pragma unroll
                for (int c = 0; c < 9; c++) { mbar_init(bFull + c * 8, 1); mbar_init(bEmpty + c * 8, 8); }
                mbar_init(bLn, 64);
                fence_mbar_init();
            }
            __syncwarp();
            bar_arrive(0, 640);
        } else {
            bar_sync(0, 640);
            if (tid == 544) {
                #pragma unroll
                for (int c = 0; c < 9; c++) mbar_expect(bFull + c * 8, 16384 + 9216);
            }
            __syncwarp();
        }
        if (tid == 512) {
            #pragma unroll
            for (int c = 0; c < KA_PRE; c++) tma3d(sm + c * 16384, &tmXA, bFull + c * 8, 0, mt * 128, c);
            pdl_wait();
            const bf16* wsrc = g_wqkv + g * (27 * 4608);
            const uint32_t sb = sm + KA_B;
            #pragma unroll
            for (int c = 0; c < 9; c++) {
                bulk_g2s(sb + c * 9216, wsrc + c * 4608, 9216, bFull + c * 8);
                const int xc = c + KA_PRE - 2;
                if (c >= 2 && xc < 9) tma3d(sm + xc * 16384, &tmXA, bFull + xc * 8, 0, mt * 128, xc);
            }
            pdl_trigger();
            #pragma unroll 1
            for (int p = 1; p < 3; p++) {
                #pragma unroll
                for (int c = 0; c < 9; c++) {
                    mbar_wait(bEmpty + c * 8, p - 1); mbar_expect(bFull + c * 8, 9216);
                    bulk_g2s(sb + c * 9216, wsrc + (p * 9 + c) * 4608, 9216, bFull + c * 8);
                }
            }
            l2_prefetch(w1 + pos * 13824, 27648);
            if (pos == 0) l2_prefetch(b1, 9216);
        } else if (warp == 17) {
            bar_sync(2, 288);
            if (lane == 0) {
                asm volatile("red.release.gpu.global.add.u32 [%0], 1;" :: "l"(g_cnt + g * CNT_S) : "memory");
                spin_ge(g_cnt + g * CNT_S, 16);
            }
            __syncwarp();
            bar_arrive(1, 288);
        } else if (warp >= 18) {
            const int m = warp - 18;
            {
                const unsigned long long* lp = g_ln + mt * 128 + m * 64 + (lane >> 3) * 16 + (lane & 7);
                unsigned long long r0, r1; int it = 0;
                __nanosleep(700);
                while (true) {
                    asm volatile("ld.relaxed.gpu.global.u64 %0, [%1];" : "=l"(r0) : "l"(lp) : "memory");
                    asm volatile("ld.relaxed.gpu.global.u64 %0, [%1];" : "=l"(r1) : "l"(lp + 8) : "memory");
                    if (__all_sync(~0u, (long long)(r0 & r1) < 0)) break;
                    if (++it > (1 << 22)) __trap();
                }
                sts128(sm + KA_LN + (m * 32 + lane) * 16, (uint32_t)r0, (uint32_t)(r0 >> 32), (uint32_t)r1, (uint32_t)(r1 >> 32));
                mbar_arrive(bLn);
            }
        }
    } else {
        const int xrow = mt * 128 + g * 16 + warp;
        uint4 xv[3];
        {
            const uint4* xr = reinterpret_cast<const uint4*>(x + xrow * D_);
            xv[0] = ldg128(xr + lane); xv[1] = ldg128(xr + lane + 32); xv[2] = ldg128(xr + 64 + (lane & 7));
        }
        asm volatile("setmaxnreg.inc.sync.aligned.u32 112;");
        bar_sync(0, 640);
        const int wg = warp >> 2, m = wg & 1, w4 = warp & 3, gq = lane >> 2, t = lane & 3;
        {
            const uint32_t w[12] = {xv[0].x, xv[0].y, xv[0].z, xv[0].w, xv[1].x, xv[1].y, xv[1].z, xv[1].w, xv[2].x, xv[2].y, xv[2].z, xv[2].w};
            float s = 0.f, s2 = 0.f;
            #pragma unroll
            for (int i = 0; i < 12; i++) { if (i < 8) s += bf_lo(w[i]) + bf_hi(w[i]); else s2 += bf_lo(w[i]) + bf_hi(w[i]); }
            if (lane < 8) s += s2;
            #pragma unroll
            for (int o = 16; o; o >>= 1) s += __shfl_xor_sync(~0u, s, o);
            const float mean = s * (1.f / D_);
            float q = 0.f, q2 = 0.f;
            #pragma unroll
            for (int i = 0; i < 12; i++) {
                const float e0 = bf_lo(w[i]) - mean, e1 = bf_hi(w[i]) - mean;
                if (i < 8) q += e0 * e0 + e1 * e1; else q2 += e0 * e0 + e1 * e1;
            }
            if (lane < 8) q += q2;
            #pragma unroll
            for (int o = 16; o; o >>= 1) q += __shfl_xor_sync(~0u, q, o);
            const unsigned long long lrec = ((unsigned long long)(__float_as_uint(rsqrtf(q * (1.f / D_) + LN_EPS)) | 0x80000000u) << 32) | __float_as_uint(mean);
            if (lane == 0) asm volatile("st.relaxed.gpu.global.u64 [%0], %1;" :: "l"(g_ln + xrow), "l"(lrec) : "memory");
        }
        float2 ln0, ln1;
        auto ln_get = [&]() {
            mbar_wait(bLn, 0);
            const uint4 v = lds128(sm + KA_LN + (m * 32 + w4 * 8 + gq) * 16);
            ln0 = make_float2(__uint_as_float(v.x), fabsf(__uint_as_float(v.y))); ln1 = make_float2(__uint_as_float(v.z), fabsf(__uint_as_float(v.w)));
        };
        const uint64_t da = mkdesc(sm + m * 8192, 16, 1024, 1), db = mkdesc(sm + KA_B, 16, 1024, 1);
        const uint32_t csa = sm + KA_CS + 8 * t;
        const int rot = (gq + 2 * t) & 7;
        const uint32_t rec = sm + KA_REC + t * 16384 + m * 8192 + (w4 * 16 + rot) * 128;
        const uint32_t kvb = sm + KA_REC;
        if (wg < 2) {
            float acc[36]; uint2 cs[9];
            #pragma unroll
            for (int c = 0; c < 9; c++) {
                mbar_wait(bFull + c * 8, 0);
                wg_fence();
                #pragma unroll
                for (int kk = 0; kk < 4; kk++) wgmma_n72<0, 0>(acc, dadv(da, c * 16384 + kk * 32), dadv(db, c * 9216 + kk * 32), (c | kk) != 0);
                wg_commit();
                if (c > 0) { wg_wait<1>(); if (lane == 0) mbar_arrive(bEmpty + (c - 1) * 8); }
            }
            wg_wait<0>();
            reg_fence<36>(acc);
            bar_arrive(5, 512);
            if (lane == 0) mbar_arrive(bEmpty + 8 * 8);
            bar_sync(6, 384);
            #pragma unroll
            for (int j = 0; j < 9; j++) cs[j] = lds64(csa + 32 * j);
            ln_get();
            uint32_t ph[2][18];
            #pragma unroll
            for (int r = 0; r < 2; r++) {
                float a[18];
                const float2 ln = r ? ln1 : ln0;
                #pragma unroll
                for (int j = 0; j < 9; j++) { a[2 * j] = fmaf(-ln.x, __uint_as_float(cs[j].x), acc[4 * j + 2 * r]); a[2 * j + 1] = fmaf(-ln.x, __uint_as_float(cs[j].y), acc[4 * j + 2 * r + 1]); }
                dual_softmax(a, ln.y * LOG2E, ph[r]);
            }
            #pragma unroll
            for (int j = 0; j < 18; j++) asm volatile("" : "+r"(ph[0][j]), "+r"(ph[1][j]));
            bar_sync(3 + m, 256);
            #pragma unroll
            for (int r = 0; r < 2; r++) {
                #pragma unroll
                for (int j = 0; j < 4; j++) sts128(rec + r * 1024 + ((j ^ rot) << 4), ph[r][4 * j], ph[r][4 * j + 1], ph[r][4 * j + 2], ph[r][4 * j + 3]);
                sts128(rec + r * 1024 + ((4 ^ rot) << 4), ph[r][16], ph[r][17], 0u, 0u);
            }
            fence_async_smem();
            bar_sync(8, 512);
            ka_kv(sm + KA_REC + wg * 16384, g_kv + (g * 4 + wg) * KV_H, w4, lane);
            bar_arrive(7, 512);
            bar_sync(11, 256);
            #pragma unroll
            for (int j = 0; j < 6; j++) if (j < 5 || tid < 196) sts128(kvb + (j * 256 + tid) * 16, 0u, 0u, 0u, 0u);
            const float* kp = g_kv + (g * 4 + w4) * KV_H + lane * 2;
            const uint32_t kd = kvb + t * 1312 + ((gq >> 1) * 8 + 2 * w4 + (gq & 1)) * 16 + w4 * 4;
            bar_sync(1, 288);
            if (m == 0) {
                const uint4 u0 = ldg128(kp + lane * 2), u1 = ldg128(kp + 128 + lane * 2); const uint2 u2 = ldg64(kp + 256);
                const uint4 v0 = ldg128(kp + 640 + lane * 2), v1 = ldg128(kp + 768 + lane * 2); const uint2 v2 = ldg64(kp + 896);
                sts32(kd, packu(u0.x, u0.y)); sts32(kd + 5248, packu(u0.z, u0.w)); sts32(kd + 10496, packu(u1.x, u1.y)); sts32(kd + 15744, packu(u1.z, u1.w));
                if (t < 2) sts32(kd + 20992, packu(u2.x, u2.y));
                if (gq < 3) {
                    sts32(kd + 1024, packu(v0.x, v0.y)); sts32(kd + 6272, packu(v0.z, v0.w)); sts32(kd + 11520, packu(v1.x, v1.y)); sts32(kd + 16768, packu(v1.z, v1.w));
                    if (t < 2) sts32(kd + 22016, packu(v2.x, v2.y));
                }
            } else {
                const uint4 u0 = ldg128(kp + 320 + lane * 2), u1 = ldg128(kp + 448 + lane * 2); const uint2 u2 = ldg64(kp + 576);
                sts32(kd + 512, packu(u0.x, u0.y)); sts32(kd + 5760, packu(u0.z, u0.w)); sts32(kd + 11008, packu(u1.x, u1.y)); sts32(kd + 16256, packu(u1.z, u1.w));
                if (t < 2) sts32(kd + 21504, packu(u2.x, u2.y));
            }
            fence_async_smem();
            bar_arrive(9, 512);
        } else {
            float avq[36], acc[36]; uint2 cs[9];
            if (m == 1) {
                pdl_wait();
                if (tid < 384 + 108) {
                    uint2 pc[18];
                    #pragma unroll
                    for (int j = 0; j < 18; j++) pc[j] = ldg64(g_cs + (g * 18 + j) * 216 + (tid - 384) * 2);
                    float a = 0.f, c = 0.f;
                    #pragma unroll
                    for (int j = 0; j < 18; j++) { a += __uint_as_float(pc[j].x); c += __uint_as_float(pc[j].y); }
                    asm volatile("st.shared.v2.f32 [%0], {%1, %2};" :: "r"(sm + KA_CS + (tid - 384) * 8), "f"(a), "f"(c) : "memory");
                }
                bar_arrive(6, 384);
            }
            bar_sync(5, 512);
            #pragma unroll
            for (int i = 9; i < 22; i++) {
                const int c = i < 17 ? (i + 1) / 2 : i - 17;
                mbar_wait(bFull + (i % 9) * 8, (i / 9) & 1);
                wg_fence();
                #pragma unroll
                for (int kk = 0; kk < 4; kk++)
                    wgmma_n72<0, 0>((i < 17 && !(i & 1)) ? acc : avq, dadv(da, c * 16384 + kk * 32), dadv(db, (i % 9) * 9216 + kk * 32), i > 10 || kk != 0);
                wg_commit();
                if (i > 9 && i <= 18) { wg_wait<1>(); if (lane == 0) mbar_arrive(bEmpty + ((i - 1) % 9) * 8); }
                if (i == 17) bar_arrive(3 + m, 256);
                if (i == 18) bar_sync(14 + m, 128);
            }
            #pragma unroll
            for (int j = 0; j < 9; j++) cs[j] = lds64(csa + 288 + 32 * j);
            ln_get();
            wg_wait<0>();
            reg_fence<36>(avq);
            #pragma unroll
            for (int r = 0; r < 2; r++) {
                uint32_t pv[9];
                const float2 ln = r ? ln1 : ln0;
                #pragma unroll
                for (int j = 0; j < 9; j++)
                    pv[j] = pack2(fmaf(-ln.x, __uint_as_float(cs[j].x), avq[4 * j + 2 * r]) * ln.y, fmaf(-ln.x, __uint_as_float(cs[j].y), avq[4 * j + 2 * r + 1]) * ln.y);
                sts128(rec + r * 1024 + ((5 ^ rot) << 4), pv[0], pv[1], pv[2], pv[3]);
                sts128(rec + r * 1024 + ((6 ^ rot) << 4), pv[4], pv[5], pv[6], pv[7]);
                sts128(rec + r * 1024 + ((7 ^ rot) << 4), pv[8], 0x00003f80u, 0u, 0u);
            }
            fence_async_smem();
            bar_sync(8, 512);
            ka_kv(sm + KA_REC + wg * 16384, g_kv + (g * 4 + wg) * KV_H, w4, lane);
            const uint32_t sm2 = __shfl_sync(~0u, sm, 1);
            const uint64_t da2 = mkdesc(sm2 + m * 8192, 16, 1024, 1), db2 = mkdesc(sm2 + KA_B, 16, 1024, 1);
            #pragma unroll
            for (int i = 22; i < 27; i++) mbar_wait(bFull + (i % 9) * 8, 0);
            #pragma unroll
            for (int j = 0; j < 9; j++) cs[j] = lds64(csa + 576 + 32 * j);
            bar_sync(7, 512);
            wg_fence();
            #pragma unroll
            for (int i = 22; i < 27; i++)
                #pragma unroll
                for (int kk = 0; kk < 4; kk++) wgmma_n72<0, 0>(acc, dadv(da2, (i - 22) * 16384 + kk * 32), dadv(db2, (i % 9) * 9216 + kk * 32), 1);
            wg_commit();
            wg_wait<0>();
            reg_fence<36>(acc);
            uint32_t ph[2][18];
            #pragma unroll
            for (int r = 0; r < 2; r++) {
                float a[18];
                const float2 ln = r ? ln1 : ln0;
                #pragma unroll
                for (int j = 0; j < 9; j++) { a[2 * j] = fmaf(-ln.x, __uint_as_float(cs[j].x), acc[4 * j + 2 * r]); a[2 * j + 1] = fmaf(-ln.x, __uint_as_float(cs[j].y), acc[4 * j + 2 * r + 1]); }
                dual_softmax(a, ln.y * LOG2E, ph[r]);
            }
            #pragma unroll
            for (int j = 0; j < 18; j++) asm volatile("" : "+r"(ph[0][j]), "+r"(ph[1][j]));
            uint32_t* og = reinterpret_cast<uint32_t*>(g_o + (mt * 2 + m) * (64 * D_) + g * 4608) + w4 * 64 + lane;
            asm volatile("" : "+l"(og));
            const uint64_t dk = mkdesc(sm2 + KA_REC, 1312, 128, 0);
            float oc[40];
            bar_sync(9, 512);
            wg_fence();
            #pragma unroll
            for (int j = 0; j < 9; j++) wgmma_rs_n80(oc, ph[0][2 * j], ph[1][2 * j], ph[0][2 * j + 1], ph[1][2 * j + 1], dadv(dk, j * 2624), j != 0);
            wg_commit();
            wg_wait<0>();
            reg_fence<40>(oc);
            const float r0 = rcp_full(oc[36] + 1e-6f), r1 = rcp_full(oc[38] + 1e-6f);
            #pragma unroll
            for (int j = 0; j < 9; j++) { og[j * 256] = pack2(oc[4 * j] * r0, oc[4 * j + 1] * r0); og[j * 256 + 32] = pack2(oc[4 * j + 2] * r1, oc[4 * j + 3] * r1); }
        }
    }
}

constexpr int K2PRE = 2, K2_B = 73728, K2_PIECE = 27648, K2_X = K2_B + 5 * K2_PIECE, K2_BAR = K2_X + 18432, K2_SMEM = K2_BAR + 128;
__global__ void __cluster_dims__(2, 1, 1) __launch_bounds__(288, 1) k2_attn(const __grid_constant__ CUtensorMap tmX, const bf16* __restrict__ b2) {
    extern __shared__ __align__(1024) char smem[];
    const uint32_t sm = smem_u32(smem);
    const uint32_t bFull = sm + K2_BAR, bX = bFull + 6 * 8;
    const int tid = threadIdx.x, lane = tid & 31, warp = __shfl_sync(~0u, tid >> 5, 0);
    const int ns = blockIdx.x & 3, mt = blockIdx.x >> 2;
    const int wg = warp >> 2, w4 = warp & 3, gq = lane >> 2, t = lane & 3;
    const bf16* wsrc = g_wo + ns * (2 * 72 * 576);
    unsigned short bb0, bb1;
    asm volatile("ld.global.nc.u16 %0, [%1];" : "=h"(bb0) : "l"(b2 + mt * 64 + w4 * 16 + gq));
    asm volatile("ld.global.nc.u16 %0, [%1];" : "=h"(bb1) : "l"(b2 + mt * 64 + w4 * 16 + gq + 8));
    auto load_w = [&](int i) {
        bulk_g2s(sm + K2_B + (i % 5) * K2_PIECE, wsrc + i * (K2_PIECE / 4), K2_PIECE / 2, bFull + i * 8);
        bulk_g2s(sm + K2_B + (i % 5) * K2_PIECE + K2_PIECE / 2, wsrc + 72 * 576 + i * (K2_PIECE / 4), K2_PIECE / 2, bFull + i * 8);
    };
    if (tid == 256) {
        #pragma unroll
        for (int i = 0; i < 7; i++) mbar_init(bFull + i * 8, 1);
        fence_mbar_init();
        #pragma unroll
        for (int i = 0; i < K2PRE; i++) load_w(i);
    }
    __syncthreads();
    if (warp == 8) {
        if (lane == 0) {
            pdl_wait();
            const bf16* osrc = g_o + mt * (64 * D_);
            #pragma unroll
            for (int i = 0; i < 6; i++) {
                bulk_g2s(sm + i * 12288, osrc + i * 6144, 12288, bFull + i * 8);
                if (i + 1 >= K2PRE && i < 4) load_w(i + 1);
            }
            pdl_trigger();
        }
        __syncwarp();
        bar_sync(3, 288);
        if (lane == 0) {
            load_w(5);
            tma2d(sm + K2_X, &tmX, bX, ns * 144, mt * 64);
            tma2d(sm + K2_X + 9216, &tmX, bX, ns * 144 + 72, mt * 64);
        }
    } else {
        if (tid == 0) {
            #pragma unroll
            for (int i = 0; i < 6; i++) mbar_expect(bFull + i * 8, K2_PIECE + 12288);
            mbar_expect(bX, 18432);
            prefetch_tm(&tmX);
        }
        __syncwarp();
        float acc[36];
        const uint32_t xs = sm + K2_X + wg * 9216;
        uint32_t xr[20];
        const int p = ns * 2 + wg;
        unsigned long long* sb = g_stats + (mt * 4 + w4) * 128 + gq * 2;
        unsigned long long* sw = sb + p * 16;
        const unsigned long long* sr = sb + t * 32;
        uint32_t* ndst = reinterpret_cast<uint32_t*>(g_hnT + (mt * D_ + p * 72) * 64) + w4 * 64 + lane;
        asm volatile("" : "+l"(sw), "+l"(sr), "+l"(ndst));
        const uint64_t da0 = mkdesc(sm, 1024, 128, 0), db0 = mkdesc(sm + K2_B + wg * (K2_PIECE / 2), 1152, 128, 0);
        #pragma unroll
        for (int i = 0; i < 6; i++) {
            mbar_wait(bFull + i * 8, 0);
            wg_fence();
            #pragma unroll
            for (int kk = 0; kk < 6; kk++)
                wgmma_n72<0, 0>(acc, dadv(da0, i * 12288 + kk * 2048), dadv(db0, (i % 5) * K2_PIECE + kk * 2304), (i | kk) != 0);
            wg_commit();
            if (i == 1) { wg_wait<1>(); bar_arrive(3, 288); }
            if (i == 5) {
                mbar_wait(bX, 0);
                #pragma unroll
                for (int j = 0; j < 5; j++)
                    asm volatile("ldmatrix.sync.aligned.m8n8.x4.shared.b16 {%0,%1,%2,%3}, [%4];" : "=r"(xr[4 * j]), "=r"(xr[4 * j + 1]), "=r"(xr[4 * j + 2]), "=r"(xr[4 * j + 3])
                                 : "r"(xs + (w4 * 16 + (lane & 15)) * 144 + (j < 4 ? (lane >> 4) * 16 : 0) + j * 32) : "memory");
            }
        }
        wg_wait<0>();
        reg_fence<36>(acc);
        #pragma unroll
        for (int j = 0; j < 18; j++) { acc[2 * j] += bf_lo(xr[j]); acc[2 * j + 1] += bf_hi(xr[j]); }
        float m0 = 0.f, m1 = 0.f;
        #pragma unroll
        for (int j = 0; j < 9; j++) { m0 += acc[4 * j] + acc[4 * j + 1]; m1 += acc[4 * j + 2] + acc[4 * j + 3]; }
        m0 *= (1.f / 18); m1 *= (1.f / 18);
        float q0 = 0.f, q1 = 0.f, q2 = 0.f, q3 = 0.f;
        #pragma unroll
        for (int j = 0; j < 9; j++) {
            float e;
            e = acc[4 * j] - m0; q0 = fmaf(e, e, q0); e = acc[4 * j + 1] - m0; q2 = fmaf(e, e, q2);
            e = acc[4 * j + 2] - m1; q1 = fmaf(e, e, q1); e = acc[4 * j + 3] - m1; q3 = fmaf(e, e, q3);
        }
        q0 += q2; q1 += q3;
        #pragma unroll
        for (int o = 1; o < 4; o <<= 1) {
            const float a0 = __shfl_xor_sync(~0u, m0, o), a1 = __shfl_xor_sync(~0u, m1, o), b0 = __shfl_xor_sync(~0u, q0, o), b1 = __shfl_xor_sync(~0u, q1, o);
            q0 += b0 + (a0 - m0) * (a0 - m0) * (9.f * o); q1 += b1 + (a1 - m1) * (a1 - m1) * (9.f * o);
            m0 = 0.5f * (m0 + a0); m1 = 0.5f * (m1 + a1);
        }
        if (t == 0) {
            const unsigned long long r0 = ((unsigned long long)(__float_as_uint(q0) | 0x80000000u) << 32) | __float_as_uint(m0);
            const unsigned long long r1 = ((unsigned long long)(__float_as_uint(q1) | 0x80000000u) << 32) | __float_as_uint(m1);
            asm volatile("st.relaxed.gpu.global.v2.u64 [%0], {%1, %2};" :: "l"(sw), "l"(r0), "l"(r1) : "memory");
        }
        unsigned long long ra, rb, rc, rd;
        {
            int it = 0;
            while (true) {
                asm volatile("ld.relaxed.gpu.global.v2.u64 {%0, %1}, [%2];" : "=l"(ra), "=l"(rc) : "l"(sr) : "memory");
                asm volatile("ld.relaxed.gpu.global.v2.u64 {%0, %1}, [%2];" : "=l"(rb), "=l"(rd) : "l"(sr + 16) : "memory");
                const bool ok = (long long)(ra & rb & rc & rd) < 0;
                if (__all_sync(~0u, ok)) break;
                if (++it > (1 << 22)) __trap();
            }
        }
        float sc[2], mu[2];
        #pragma unroll
        for (int r = 0; r < 2; r++) {
            const unsigned long long u = r ? rc : ra, v = r ? rd : rb;
            const float ma = __uint_as_float((uint32_t)u), mb = __uint_as_float((uint32_t)v);
            float ms = ma + mb;
            ms += __shfl_xor_sync(~0u, ms, 1); ms += __shfl_xor_sync(~0u, ms, 2);
            const float mean = ms * 0.125f;
            float M2 = fabsf(__uint_as_float((uint32_t)(u >> 32))) + fabsf(__uint_as_float((uint32_t)(v >> 32))) + 72.f * ((ma - mean) * (ma - mean) + (mb - mean) * (mb - mean));
            M2 += __shfl_xor_sync(~0u, M2, 1); M2 += __shfl_xor_sync(~0u, M2, 2);
            const float var = M2 * (1.f / D_);
            const float r1 = rsqrtf(var + LN_EPS);
            const float var2 = var * r1 * r1;
            const float r2 = rsqrtf(var2 + LN_EPS);
            sc[r] = 0.5f * (r1 * r2); mu[r] = mean;
        }
        const float of0 = -mu[0] * sc[0], of1 = -mu[1] * sc[1];
        #pragma unroll
        for (int j = 0; j < 9; j++) {
            ndst[j * 256] = pack2(fmaf(acc[4 * j], sc[0], of0), fmaf(acc[4 * j + 1], sc[0], of0));
            ndst[j * 256 + 32] = pack2(fmaf(acc[4 * j + 2], sc[1], of1), fmaf(acc[4 * j + 3], sc[1], of1));
        }
        if (p == 1 && t < 2) g_ln[mt * 64 + w4 * 16 + gq + 8 * t] = 0ull;
        if (p == 0 && t < 2) {
            asm volatile("" : "+h"(bb0), "+h"(bb1));
            g_rc[mt * 64 + w4 * 16 + gq + 8 * t] = make_float2(1.f / (t ? sc[1] : sc[0]), (t ? mu[1] : mu[0]) + __uint_as_float((uint32_t)(t ? bb1 : bb0) << 16));
        }
    }
}

constexpr int PFT = 4, W2HEAD = 9;
constexpr int K3_STAGES = 6, K3_STAGE = 36864, K3_STAG = 6, K3_PRE = 2, K3_BAR = K3_STAGES * K3_STAGE, K3_SMEM = K3_BAR + 256;
DEVI uint32_t gelu2(float a0, float a1) {
    const float z0 = a0 * fmaf(a0 * a0, 0.2854192650904f, 1.5957691216057f), z1 = a1 * fmaf(a1 * a1, 0.2854192650904f, 1.5957691216057f);
    return pack2(fmaf(a0, tanh_fast(z0), a0), fmaf(a1, tanh_fast(z1), a1));
}
template<int NB> DEVI void k3_store(const float* q, uint32_t* dst) {
    #pragma unroll
    for (int j = 0; j < NB; j++) { dst[j * 256] = gelu2(q[4 * j], q[4 * j + 1]); dst[j * 256 + 32] = gelu2(q[4 * j + 2], q[4 * j + 3]); }
}
DEVI void k3_typeb(uint32_t sm_, int fc_, float bias0, float bias1, const bf16* __restrict__ b1) {
    const uint32_t sm = __shfl_sync(~0u, sm_, 0);
    const int fc = __shfl_sync(~0u, fc_, 0);
    const uint32_t bFull = sm + K3_BAR, bEmpty = bFull + K3_STAGES * 8;
    const int tid = threadIdx.x, lane = tid & 31, warp = __shfl_sync(~0u, tid >> 5, 0);
    const int wg = warp >> 2, w4 = warp & 3, gq = lane >> 2;
    const uint32_t st = sm + wg * 8192;
    const uint64_t da0 = mkdesc(st, 8192, 1024, 1);
    int s = 0, ps = 0; uint32_t ph = 0;
    {
            const int f2 = (fc + 2) * 64 + w4 * 16 + gq;
            const float bias2 = 0.5f * __bfloat162float(b1[f2]), bias3 = 0.5f * __bfloat162float(b1[f2 + 8]);
            float acc[48], acc2[24];
            const uint64_t da2 = mkdesc(sm + 16384, 8192, 1024, 1), db0 = mkdesc(sm + 24576, 128, 1024, 0), db2 = mkdesc(sm + 24576 + wg * 6144, 128, 1024, 0);
            #pragma unroll 1
            for (int i = 0; i < 32 - K3_STAG; i++) {
                mbar_wait(bFull + s * 8, ph);
                const uint32_t so = s * K3_STAGE;
                wg_fence();
                #pragma unroll
                for (int kk = 0; kk < 4; kk++) {
                    wgmma_n96<1, 1>(acc, dadv(da0, so + kk * 2048), dadv(db0, so + kk * 256), (i | kk) != 0);
                    wgmma_n48<1, 1>(acc2, dadv(da2, so + kk * 2048), dadv(db2, so + kk * 256), (i | kk) != 0);
                }
                wg_commit();
                wg_wait<1>();
                if (i > 0 && lane == 0) mbar_arrive(bEmpty + ps * 8);
                ps = s;
                if (++s == K3_STAGES) { s = 0; ph ^= 1; }
            }
            if (wg == 1) {
                wg_wait<0>();
                if (lane == 0) mbar_arrive(bEmpty + ps * 8);
                #pragma unroll
                for (int i = 32 - K3_STAG; i < 32; i++) mbar_wait(bFull + (i % K3_STAGES) * 8, (i / K3_STAGES) & 1);
                bar_sync(3, 256);
            }
            #pragma unroll
            for (int i = 32 - K3_STAG; i < 32; i++) {
                if (wg == 0) mbar_wait(bFull + (i % K3_STAGES) * 8, (i / K3_STAGES) & 1);
                const uint32_t so = (i % K3_STAGES) * K3_STAGE;
                wg_fence();
                #pragma unroll
                for (int kk = 0; kk < 4; kk++) {
                    wgmma_n96<1, 1>(acc, dadv(da0, so + kk * 2048), dadv(db0, so + kk * 256), 1);
                    wgmma_n48<1, 1>(acc2, dadv(da2, so + kk * 2048), dadv(db2, so + kk * 256), 1);
                }
                wg_commit();
                if (i == 32 - K3_STAG && wg == 0) { wg_wait<1>(); if (lane == 0) mbar_arrive(bEmpty + ps * 8); }
            }
            if (wg == 0) bar_arrive(3, 256);
            wg_wait<0>();
            reg_fence<48>(acc); reg_fence<24>(acc2);
            #pragma unroll
            for (int j = 0; j < 48; j++) acc[j] += (j & 2) ? bias1 : bias0;
            #pragma unroll
            for (int j = 0; j < 24; j++) acc2[j] += (j & 2) ? bias3 : bias2;
            k3_store<12>(acc, reinterpret_cast<uint32_t*>(g_u + ((fc + wg) * D_ + 480) * 64) + w4 * 64 + lane);
            k3_store<6>(acc2, reinterpret_cast<uint32_t*>(g_u + ((fc + 2) * D_ + 480 + wg * 48) * 64) + w4 * 64 + lane);
    }
}
__global__ void __cluster_dims__(2, 1, 1) __launch_bounds__(288, 1) k3_mix1(const __grid_constant__ CUtensorMap tmW1a, const __grid_constant__ CUtensorMap tmW1b,
                                                                             const bf16* __restrict__ b1, const bf16* __restrict__ w1, const bf16* __restrict__ w2) {
    extern __shared__ __align__(1024) char smem[];
    const uint32_t sm = smem_u32(smem);
    const uint32_t bFull = sm + K3_BAR, bEmpty = bFull + K3_STAGES * 8;
    const int tid = threadIdx.x, lane = tid & 31, warp = __shfl_sync(~0u, tid >> 5, 0);
    const int cl = blockIdx.x >> 1, rank = blockIdx.x & 1;
    bool tb = false; int fc, d0;
    if (cl < 36) { fc = 2 * cl; d0 = 160 * rank; }
    else if (cl < 60) { const int q = (cl - 36) >> 1, e = (cl - 36) & 1; tb = rank; fc = rank ? 6 * q + 3 * e : 6 * q + 4 * e; d0 = rank ? 480 : 320; }
    else { fc = 6 * (2 * (cl - 60) + rank) + 2; d0 = 320; }
    const CUtensorMap* tm = tb ? &tmW1b : &tmW1a;
    const uint32_t abytes = tb ? 24576 : 16384;
    if (tid == 256) {
        #pragma unroll
        for (int i = 0; i < K3_STAGES; i++) { mbar_init(bFull + i * 8, 1); mbar_init(bEmpty + i * 8, 8); }
        fence_mbar_init();
        #pragma unroll
        for (int i = 0; i < K3_STAGES; i++) mbar_expect(bFull + i * 8, K3_STAGE);
        #pragma unroll
        for (int i = 0; i < K3_PRE; i++) tma3d(sm + i * K3_STAGE, tm, bFull + i * 8, 0, i * 64, fc);
    }
    __syncthreads();
    if (warp == 8) {
        if (tid == 256) {
            if (blockIdx.x == 0) { g_claim = 0ull; __threadfence(); }
            pdl_wait();
            pdl_trigger();
            const bf16* hs = g_hnT + d0 * 64;
            #pragma unroll
            for (int i = 0; i < K3_STAGES; i++) {
                bulk_g2s(sm + i * K3_STAGE + abytes, hs + i * (D_ * 64), K3_STAGE - abytes, bFull + i * 8);
                if (i >= K3_PRE) tma3d(sm + i * K3_STAGE, tm, bFull + i * 8, 0, i * 64, fc);
            }
            int s = 0; uint32_t ph = 0;
            #pragma unroll 1
            for (int i = K3_STAGES; i < 32; i++) {
                mbar_wait(bEmpty + s * 8, ph);
                mbar_expect(bFull + s * 8, K3_STAGE);
                tma3d(sm + s * K3_STAGE, tm, bFull + s * 8, 0, i * 64, fc);
                bulk_g2s(sm + s * K3_STAGE + abytes, hs + i * (D_ * 64), K3_STAGE - abytes, bFull + s * 8);
                if (i == 18 && blockIdx.x < 128) l2_prefetch(w1 + (size_t)(2048 - 64 * PFT) * F_ + blockIdx.x * (2304 * PFT), 4608 * PFT);
                if (++s == K3_STAGES) { s = 0; ph ^= 1; }
            }
            if (blockIdx.x < 128) l2_prefetch(w2 + (size_t)(blockIdx.x & 1) * (2304 * S_) + (blockIdx.x >> 1) * (W2HEAD * 2048), W2HEAD * 4096);
        }
    } else {
        const int wg = warp >> 2, w4 = warp & 3, gq = lane >> 2;
        const int f0 = (fc + wg) * 64 + w4 * 16 + gq;
        const float bias0 = 0.5f * __bfloat162float(b1[f0]), bias1 = 0.5f * __bfloat162float(b1[f0 + 8]);
        uint32_t* dst = reinterpret_cast<uint32_t*>(g_u + ((fc + wg) * D_ + d0) * 64) + w4 * 64 + lane;
        const uint32_t st = sm + wg * 8192;
        const uint64_t da0 = mkdesc(st, 8192, 1024, 1);
        int s = 0, ps = 0; uint32_t ph = 0;
        if (!tb) {
            float acc[80];
            #pragma unroll
            for (int j = 0; j < 80; j++) acc[j] = (j & 2) ? bias1 : bias0;
            reg_fence<80>(acc);
            const uint64_t db0 = mkdesc(sm + 16384, 128, 1024, 0);
            #pragma unroll 1
            for (int i = 0; i < 32 - K3_STAG; i++) {
                mbar_wait(bFull + s * 8, ph);
                const uint64_t da = dadv(da0, s * K3_STAGE), db = dadv(db0, s * K3_STAGE);
                wg_fence();
                #pragma unroll
                for (int kk = 0; kk < 4; kk++)
                    wgmma_n160<1, 1>(acc, dadv(da, kk * 2048), dadv(db, kk * 256), 1);
                wg_commit();
                wg_wait<1>();
                if (i > 0 && lane == 0) mbar_arrive(bEmpty + ps * 8);
                ps = s;
                if (++s == K3_STAGES) { s = 0; ph ^= 1; }
            }
            if (wg == 1) {
                wg_wait<0>();
                if (lane == 0) mbar_arrive(bEmpty + ps * 8);
                #pragma unroll
                for (int i = 32 - K3_STAG; i < 32; i++) mbar_wait(bFull + (i % K3_STAGES) * 8, (i / K3_STAGES) & 1);
                bar_sync(3, 256);
            }
            #pragma unroll
            for (int i = 32 - K3_STAG; i < 32; i++) {
                if (wg == 0) mbar_wait(bFull + (i % K3_STAGES) * 8, (i / K3_STAGES) & 1);
                wg_fence();
                #pragma unroll
                for (int kk = 0; kk < 4; kk++)
                    wgmma_n160<1, 1>(acc, dadv(da0, (i % K3_STAGES) * K3_STAGE + kk * 2048), dadv(db0, (i % K3_STAGES) * K3_STAGE + kk * 256), 1);
                wg_commit();
                if (i == 32 - K3_STAG && wg == 0) { wg_wait<1>(); if (lane == 0) mbar_arrive(bEmpty + ps * 8); }
            }
            if (wg == 0) bar_arrive(3, 256);
            wg_wait<0>();
            reg_fence<80>(acc);
            k3_store<20>(acc, dst);
        } else {
            k3_typeb(sm, fc, bias0, bias1, b1);
        }
    }
}

constexpr int SLOTC = 1400, SLOTP = 578, K4_PD = 4;
constexpr int K4_STAGES = 5, K4_STAGE = 8192 + 36864, K4_STAG = 3, K4_BAR = K4_STAGES * K4_STAGE, K4_SMEM = K4_BAR + 256;
constexpr int K4_XS = (36 - K4_STAG - 1) % K4_STAGES;
DEVI int k4_claim() {
    unsigned smid; asm volatile("mov.u32 %0, %%smid;" : "=r"(smid));
    const int tpc = smid >> 1;
    const int grp = tpc < 32 ? tpc & 7 : tpc < 60 ? 1 + (tpc - 32) % 7 : tpc < 62 ? tpc - 54 : 8;
    unsigned long long w = atomicAdd(&g_claim, 1ull << (7 * grp));
    const int slot = (int)(w >> (7 * grp)) & 127;
    if (slot < ((grp & 7) ? 8 : 4)) return (grp ? 8 * grp - 4 : 0) + slot;
    int it = 0, tot;
    do {
        asm volatile("ld.relaxed.gpu.global.u64 %0, [%1];" : "=l"(w) : "l"(&g_claim) : "memory");
        tot = 0;
        for (int j = 0; j < 9; j++) tot += (int)(w >> (7 * j)) & 127;
        if (++it > (1 << 22)) __trap();
    } while (tot < (int)(gridDim.x >> 1));
    int rank = slot - ((grp & 7) ? 8 : 4);
    for (int j = 0; j < grp; j++) rank += max(((int)(w >> (7 * j)) & 127) - ((j & 7) ? 8 : 4), 0);
    for (int j = 0; j < 9; j++) {
        const int have = (int)(w >> (7 * j)) & 127, miss = max(((j & 7) ? 8 : 4) - have, 0);
        if (rank < miss) return (j ? 8 * j - 4 : 0) + have + rank;
        rank -= miss;
    }
    return 64;
}
__global__ void __cluster_dims__(2, 1, 1) __launch_bounds__(288, 1) k4_mix2(const __grid_constant__ CUtensorMap tmW2, const __grid_constant__ CUtensorMap tmOut) {
    extern __shared__ __align__(1024) char smem[];
    const uint32_t sm = smem_u32(smem);
    const uint32_t bFull = sm + K4_BAR, bEmpty = bFull + K4_STAGES * 8, bP = bEmpty + K4_STAGES * 8, bRdy = bP + 16, bH = bRdy + 8;
    const int tid = threadIdx.x, lane = tid & 31, warp = __shfl_sync(~0u, tid >> 5, 0);
    const int ks = blockIdx.x & 1;
    const int k0 = ks * 36;
    const uint32_t bT = bH + 8, sT = bT + 8;
    int tile = 0;
    if (tid == 256) {
        #pragma unroll
        for (int i = 0; i < K4_STAGES; i++) { mbar_init(bFull + i * 8, 1); mbar_init(bEmpty + i * 8, 8); }
        mbar_init(bP, 1); mbar_init(bP + 8, 1); mbar_init(bRdy, 8); mbar_init(bH, 1); mbar_init(bT, 1);
        fence_mbar_init();
        mbar_expect(bT, 4);
    }
    if (tid == 64) prefetch_tm(&tmW2);
    __syncwarp();
    cluster_arrive_relaxed();
    uint32_t slot = 0;
    if (warp == 8) {
        if (lane == 0) { pdl_wait(); slot = clock() + SLOTC; }
        __syncwarp();
        cluster_wait();
    } else {
        if (tid == 0 && ks == 0) tile = k4_claim();
        __syncwarp();
        cluster_wait();
        if (tid == 0 && ks == 0) {
            #pragma unroll
            for (int r = 1; r >= 0; r--)
                asm volatile("st.async.shared::cluster.mbarrier::complete_tx::bytes.u32 [%0], %1, [%2];" :: "r"(mapa(sT, r)), "r"(tile), "r"(mapa(bT, r)) : "memory");
        }
        if (tid == 32) {
            #pragma unroll
            for (int i = 0; i < K4_STAGES; i++) mbar_expect(bFull + i * 8, K4_STAGE);
        }
        if (tid == 128) { mbar_expect(bP, 9216); mbar_expect(bP + 8, 9216); prefetch_tm(&tmOut); }
        __syncwarp();
    }
    mbar_wait(bT, 0);
    asm volatile("ld.shared.b32 %0, [%1];" : "=r"(tile) : "r"(sT) : "memory");
    tile = __shfl_sync(~0u, tile, 0);
    if (tile >= 64) return;
    const int tm = tile >> 1, tn = tile & 1;
    if (tid == 64) {
        #pragma unroll
        for (int i = 0; i < 2; i++) tma3d(sm + i * K4_STAGE, &tmW2, bFull + i * 8, 0, (k0 + i) * 64, tm);
    }
    __syncwarp();
    if (warp == 8) {
        if (lane == 0) {
            const bf16* us = g_u + ((size_t)k0 * D_ + tn * 288) * 64;
            #pragma unroll
            for (int i = 0; i < K4_STAGES; i++) {
                if (i >= 2) { tma3d(sm + i * K4_STAGE, &tmW2, bFull + i * 8, 0, (k0 + i) * 64, tm); while ((int)(clock() - slot) < 0) {} slot += SLOTP; }
                bulk_g2s(sm + i * K4_STAGE + 8192, us + (size_t)i * (D_ * 64), 36864, bFull + i * 8);
            }
            int s = 0; uint32_t ph = 0;
            #pragma unroll 1
            for (int i = K4_STAGES; i < 36; i++) {
                mbar_wait(bEmpty + s * 8, ph);
                mbar_expect(bFull + s * 8, K4_STAGE);
                tma3d(sm + s * K4_STAGE, &tmW2, bFull + s * 8, 0, (k0 + i) * 64, tm);
                if (i + K4_PD < 36 && ((i ^ tn) & 1)) tma3d_prefetch(&tmW2, 0, (k0 + i + K4_PD) * 64, tm);
                if (i < 32) { while ((int)(clock() - slot) < 0) {} slot += SLOTP; }
                bulk_g2s(sm + s * K4_STAGE + 8192, us + (size_t)i * (D_ * 64), 36864, bFull + s * 8);
                if (++s == K4_STAGES) { s = 0; ph ^= 1; }
            }
            static_assert(K4_STAG <= 3, "stage of step 31 is free");
            mbar_wait(bEmpty + s * 8, ph);
            mbar_expect(bH, 18432);
            bulk_g2s(sm + (31 % K4_STAGES) * K4_STAGE, g_hnT + (tm * D_ + tn * 288 + ks * 144) * 64, 18432, bH);
        }
        __syncwarp();
        #pragma unroll
        for (int hh = 0; hh < 2; hh++) {
            bar_sync(4 + hh, 160);
            if (lane == 0) {
                tma2d_store(&tmOut, sm + K4_XS * K4_STAGE + 24576 + hh * 9216, tn * 288 + ks * 144 + hh * 72, tm * 64);
                bulk_commit();
            }
            __syncwarp();
        }
        if (lane == 0) { bulk_wait_read(); }
    } else {
        const int wg = warp >> 2, w4 = warp & 3, tw = tid & 127;
        const bool keep = wg == ks;
        float acc[72];
        const uint64_t da0 = mkdesc(sm, 8192, 1024, 1), db0 = mkdesc(sm + 8192 + wg * 18432, 128, 1024, 0);
        const uint32_t rdy = mapa(bRdy, ks ^ 1);
        int s = 0, ps = 0; uint32_t ph = 0;
        #pragma unroll 1
        for (int i = 0; i < 36 - K4_STAG; i++) {
            mbar_wait(bFull + s * 8, ph);
            const uint64_t da = dadv(da0, s * K4_STAGE), db = dadv(db0, s * K4_STAGE);
            wg_fence();
            #pragma unroll
            for (int kk = 0; kk < 4; kk++)
                wgmma_n144<1, 1>(acc, dadv(da, kk * 2048), dadv(db, kk * 256), (i | kk) != 0);
            wg_commit();
            wg_wait<1>();
            if (i > 0 && lane == 0) mbar_arrive(bEmpty + ps * 8);
            ps = s;
            if (++s == K4_STAGES) { s = 0; ph ^= 1; }
        }
        const uint32_t xa = sm + K4_XS * K4_STAGE + tw * 16;
        const uint2 rc0 = ldg64(g_rc + tm * 64 + w4 * 16 + (lane >> 2)), rc1 = ldg64(g_rc + tm * 64 + w4 * 16 + (lane >> 2) + 8);
        float res[36];
        const uint32_t ya = sm + (31 % K4_STAGES) * K4_STAGE + 20480 + tw * 16;
        auto residual = [&](int hh) {
            uint32_t hp[20];
            mbar_wait(bH, 0);
            const uint32_t ha = sm + (31 % K4_STAGES) * K4_STAGE + hh * 9216 + (lane >> 4) * 1024 + w4 * 256 + (lane & 15) * 16;
            #pragma unroll
            for (int j = 0; j < 5; j++)
                asm volatile("ldmatrix.sync.aligned.m8n8.x4.shared.b16 {%0,%1,%2,%3}, [%4];" : "=r"(hp[4 * j]), "=r"(hp[4 * j + 1]), "=r"(hp[4 * j + 2]), "=r"(hp[4 * j + 3]) : "r"(ha + j * 2048) : "memory");
            #pragma unroll
            for (int j = 0; j < 18; j++) {
                const float is = __uint_as_float((j & 1) ? rc1.x : rc0.x), of = __uint_as_float((j & 1) ? rc1.y : rc0.y);
                res[2 * j] = fmaf(bf_lo(hp[j]), is, of); res[2 * j + 1] = fmaf(bf_hi(hp[j]), is, of);
            }
            reg_fence<36>(res);
        };
        auto partial = [&](int hh) {
            mbar_wait(bP + hh * 8, 0);
            uint32_t o[18];
            #pragma unroll
            for (int j = 0; j < 4; j++) { const uint4 v = lds128(xa + hh * 10240 + j * 2048); o[4 * j] = v.x; o[4 * j + 1] = v.y; o[4 * j + 2] = v.z; o[4 * j + 3] = v.w; }
            { const uint2 v = lds64(xa + hh * 10240 + 8192); o[16] = v.x; o[17] = v.y; }
            #pragma unroll
            for (int j = 0; j < 18; j++) { res[2 * j] += bf_lo(o[j]); res[2 * j + 1] += bf_hi(o[j]); }
        };
        if (!keep) {
            #pragma unroll
            for (int i = 36 - K4_STAG; i < 36; i++) {
                mbar_wait(bFull + (i % K4_STAGES) * 8, (i / K4_STAGES) & 1);
                wg_fence();
                #pragma unroll
                for (int kk = 0; kk < 4; kk++)
                    wgmma_n144<1, 1>(acc, dadv(da0, (i % K4_STAGES) * K4_STAGE + kk * 2048), dadv(db0, (i % K4_STAGES) * K4_STAGE + kk * 256), 1);
                wg_commit();
                if (i == 36 - K4_STAG) { wg_wait<1>(); if (lane == 0) mbar_arrive_remote(rdy); }
            }
            bar_arrive(3, 256);
            mbar_wait(bRdy, 0);
            wg_wait<0>();
            reg_fence<72>(acc);
            const uint32_t rd = mapa(xa, ks ^ 1), rb = mapa(bP, ks ^ 1);
            #pragma unroll
            for (int hh = 0; hh < 2; hh++) {
                const float* q = acc + hh * 36;
                #pragma unroll
                for (int j = 0; j < 4; j++)
                    asm volatile("st.async.shared::cluster.mbarrier::complete_tx::bytes.v4.b32 [%0], {%1,%2,%3,%4}, [%5];"
                                 :: "r"(rd + hh * 10240 + j * 2048), "r"(pack2(q[8 * j], q[8 * j + 1])), "r"(pack2(q[8 * j + 2], q[8 * j + 3])),
                                    "r"(pack2(q[8 * j + 4], q[8 * j + 5])), "r"(pack2(q[8 * j + 6], q[8 * j + 7])), "r"(rb + hh * 8) : "memory");
                asm volatile("st.async.shared::cluster.mbarrier::complete_tx::bytes.v2.b32 [%0], {%1,%2}, [%3];"
                             :: "r"(rd + hh * 10240 + 8192), "r"(pack2(q[32], q[33])), "r"(pack2(q[34], q[35])), "r"(rb + hh * 8) : "memory");
            }
            residual(1);
            partial(1);
            reg_fence<36>(res);
            bar_sync(1, 256);
            #pragma unroll
            for (int j = 0; j < 9; j++) {
                const uint4 v = lds128(ya + j * 2048);
                res[4 * j] += __uint_as_float(v.x); res[4 * j + 1] += __uint_as_float(v.y); res[4 * j + 2] += __uint_as_float(v.z); res[4 * j + 3] += __uint_as_float(v.w);
            }
        } else {
            wg_wait<0>();
            if (lane == 0) mbar_arrive_remote(rdy);
            #pragma unroll
            for (int i = 36 - K4_STAG; i < 36; i++) mbar_wait(bFull + (i % K4_STAGES) * 8, (i / K4_STAGES) & 1);
            bar_sync(3, 256);
            wg_fence();
            #pragma unroll
            for (int i = 36 - K4_STAG; i < 36; i++)
                #pragma unroll
                for (int kk = 0; kk < 4; kk++)
                    wgmma_n144<1, 1>(acc, dadv(da0, (i % K4_STAGES) * K4_STAGE + kk * 2048), dadv(db0, (i % K4_STAGES) * K4_STAGE + kk * 256), 1);
            wg_commit();
            residual(0);
            wg_wait<0>();
            reg_fence<72>(acc);
            #pragma unroll
            for (int j = 0; j < 9; j++)
                sts128(ya + j * 2048, __float_as_uint(acc[36 + 4 * j]), __float_as_uint(acc[37 + 4 * j]), __float_as_uint(acc[38 + 4 * j]), __float_as_uint(acc[39 + 4 * j]));
            bar_arrive(1, 256);
            #pragma unroll
            for (int j = 0; j < 36; j++) res[j] += acc[j];
            partial(0);
        }
        const int hh = keep ? 0 : 1;
        uint32_t o[18];
        #pragma unroll
        for (int j = 0; j < 18; j++) o[j] = pack2(res[2 * j], res[2 * j + 1]);
        const uint32_t ad = sm + K4_XS * K4_STAGE + 24576 + hh * 9216 + (w4 * 16 + ((lane >> 3) & 1) * 8 + (lane & 7)) * 144;
        #pragma unroll
        for (int j = 0; j < 4; j++) stsm4(ad + (lane >> 4) * 16 + j * 32, o[4 * j], o[4 * j + 1], o[4 * j + 2], o[4 * j + 3]);
        stsm2(ad + 128, o[16], o[17]);
        fence_async_smem();
        bar_arrive(4 + hh, 160);
    }
}

typedef CUresult (*EncFn)(CUtensorMap*, CUtensorMapDataType, cuuint32_t, void*, const cuuint64_t*, const cuuint64_t*, const cuuint32_t*,
                          const cuuint32_t*, CUtensorMapInterleave, CUtensorMapSwizzle, CUtensorMapL2promotion, CUtensorMapFloatOOBfill);

template <typename... KArgs, typename... Args>
static void launch(void (*kern)(KArgs...), dim3 grid, int block, int smem, bool pdl, Args... args) {
    cudaLaunchConfig_t cfg = {};
    cfg.gridDim = grid; cfg.blockDim = dim3(block); cfg.dynamicSmemBytes = smem; cfg.stream = cudaStreamPerThread;
    cudaLaunchAttribute at[1];
    at[0].id = cudaLaunchAttributeProgrammaticStreamSerialization; at[0].val.programmaticStreamSerializationAllowed = 1;
    cfg.attrs = at; cfg.numAttrs = pdl ? 1 : 0;
    cudaLaunchKernelEx(&cfg, kern, args...);
}

extern "C" void kernel_launch(void* const* d_in, const int* in_sizes, int n_in, void* d_out, int out_size) {
    const bf16* x = (const bf16*)d_in[0];
    const bf16* wqkv = (const bf16*)d_in[1];
    const bf16* wphi = (const bf16*)d_in[2];
    const bf16* wo = (const bf16*)d_in[3];
    const bf16* w1 = (const bf16*)d_in[5];
    const bf16* b1 = (const bf16*)d_in[6];
    const bf16* w2 = (const bf16*)d_in[7];
    const bf16* b2 = (const bf16*)d_in[8];
    static EncFn enc = nullptr;
    if (!enc) {
        void* fn = nullptr; cudaDriverEntryPointQueryResult qr;
        cudaGetDriverEntryPoint("cuTensorMapEncodeTiled", &fn, cudaEnableDefault, &qr);
        enc = (EncFn)fn;
        cudaFuncSetAttribute(ka_front, cudaFuncAttributeMaxDynamicSharedMemorySize, KA_SMEM);
        cudaFuncSetAttribute(k2_attn, cudaFuncAttributeMaxDynamicSharedMemorySize, K2_SMEM);
        cudaFuncSetAttribute(k3_mix1, cudaFuncAttributeMaxDynamicSharedMemorySize, K3_SMEM);
        cudaFuncSetAttribute(k4_mix2, cudaFuncAttributeMaxDynamicSharedMemorySize, K4_SMEM);
    }
    CUtensorMap tmW1, tmW1b, tmW2, tmOut, tmX, tmXA;
    const cuuint32_t es[3] = {1, 1, 1};
    {
        cuuint64_t dims[3] = {64, (cuuint64_t)S_, (cuuint64_t)(F_ / 64)}; cuuint64_t st[2] = {(cuuint64_t)F_ * 2, 128}; cuuint32_t box[3] = {64, 64, 2};
        enc(&tmW1, CU_TENSOR_MAP_DATA_TYPE_BFLOAT16, 3, (void*)w1, dims, st, box, es, CU_TENSOR_MAP_INTERLEAVE_NONE, CU_TENSOR_MAP_SWIZZLE_128B, CU_TENSOR_MAP_L2_PROMOTION_L2_128B, CU_TENSOR_MAP_FLOAT_OOB_FILL_NONE);
        box[2] = 3;
        enc(&tmW1b, CU_TENSOR_MAP_DATA_TYPE_BFLOAT16, 3, (void*)w1, dims, st, box, es, CU_TENSOR_MAP_INTERLEAVE_NONE, CU_TENSOR_MAP_SWIZZLE_128B, CU_TENSOR_MAP_L2_PROMOTION_L2_128B, CU_TENSOR_MAP_FLOAT_OOB_FILL_NONE);
    }
    {
        cuuint64_t dims[3] = {64, (cuuint64_t)F_, (cuuint64_t)(S_ / 64)}; cuuint64_t st[2] = {(cuuint64_t)S_ * 2, 128}; cuuint32_t box[3] = {64, 64, 1};
        enc(&tmW2, CU_TENSOR_MAP_DATA_TYPE_BFLOAT16, 3, (void*)w2, dims, st, box, es, CU_TENSOR_MAP_INTERLEAVE_NONE, CU_TENSOR_MAP_SWIZZLE_128B, CU_TENSOR_MAP_L2_PROMOTION_L2_128B, CU_TENSOR_MAP_FLOAT_OOB_FILL_NONE);
    }
    {
        cuuint64_t dims[2] = {(cuuint64_t)D_, (cuuint64_t)S_}; cuuint64_t st[1] = {(cuuint64_t)D_ * 2}; cuuint32_t box[2] = {72, 64};
        enc(&tmOut, CU_TENSOR_MAP_DATA_TYPE_BFLOAT16, 2, d_out, dims, st, box, es, CU_TENSOR_MAP_INTERLEAVE_NONE, CU_TENSOR_MAP_SWIZZLE_NONE, CU_TENSOR_MAP_L2_PROMOTION_NONE, CU_TENSOR_MAP_FLOAT_OOB_FILL_NONE);
        enc(&tmX, CU_TENSOR_MAP_DATA_TYPE_BFLOAT16, 2, (void*)x, dims, st, box, es, CU_TENSOR_MAP_INTERLEAVE_NONE, CU_TENSOR_MAP_SWIZZLE_NONE, CU_TENSOR_MAP_L2_PROMOTION_NONE, CU_TENSOR_MAP_FLOAT_OOB_FILL_NONE);
    }
    {
        cuuint64_t dims[3] = {64, (cuuint64_t)S_, 9}; cuuint64_t st[2] = {(cuuint64_t)D_ * 2, 128}; cuuint32_t box[3] = {64, 128, 1};
        enc(&tmXA, CU_TENSOR_MAP_DATA_TYPE_BFLOAT16, 3, (void*)x, dims, st, box, es, CU_TENSOR_MAP_INTERLEAVE_NONE, CU_TENSOR_MAP_SWIZZLE_128B, CU_TENSOR_MAP_L2_PROMOTION_L2_128B, CU_TENSOR_MAP_FLOAT_OOB_FILL_NONE);
    }
    launch(k0_prep, dim3(9, 8, 4), 256, 0, false, x, wqkv, wphi);
    launch(ka_front, 132, 640, KA_SMEM, true, tmXA, x, wo, w1, b1);
    launch(k2_attn, 128, 288, K2_SMEM, true, tmX, b2);
    launch(k3_mix1, 132, 288, K3_SMEM, true, tmW1, tmW1b, b1, w1, w2);
    launch(k4_mix2, 132, 288, K4_SMEM, true, tmW2, tmOut);
}
```
